```python
import torch

def _softmax(x, axis=-1):
    return torch.softmax(x, dim=axis)

def _gelu(x):
    return torch.nn.functional.gelu(x, approximate='tanh')

def _silu(x):
    return torch.nn.functional.silu(x)

def _sigmoid(x):
    return torch.sigmoid(x)

def _layernorm(x, axis=-1, eps=1e-05):
    m = x.mean(dim=axis, keepdim=True)
    v = x.var(dim=axis, keepdim=True, unbiased=False)
    return (x - m) / torch.sqrt(v + eps)

def _scatter_add(tgt, idx, src, axis=0):
    return tgt.clone().index_add_(axis, idx, src)

def _segment_sum(src, seg, n):
    out = torch.zeros((n,) + src.shape[1:], dtype=src.dtype)
    return out.index_add_(0, seg, src)

def _pad(x, pw):
    flat = tuple((v for pair in reversed(pw) for v in pair))
    return torch.nn.functional.pad(x, flat)
kernel_name = 'gated_mix__ssm_conv_h3__memory_aug_recurrent_mem_tr__prompt'

def setup_inputs():

    _w = lambda a: (lambda t: t.to(torch.bfloat16) if t.is_floating_point() else t)(torch.as_tensor(a))

    def _A_setup():
        B, S, D = (1, 2048, 1024)
        ks = 4
        return {'q': _w((lambda *s: torch.randn(*s, dtype=torch.bfloat16) * 0.05)(B, S, D)), 'k': _w((lambda *s: torch.randn(*s, dtype=torch.bfloat16) * 0.4)(B, S, D)), 'v': _w((lambda *s: torch.randn(*s, dtype=torch.bfloat16) * 0.4)(B, S, D)), 'shift_k': _w((lambda *s: torch.randn(*s, dtype=torch.bfloat16) * 0.4)(D, ks) * 0.5), 'ssm_k': _w((lambda *s: torch.randn(*s, dtype=torch.bfloat16) * 0.4)(D, S) * (1.0 / S ** 0.5)), 'ssm_D': _w((lambda *s: torch.randn(*s, dtype=torch.bfloat16) * 0.4)(D))}
    _A_in = _A_setup()

    def _B_setup():
        B, S, Dm = (1, 2048, 1024)
        H, Dh = (32, 128)
        M, seg = (8, 32)
        seg = min(seg, S)
        S = S // seg * seg
        return {'x': _w((lambda *s: torch.randn(*s, dtype=torch.bfloat16) * 0.05)(B, S, Dm)), 'mem0': _w((lambda *s: torch.randn(*s, dtype=torch.bfloat16) * 0.4)(B, M, Dm)), 'Wq': _w((lambda *s: torch.randn(*s, dtype=torch.bfloat16) * 6.4)(Dm, H, Dh) * Dm ** (-0.5)), 'Wk': _w((lambda *s: torch.randn(*s, dtype=torch.bfloat16) * 6.4)(Dm, H, Dh) * Dm ** (-0.5)), 'Wv': _w((lambda *s: torch.randn(*s, dtype=torch.bfloat16) * 0.4)(Dm, H, Dh) * Dm ** (-0.5)), 'Wo': _w((lambda *s: torch.randn(*s, dtype=torch.bfloat16) * 0.4)(H, Dh, Dm) * (H * Dh) ** (-0.5)), 'seg_len': seg}
    _B_in = _B_setup()
    return {'A_q': _A_in['q'], 'A_k': _A_in['k'], 'A_v': _A_in['v'], 'A_shift_k': _A_in['shift_k'], 'A_ssm_k': _A_in['ssm_k'], 'A_ssm_D': _A_in['ssm_D'], 'B_x': _B_in['x'], 'B_mem0': _B_in['mem0'], 'B_Wq': _B_in['Wq'], 'B_Wk': _B_in['Wk'], 'B_Wv': _B_in['Wv'], 'B_Wo': _B_in['Wo'], 'B_seg_len': _B_in['seg_len'], 'gate_w': _w((lambda *s: torch.randn(*s, dtype=torch.bfloat16) * 0.05)(1024) * 16.0)}

def reference(A_q, A_k, A_v, A_shift_k, A_ssm_k, A_ssm_D, B_x, B_mem0, B_Wq, B_Wk, B_Wv, B_Wo, B_seg_len, gate_w):

    def _A_ref(q, k, v, shift_k, ssm_k, ssm_D):
        B, S, D = q.shape
        ks = shift_k.shape[-1]
        k_pad = _pad(k, ((0, 0), (ks - 1, 0), (0, 0)))
        k_shift = torch.zeros_like(k)
        for t in range(ks):
            k_shift = k_shift + k_pad[:, t:t + S, :] * shift_k[:, ks - 1 - t][None, None, :]
        kv = k_shift * v
        L = 2 * S
        kv_pad = _pad(kv, ((0, 0), (0, S), (0, 0)))
        kf_pad = _pad(ssm_k, ((0, 0), (0, S)))
        kv_f = (lambda x, axes=(-2, -1): torch.fft.rfft2(x.float(), dim=axes))(kv_pad[:, None, :, :], axes=(1, 2))
        kf_f = (lambda x, axes=(-2, -1): torch.fft.rfft2(x.float(), dim=axes))(kf_pad[:, None, :], axes=(1, 2))
        kf_f = (lambda x, *d: x.permute(*d))(kf_f, 1, 2, 0)
        y_f = kv_f * kf_f[None, :, :, :]
        y = (lambda x, s, axes=(-2, -1): torch.fft.irfft2(x, s=s, dim=axes).to(torch.bfloat16))(y_f, (1, L), axes=(1, 2))[:, 0, :S, :]
        y = y + kv * ssm_D[None, None, :]
        return q * y

    def _B_ref(x, mem0, Wq, Wk, Wv, Wo, seg_len):
        B, S, Dm = x.shape
        H, Dh = (Wq.shape[1], Wq.shape[2])
        M = mem0.shape[1]
        scale = Dh ** (-0.5)
        n_seg = S // seg_len
        L = M + seg_len
        idx = torch.arange(L)
        mask = (idx[:, None] < M) | (idx[:, None] >= idx[None, :])
        mem = mem0
        outs = []
        for s in range(n_seg):
            xs = x[:, s * seg_len:(s + 1) * seg_len, :].clone()
            h = torch.concatenate([mem, xs], axis=1)
            q = torch.einsum('btd,dhe->bhte', h, Wq)
            k = torch.einsum('btd,dhe->bhte', h, Wk)
            v = torch.einsum('btd,dhe->bhte', h, Wv)
            scores = torch.einsum('bhqe,bhke->bhqk', q, k) * scale
            scores = torch.where(mask[None, None], scores, -1000000000.0)
            p = _softmax(scores, axis=-1)
            o = torch.einsum('bhqk,bhke->bhqe', p, v)
            o = torch.einsum('bhte,hed->btd', o, Wo)
            mem = o[:, :M, :].clone()
            outs.append(o[:, M:, :])
        return torch.concatenate(outs, axis=1)
    x = A_q
    g = _sigmoid((x * gate_w).sum(-1, keepdims=True))
    a = _A_ref(x, A_k, A_v, A_shift_k, A_ssm_k, A_ssm_D)
    b = _B_ref(x, B_mem0, B_Wq, B_Wk, B_Wv, B_Wo, B_seg_len)
    return g * a + (1 - g) * b
```

```cpp
#include <cuda_runtime.h>
#include <cuda_bf16.h>
#include <cuda.h>
#include <stdint.h>

typedef __nv_bfloat16 bf16;

constexpr int SEQ = 2048, DM = 1024, NH = 32, DH = 128, NSEG = 64;
constexpr int SPIN_LIMIT = 1 << 13, NCTA = 132;
#define NPR 6
#define PDL 1
#define TPF 1

constexpr uint32_t HOME_BITS = 0xB3000;
constexpr uint32_t RB_R = 0;
constexpr uint32_t RB_B = 0x80000;
constexpr uint32_t RB_T = RB_B + 0x4000;
constexpr uint32_t RB_P = RB_B + 0x20000;
constexpr uint32_t RB_X = 2u << 20;
__device__ uint4 g_RB[(8 << 20) / 16];
__device__ uint32_t g_cls[160];
__device__ uint4 g_T[8 * NH * 1536];
__device__ uint4 g_O[NSEG * 4 * 4096];
__device__ uint4 g_A[SEQ * DM / 8];
__device__ float g_gate[SEQ];
__device__ uint32_t g_err;
#define TL(i)
#define TLX(i)

__device__ __forceinline__ uint32_t smem_u32(const void* p) { return (uint32_t)__cvta_generic_to_shared(p); }
__device__ __forceinline__ uint32_t clk() { uint32_t c; asm volatile("mov.u32 %0, %%clock;" : "=r"(c) :: "memory"); return c; }
__device__ __forceinline__ void ldsm4(uint32_t& r0, uint32_t& r1, uint32_t& r2, uint32_t& r3, uint32_t a) {
    asm volatile("ldmatrix.sync.aligned.m8n8.x4.shared.b16 {%0,%1,%2,%3}, [%4];" : "=r"(r0), "=r"(r1), "=r"(r2), "=r"(r3) : "r"(a) : "memory");
}
__device__ __forceinline__ void ldsm4t(uint32_t& r0, uint32_t& r1, uint32_t& r2, uint32_t& r3, uint32_t a) {
    asm volatile("ldmatrix.sync.aligned.m8n8.x4.trans.shared.b16 {%0,%1,%2,%3}, [%4];" : "=r"(r0), "=r"(r1), "=r"(r2), "=r"(r3) : "r"(a) : "memory");
}
__device__ __forceinline__ void ldsm2(uint32_t& r0, uint32_t& r1, uint32_t a) {
    asm volatile("ldmatrix.sync.aligned.m8n8.x2.shared.b16 {%0,%1}, [%2];" : "=r"(r0), "=r"(r1) : "r"(a) : "memory");
}
__device__ __forceinline__ void stsm4t(uint32_t a, uint32_t r0, uint32_t r1, uint32_t r2, uint32_t r3) {
    asm volatile("stmatrix.sync.aligned.m8n8.x4.trans.shared.b16 [%0], {%1,%2,%3,%4};" :: "r"(a), "r"(r0), "r"(r1), "r"(r2), "r"(r3) : "memory");
}
__device__ __forceinline__ void mma16(float* c, uint32_t a0, uint32_t a1, uint32_t a2, uint32_t a3, uint32_t b0, uint32_t b1) {
    asm volatile("mma.sync.aligned.m16n8k16.row.col.f32.bf16.bf16.f32 {%0,%1,%2,%3}, {%4,%5,%6,%7}, {%8,%9}, {%0,%1,%2,%3};"
        : "+f"(c[0]), "+f"(c[1]), "+f"(c[2]), "+f"(c[3]) : "r"(a0), "r"(a1), "r"(a2), "r"(a3), "r"(b0), "r"(b1));
}
__device__ __forceinline__ void mma8(float* c, uint32_t a0, uint32_t a1, uint32_t b0) {
    asm volatile("mma.sync.aligned.m16n8k8.row.col.f32.bf16.bf16.f32 {%0,%1,%2,%3}, {%4,%5}, {%6}, {%0,%1,%2,%3};"
        : "+f"(c[0]), "+f"(c[1]), "+f"(c[2]), "+f"(c[3]) : "r"(a0), "r"(a1), "r"(b0));
}
__device__ __forceinline__ uint32_t pack2(float lo, float hi) {
    uint32_t r; asm("cvt.rn.bf16x2.f32 %0, %1, %2;" : "=r"(r) : "f"(hi), "f"(lo)); return r;
}
__device__ __forceinline__ uint32_t hadd2(uint32_t a, uint32_t b) {
    uint32_t r; asm("add.rn.bf16x2 %0, %1, %2;" : "=r"(r) : "r"(a), "r"(b)); return r;
}
__device__ __forceinline__ float bflo(uint32_t w) { return __uint_as_float(w << 16); }
__device__ __forceinline__ float bfhi(uint32_t w) { return __uint_as_float(w & 0xFFFF0000u); }
__device__ __forceinline__ void st_g32(void* p, uint32_t v) { asm volatile("st.relaxed.gpu.global.u32 [%0], %1;" :: "l"(p), "r"(v) : "memory"); }
__device__ __forceinline__ void st_g128(void* p, uint32_t a, uint32_t b, uint32_t c, uint32_t d) {
    asm volatile("st.relaxed.gpu.global.v4.u32 [%0], {%1,%2,%3,%4};" :: "l"(p), "r"(a), "r"(b), "r"(c), "r"(d) : "memory");
}
__device__ __forceinline__ uint4 lds128(uint32_t a) { uint4 v; asm volatile("ld.shared.v4.u32 {%0,%1,%2,%3}, [%4];" : "=r"(v.x), "=r"(v.y), "=r"(v.z), "=r"(v.w) : "r"(a) : "memory"); return v; }
__device__ __forceinline__ void sts128(uint32_t a, uint4 v) { asm volatile("st.shared.v4.u32 [%0], {%1,%2,%3,%4};" :: "r"(a), "r"(v.x), "r"(v.y), "r"(v.z), "r"(v.w) : "memory"); }
__device__ __forceinline__ float2 lds64f(uint32_t a) { float2 v; asm volatile("ld.shared.v2.f32 {%0,%1}, [%2];" : "=f"(v.x), "=f"(v.y) : "r"(a) : "memory"); return v; }
__device__ __forceinline__ void sts64f(uint32_t a, float x, float y) { asm volatile("st.shared.v2.f32 [%0], {%1,%2};" :: "r"(a), "f"(x), "f"(y) : "memory"); }
__device__ __forceinline__ void sts32f(uint32_t a, float x) { asm volatile("st.shared.f32 [%0], %1;" :: "r"(a), "f"(x) : "memory"); }
__device__ __forceinline__ void sts32(uint32_t a, uint32_t x) { asm volatile("st.shared.u32 [%0], %1;" :: "r"(a), "r"(x) : "memory"); }
__device__ __forceinline__ uint32_t lds32(uint32_t a) { uint32_t v; asm volatile("ld.shared.u32 %0, [%1];" : "=r"(v) : "r"(a) : "memory"); return v; }
__device__ __forceinline__ void cpa16(uint32_t dst, const void* src) { asm volatile("cp.async.cg.shared.global [%0], [%1], 16;" :: "r"(dst), "l"(src) : "memory"); }
__device__ __forceinline__ void cpa_commit() { asm volatile("cp.async.commit_group;" ::: "memory"); }
__device__ __forceinline__ void cpa_wait() { asm volatile("cp.async.wait_all;" ::: "memory"); }
template <int ID, int N> __device__ __forceinline__ void bsync() { asm volatile("bar.sync %0, %1;" :: "n"(ID), "n"(N) : "memory"); }
template <int ID, int N> __device__ __forceinline__ void barrive() { asm volatile("bar.arrive %0, %1;" :: "n"(ID), "n"(N) : "memory"); }
template <int ID, int N> __device__ __forceinline__ void bsync_if(bool on) { asm volatile("{ .reg .pred p; setp.ne.b32 p, %2, 0; @p bar.sync %0, %1; }" :: "n"(ID), "n"(N), "r"((int)on) : "memory"); }
template <int ID, int N> __device__ __forceinline__ void barrive_if(bool on) { asm volatile("{ .reg .pred p; setp.ne.b32 p, %2, 0; @p bar.arrive %0, %1; }" :: "n"(ID), "n"(N), "r"((int)on) : "memory"); }
__device__ __forceinline__ void mbar_init(uint32_t mb, uint32_t n) { asm volatile("mbarrier.init.shared::cta.b64 [%0], %1;" :: "r"(mb), "r"(n) : "memory"); }
__device__ __forceinline__ void mbar_expect(uint32_t mb, uint32_t bytes) { asm volatile("mbarrier.arrive.expect_tx.shared::cta.b64 _, [%0], %1;" :: "r"(mb), "r"(bytes) : "memory"); }
__device__ __forceinline__ void mbar_arrive(uint32_t mb) { asm volatile("mbarrier.arrive.shared::cta.b64 _, [%0];" :: "r"(mb) : "memory"); }
__device__ __forceinline__ void mbar_wait(uint32_t mb, uint32_t ph) {
    asm volatile("{ .reg .pred p; .reg .u32 n; mov.u32 n, 0;\n"
                 "MW_%=: mbarrier.try_wait.parity.shared::cta.b64 p, [%0], %1; add.u32 n, n, 1; setp.lt.and.u32 p, n, %2, !p; @p bra.uni MW_%=; }"
                 :: "r"(mb), "r"(ph), "n"(SPIN_LIMIT) : "memory");
}
__device__ __forceinline__ void tma2d(uint32_t dst, const CUtensorMap* m, int c0, int c1, uint32_t mb) {
    asm volatile("cp.async.bulk.tensor.2d.shared::cluster.global.mbarrier::complete_tx::bytes [%0], [%1, {%3, %4}], [%2];"
        :: "r"(dst), "l"(m), "r"(mb), "r"(c0), "r"(c1) : "memory");
}
__device__ __forceinline__ void tma3d(uint32_t dst, const CUtensorMap* m, int c0, int c1, int c2, uint32_t mb) {
    asm volatile("cp.async.bulk.tensor.3d.shared::cluster.global.mbarrier::complete_tx::bytes [%0], [%1, {%3, %4, %5}], [%2];"
        :: "r"(dst), "l"(m), "r"(mb), "r"(c0), "r"(c1), "r"(c2) : "memory");
}
__device__ __forceinline__ void bulk_ld(uint32_t dst, const void* src, uint32_t bytes, uint32_t mb) {
    asm volatile("cp.async.bulk.shared::cluster.global.mbarrier::complete_tx::bytes [%0], [%1], %2, [%3];" :: "r"(dst), "l"(src), "r"(bytes), "r"(mb) : "memory");
}
__device__ __forceinline__ uint64_t mkdesc(uint32_t addr, uint32_t lbo, uint32_t sbo, uint32_t swz) {
    return (uint64_t)((addr & 0x3FFFF) >> 4) | ((uint64_t)(lbo >> 4) << 16) | ((uint64_t)(sbo >> 4) << 32) | ((uint64_t)swz << 62);
}
__device__ __forceinline__ void wg_fence() { asm volatile("wgmma.fence.sync.aligned;" ::: "memory"); }
__device__ __forceinline__ void wg_commit() { asm volatile("wgmma.commit_group.sync.aligned;" ::: "memory"); }
template <int N> __device__ __forceinline__ void wg_wait() { asm volatile("wgmma.wait_group.sync.aligned %0;" :: "n"(N) : "memory"); }
#define F4(d, o) "+f"(d[o]), "+f"(d[o + 1]), "+f"(d[o + 2]), "+f"(d[o + 3])
__device__ __forceinline__ void wgmma_n32_rs(float* d, const uint32_t* a, uint64_t db, int accum) {
    asm volatile("{.reg .pred p; setp.ne.b32 p, %21, 0;\n"
        "wgmma.mma_async.sync.aligned.m64n32k16.f32.bf16.bf16 {%0,%1,%2,%3,%4,%5,%6,%7,%8,%9,%10,%11,%12,%13,%14,%15}, {%16,%17,%18,%19}, %20, p, 1, 1, 0;}"
        : F4(d, 0), F4(d, 4), F4(d, 8), F4(d, 12) : "r"(a[0]), "r"(a[1]), "r"(a[2]), "r"(a[3]), "l"(db), "r"(accum));
}
__device__ __forceinline__ void wait_until(uint32_t tgt, uint32_t any) {
    asm volatile("{ .reg .pred p, q; .reg .u32 t; .reg .s32 d; mov.u32 t, %0; setp.ne.u32 q, %1, 0xFFFFFFFF;\n"
                 "WU_%=: @q mov.u32 t, %%clock; sub.s32 d, t, %0; setp.lt.s32 p, d, 0; @p bra.uni WU_%=; }" :: "r"(tgt), "r"(any) : "memory");
}

namespace mk {
constexpr uint32_t SB = 1024;
constexpr uint32_t WV = SB, WO = SB + 65536, XT = SB + 131072, TK = SB + 163840  , PB = TK + 24576, MEM = PB + 12288,
                   SC = MEM + 8192  , PT = SC + 6144,
                   OB = SC + 8192, SUM = OB + 2048, ANB = SUM + 512, BAR = ANB + 512, GRP = BAR + 128, PROFB = BAR + 192,
                   TOTAL = PROFB - SB;
static_assert(TOTAL <= 232448, "shared memory");
constexpr uint32_t MB_WQ = BAR, MB_WK = BAR + 8, MB_WV = BAR + 16, MB_WO = BAR + 24, MB_X = BAR + 32, MB_KV = BAR + 40, MB_R = BAR + 48, MB_B = BAR + 56, MB_P = BAR + 64;
constexpr uint32_t XT2 = WV, RS = WV + 32768, VE = RS + 4096;
enum { B_START = 1, B_H0, B_H2, B_H3, B_S1, B_SC, B_SC2, B_S0, B_O, B_O2, B_PT, B_GO, B_VX, B_RD, B_BT };
constexpr uint64_t XD0 = (uint64_t)(XT >> 4) | ((uint64_t)1 << 16) | ((uint64_t)64 << 32) | ((uint64_t)1 << 62);
constexpr uint32_t TSLOT = NH * 24576;
}
struct MainParams { int d[12]; uint32_t zero; char* rb; };
#define XD(i) (mk::XD0 - ((i) >> 5) * ((mk::XT - mk::XT2) >> 4) + (((i) & 31) >> 2) * 256 + ((i) & 3) * 2)
#define XD4(i) XD(i), XD(i + 1), XD(i + 2), XD(i + 3)
#define XD16(i) XD4(i), XD4(i + 4), XD4(i + 8), XD4(i + 12)
__constant__ __align__(256) uint64_t c_xd[64] = {XD16(0), XD16(16), XD16(32), XD16(48)};
#define CUT(r) asm volatile("{ .reg .pred q; setp.eq.u32 q, %1, 0xFFFFFFFF; @q mov.u32 %0, %%clock; }" : "+r"(r) : "r"(t16) : "memory")
__device__ __forceinline__ uint32_t opq(uint32_t x) { asm volatile("" : "+r"(x)); return x; }
__device__ __forceinline__ float opqf(float x) { asm volatile("" : "+f"(x)); return x; }
#define PROF(i)
#define PROFW(i, w)
#define TRC(i, v)
#define RETRY(i, on)
#define P(i) prm.d[i]
#define DELAY(n) do { if (n) { _Pragma("unroll") for (int i_ = 0; i_ < n; i_++) asm volatile("mad.lo.u32 %0, %0, %1, %0;" : "+r"(pb) : "r"(prm.zero)); CUT(pa); } } while (0)

__device__ __forceinline__ uint32_t tagw(uint32_t w, uint32_t tau) { return (w & ~1u) | tau; }
__device__ __forceinline__ uint32_t ld_g32(const void* p) { uint32_t v; asm volatile("ld.relaxed.gpu.global.u32 %0, [%1];" : "=r"(v) : "l"(p) : "memory"); return v; }
__device__ __forceinline__ void ld_g64(uint32_t* v, const void* p) { asm volatile("ld.relaxed.gpu.global.v2.u32 {%0,%1}, [%2];" : "=r"(v[0]), "=r"(v[1]) : "l"(p) : "memory"); }
__device__ __forceinline__ void ld_g128(uint32_t* v, const void* p) {
    asm volatile("ld.relaxed.gpu.global.v4.u32 {%0,%1,%2,%3}, [%4];" : "=r"(v[0]), "=r"(v[1]), "=r"(v[2]), "=r"(v[3]) : "l"(p) : "memory");
}
__device__ __forceinline__ void st_g64(void* p, uint32_t a, uint32_t b) { asm volatile("st.relaxed.gpu.global.v2.u32 [%0], {%1,%2};" :: "l"(p), "r"(a), "r"(b) : "memory"); }
__device__ __forceinline__ void lds128f(float* v, uint32_t a) { asm volatile("ld.shared.v4.f32 {%0,%1,%2,%3}, [%4];" : "=f"(v[0]), "=f"(v[1]), "=f"(v[2]), "=f"(v[3]) : "r"(a) : "memory"); }
__device__ __forceinline__ void sts128f(uint32_t a, float x, float y, float z, float w) { asm volatile("st.shared.v4.f32 [%0], {%1,%2,%3,%4};" :: "r"(a), "f"(x), "f"(y), "f"(z), "f"(w) : "memory"); }
__device__ __forceinline__ void stsm4(uint32_t a, uint32_t r0, uint32_t r1, uint32_t r2, uint32_t r3) {
    asm volatile("stmatrix.sync.aligned.m8n8.x4.shared.b16 [%0], {%1,%2,%3,%4};" :: "r"(a), "r"(r0), "r"(r1), "r"(r2), "r"(r3) : "memory");
}
__device__ __forceinline__ void mmaq(float* c, const uint32_t* a, uint32_t b0, uint32_t b1) { mma16(c, a[0], a[1], a[2], a[3], b0, b1); }
template <int LUT> __device__ __forceinline__ uint32_t lop3(uint32_t a, uint32_t b, uint32_t c) { uint32_t r; asm("lop3.b32 %0, %1, %2, %3, %4;" : "=r"(r) : "r"(a), "r"(b), "r"(c), "n"(LUT)); return r; }
template <int N, int S> __device__ __forceinline__ uint32_t stale(const uint32_t* x, uint32_t tau) {
    if constexpr (N == 2) return lop3<0x7E>(x[0], tau, x[S]);
    else if constexpr (N == 3) return lop3<0xF6>(stale<2, S>(x, tau), x[2 * S], tau);
    else if constexpr (N == 4 || N == 16) return lop3<0xFC>(stale<N / 2, S>(x, tau), stale<N / 2, S>(x + N / 2 * S, tau), 0);
    else return lop3<0xFE>(stale<3, S>(x, tau), stale<3, S>(x + 3 * S, tau), stale<2, S>(x + 6 * S, tau));
}
__device__ __forceinline__ uint32_t late(uint32_t a, uint32_t b, uint32_t mask) {
    uint32_t r;
    asm volatile("{ .reg .pred p; .reg .b32 t; lop3.b32 t, %1, %2, %3, 0xA8; setp.ne.b32 p, t, 0; vote.sync.any.pred p, p, 0xFFFFFFFF; selp.u32 %0, 1, 0, p; }" : "=r"(r) : "r"(a), "r"(b), "r"(mask));
    return r;
}
#define AGAIN(id, reload, ...) _Pragma("unroll 1") for (int n_ = 0; __builtin_expect(__VA_ARGS__, 0) && n_ < SPIN_LIMIT; n_++) { RETRY(id, 1); reload; }
__device__ __forceinline__ uint32_t tile_off(int lane, int chunk0) {
    return ((lane >> 4) * 8 + (lane & 7)) * 128 + (((chunk0 + ((lane >> 3) & 1)) ^ (lane & 7)) << 4);
}
template <int K0, int K1>
__device__ __forceinline__ void load_tile(uint32_t a, uint32_t* T) {
    #pragma unroll
    for (int ks = K0; ks < K1; ks++) ldsm4t(T[4 * ks], T[4 * ks + 1], T[4 * ks + 2], T[4 * ks + 3], a + ks * 2048);
}
__device__ __forceinline__ void lds128u(uint32_t* v, uint32_t a) { asm volatile("ld.shared.v4.u32 {%0,%1,%2,%3}, [%4];" : "=r"(v[0]), "=r"(v[1]), "=r"(v[2]), "=r"(v[3]) : "r"(a) : "memory"); }
template <int K0, int K1, int STRIDE = 4096>
__device__ __forceinline__ void load_frag(uint32_t a, uint32_t* T) {
    #pragma unroll
    for (int ks = K0; ks < K1; ks++) lds128u(&T[4 * ks], a + ks * STRIDE);
}
template <int L0, int L1, bool INIT = false>
__device__ __forceinline__ void wg_run(float* acc, const uint32_t* A, const uint64_t* d) {
    if (L1 > L0) {
        wg_fence();
        #pragma unroll
        for (int l = L0; l < L1; l++) wgmma_n32_rs(acc, &A[4 * l], d[l], INIT || l != 0);
        wg_commit();
    }
}
__device__ __forceinline__ void load_x(const CUtensorMap* tmX, int c, int seg, uint32_t dst, bool on) {
    asm volatile("{ .reg .pred p; elect.sync _|p, 0xFFFFFFFF; setp.ne.and.b32 p, %6, 0, p;\n"
        "@p mbarrier.arrive.expect_tx.shared::cta.b64 _, [%3], 32768;\n"
        "@p cp.async.bulk.tensor.3d.shared::cluster.global.mbarrier::complete_tx::bytes [%4], [%0, {%5, %1, %2}], [%3]; }"
        :: "l"(tmX), "r"(seg * 32), "r"((c & 1) * 8), "r"(mk::MB_X), "r"(dst), "r"(0), "r"((int)on) : "memory");
}
__device__ __forceinline__ void bulk_expect(uint32_t mb, uint32_t bytes) {
    asm volatile("{ .reg .pred p; elect.sync _|p, 0xFFFFFFFF; @p mbarrier.arrive.expect_tx.shared::cta.b64 _, [%0], %1; }" :: "r"(mb), "r"(bytes) : "memory");
}
__device__ __forceinline__ void bulk_copy(uint32_t dst, const void* src, uint32_t bytes, uint32_t mb) {
    asm volatile("{ .reg .pred p; elect.sync _|p, 0xFFFFFFFF; @p cp.async.bulk.shared::cluster.global.mbarrier::complete_tx::bytes [%0], [%1], %2, [%3]; }"
        :: "r"(dst), "l"(src), "r"(bytes), "r"(mb) : "memory");
    __syncwarp();
}
__device__ __forceinline__ void bulk_copy_if(bool on, uint32_t dst, const void* src, uint32_t bytes, uint32_t mb) {
    asm volatile("{ .reg .pred p; elect.sync _|p, 0xFFFFFFFF; setp.ne.and.b32 p, %4, 0, p; @p cp.async.bulk.shared::cluster.global.mbarrier::complete_tx::bytes [%0], [%1], %2, [%3]; }"
        :: "r"(dst), "l"(src), "r"(bytes), "r"(mb), "r"((int)on) : "memory");
    __syncwarp();
}
__device__ __forceinline__ void kv_expect(uint32_t bytes) { bulk_expect(mk::MB_KV, bytes); }
__device__ __forceinline__ void kv_copy(uint32_t dst, const void* src, uint32_t bytes) { bulk_copy(dst, src, bytes, mk::MB_KV); }
__device__ __forceinline__ uint32_t gtime() { uint32_t c; asm volatile("mov.u32 %0, %%globaltimer_lo;" : "=r"(c) :: "memory"); return c; }
__device__ __forceinline__ void wait_g(uint32_t tgt, uint32_t any) {
    asm volatile("{ .reg .pred p, q; .reg .u32 t; mov.u32 t, %0; setp.ne.u32 q, %1, 0xFFFFFFFF;\n"
                 "WG_%=: @q mov.u32 t, %%globaltimer_lo; sub.u32 t, t, %0; setp.gt.u32 p, t, 0xFFFF0000; @p bra.uni WG_%=; }" :: "r"(tgt), "r"(any) : "memory");
    __syncwarp();
}
__device__ __forceinline__ uint32_t clkv(uint32_t any) {
    uint32_t c; asm volatile("{ .reg .pred q; setp.ne.u32 q, %1, 0xFFFFFFFF; mov.u32 %0, 0; @q mov.u32 %0, %%clock; }" : "=r"(c) : "r"(any) : "memory"); return c;
}
__device__ __forceinline__ const char* kv_src(int c, int seg) { return (const char*)g_T + ((4 + (seg & 3)) * mk::TSLOT + (c >> 2) * 24576); }
__device__ __forceinline__ const char* pp_src(int c, int seg) { return (const char*)g_T + ((seg & 3) * mk::TSLOT + (c >> 1) * 12288); }
__device__ __forceinline__ void prefetch_l2(const void* p, uint32_t bytes) {
    asm volatile("{ .reg .pred p; elect.sync _|p, 0xFFFFFFFF; @p cp.async.bulk.prefetch.L2.global [%0], %1; }" :: "l"(p), "r"(bytes) : "memory");
}
__device__ __forceinline__ void refetch_kv(int c, int seg, uint32_t l16) {
    const char* src = kv_src(c, seg);
    #pragma unroll 1
    for (int i = 0; i < 48; i++) {
        uint32_t v[4];
        ld_g128(v, src + i * 512 + l16);
        sts128(mk::TK + i * 512 + l16, make_uint4(v[0], v[1], v[2], v[3]));
    }
    __syncwarp();
}
__device__ __forceinline__ uint32_t phase(int i) { return (~i >> 1) & 1; }
__device__ __forceinline__ uint32_t phase4(int i) { return (~i >> 2) & 1; }
__device__ __forceinline__ void qk_pack(const float* acc, uint32_t* p) {
    #pragma unroll
    for (int i = 0; i < 4; i++) { p[i] = pack2(acc[4 * i], acc[4 * i + 1]); p[4 + i] = pack2(acc[4 * i + 2], acc[4 * i + 3]); }
}
template <int N> __device__ __forceinline__ void add_part(const uint32_t* own, uint32_t* p, uint32_t tau) {
    #pragma unroll
    for (int i = 0; i < N; i++) { p[i] = hadd2(own[i], p[i]); if (!(i & 3)) p[i] = tagw(p[i], tau); }
}
__device__ __forceinline__ void sts128_if(bool on, uint32_t a, const uint32_t* p) {
    asm volatile("{ .reg .pred p; setp.ne.b32 p, %5, 0; @p st.shared.v4.u32 [%0], {%1,%2,%3,%4}; }" :: "r"(a), "r"(p[0]), "r"(p[1]), "r"(p[2]), "r"(p[3]), "r"((int)on) : "memory");
}
__device__ __forceinline__ void st_if(bool on, char* a, const uint32_t* p) {
    asm volatile("{ .reg .pred p; setp.ne.b32 p, %5, 0; @p st.relaxed.gpu.global.v4.u32 [%0], {%1,%2,%3,%4}; }" :: "l"(a), "r"(p[0]), "r"(p[1]), "r"(p[2]), "r"(p[3]), "r"((int)on) : "memory");
}
__device__ __forceinline__ char* tok_dst(int c, int seg) { return (char*)g_T + (((c & 1) * 4 + (seg & 3)) * mk::TSLOT + (c >> 1) * 12288); }
__device__ __forceinline__ void st_qk(bool on, int c, int seg, uint32_t ps, const uint32_t* p) { st_if(on, tok_dst(c, seg) + ps, p); st_if(on, tok_dst(c, seg) + (ps ^ 0x220), p + 4); }
__device__ __forceinline__ void acc_init(float* acc, const uint32_t* p) {
    #pragma unroll
    for (int i = 0; i < 4; i++) { acc[4 * i] = bflo(p[i]); acc[4 * i + 1] = bfhi(p[i]); acc[4 * i + 2] = bflo(p[4 + i]); acc[4 * i + 3] = bfhi(p[4 + i]); }
}
__device__ __forceinline__ void acc_add(float* acc, const uint32_t* p) {
    #pragma unroll
    for (int i = 0; i < 4; i++) { acc[4 * i] += bflo(p[i]); acc[4 * i + 1] += bfhi(p[i]); acc[4 * i + 2] += bflo(p[4 + i]); acc[4 * i + 3] += bfhi(p[4 + i]); }
}
__device__ __forceinline__ void pack_tag(const float* acc, uint32_t* p, uint32_t tau) { qk_pack(acc, p); p[0] = tagw(p[0], tau); p[4] = tagw(p[4], tau); }
constexpr uint32_t ONES = 0x3F803F80u;
__device__ __forceinline__ float rcpf(float x) { float r; asm("rcp.approx.ftz.f32 %0, %1;" : "=f"(r) : "f"(x)); return r; }

#define ANN 2
#define POL 101
#define R4 1
#define KVP (POL < 100 ? -1 : POL - 96)
#define LD7 8
#define XP 3
#define G2 0
#define NB 26
#define BD 8
#define NP 22
#define TA 4
#define TA0 2
#define NT 19
#define VH 1
#define TRIES 200
#define NPW 3
#define EV0 4
#define EV1 8
#define WA1 6
#define WA2 9
#define H2 12
#define QV 1
#define QD 0
#define KD 0
#define VD 0
#define WA0 4
#define ONE 0
#define PP 12
#define OBA 3
#define WA3 1
#define WB1 0
#define WB2 12
#define WB3 12
#define H0 10
#define H3 10
__device__ __forceinline__ uint32_t tagm(uint32_t w, uint32_t mask, uint32_t tau) { return lop3<0xB8>(w, mask, tau); }
__device__ __forceinline__ char* at(uint32_t lo, uint32_t hi) { char* p; asm("mov.b64 %0, {%1,%2};" : "=l"(p) : "r"(lo), "r"(hi)); return p; }
__device__ __forceinline__ float ex2(float x) { float r; asm("ex2.approx.ftz.f32 %0, %1;" : "=f"(r) : "f"(x)); return r; }
__device__ __forceinline__ float max8(const float* x) { return fmaxf(fmaxf(fmaxf(x[0], x[1]), fmaxf(x[2], x[3])), fmaxf(fmaxf(x[4], x[5]), fmaxf(x[6], x[7]))); }
__device__ __forceinline__ float max4lanes(float m) { return fmaxf(fmaxf(m, __shfl_xor_sync(~0u, m, 1)), fmaxf(__shfl_xor_sync(~0u, m, 2), __shfl_xor_sync(~0u, m, 3))); }
constexpr float SCL = 0.08838834764831845f * 1.4426950408889634f;
__device__ __forceinline__ void tok_scores(float* x, uint32_t sa) {
    float y[8];
    lds128f(x, sa); lds128f(y, sa + 1024); lds128f(x + 4, sa + 512); lds128f(y + 4, sa + 1536);
    #pragma unroll
    for (int i = 0; i < 8; i++) x[i] += y[i];
}
__device__ __forceinline__ void mem_scores(float* x, uint32_t sa) {
    float z[8];
    lds128f(z, sa + 2048); lds128f(z + 4, sa + 2560);
    x[8] = (z[0] + z[2]) + (z[4] + z[6]); x[9] = (z[1] + z[3]) + (z[5] + z[7]);
}

struct Ctx { uint32_t u_rs, u_rl, u_bs, u_bl, rblo, rbhi; int w8, c; };
template <int wg>
__device__ __forceinline__ void steps(uint32_t* W, uint32_t* T, uint32_t t16, uint32_t pa, uint32_t pb, const Ctx& cx, const CUtensorMap* tmX, const MainParams& prm) {
    using namespace mk;
    const int c = cx.c, kap = c & 1, w8 = cx.w8;
    const uint32_t rbhi = cx.rbhi;
    uint32_t u_rs = cx.u_rs, u_rl = cx.u_rl, u_bs = cx.u_bs, u_bl = cx.u_bl ^ ((c & 2) << 14);
    uint32_t u_x = cx.rblo + RB_X + (c >> 2) * 16384, u_xs = u_x + kap * 2048 + (c & 2) * 512;
    uint32_t u_ta = ((cx.u_bl & ~0x10000u) ^ (kap << 12)) + (RB_T - RB_B) + 1024 + (wg || POL < 100 ? 0 : w8 * 128);
    uint32_t u_rp = cx.rblo + RB_T + 1024 + c * 4;
    uint32_t u_og = (c & 3) * 65536 + (c >> 2) * 2048 + (w8 & 3) * 256;
    const uint32_t u_sa = (w8 & 2) * 256 + (w8 & 1) * 8, u_cq = ((w8 & 1) * 2 ^ (c & 3)) << 4;
    #define TOK_DST() tok_dst(c, seg)
    constexpr int EV = wg ? EV1 : EV0;
    constexpr uint32_t VEB = VE + (wg ? EV0 * 2048 - 2048 : 0) - (16 - EV) * 2048;
    static_assert((EV0 + EV1) * 2048 <= 28672, "");
    __syncthreads();
    #pragma unroll
    for (int i = 16 - EV; i < 16; i++) sts128(VEB + i * 2048 + t16, make_uint4(T[4 * i], T[4 * i + 1], T[4 * i + 2], T[4 * i + 3]));
    asm volatile("fence.proxy.async.shared::cta;" ::: "memory");
    if (wg) barrive<B_START, 256>();
    #pragma unroll 1
    for (int s = 0, bc = 0, redo = 0;;) {
        bc = opq(bc + 1);
        t16 |= prm.zero & bc;
        const int seg = s + 3 - kap;
        const uint32_t tau = phase(s), tau2 = phase4(s) * 0x10001u;
        const uint32_t l16 = opq(t16 & 0x1F0);
        uint32_t F[64];
        float ot[3][2][4];
        #define LDB(i) ldsm4t(b[i][0], b[i][1], b[i][2], b[i][3], MEM + l16 + (i) * 512)
        #define ST_X() do { char* xs = at(u_xs + (pb >> 16), rbhi) + wg * 4096; \
            st_g32(xs, tagm(pack2((a[0][0] + a[1][0]) + (a[2][0] + a[3][0]), (a[0][2] + a[1][2]) + (a[2][2] + a[3][2])), mG, tau * 0x10001u)); \
            st_g32(xs + 32, tagm(pack2((a[0][1] + a[1][1]) + (a[2][1] + a[3][1]), (a[0][3] + a[1][3]) + (a[2][3] + a[3][3])), mG, tau * 0x10001u)); } while (0)
        #define ST_V() st_g64(at(u_xs + (t16 >> 1), rbhi) + (8192 + wg * 3072), \
            tagm(pack2((v[0][0] + v[1][0]) + (v[2][0] + v[3][0]), (v[0][1] + v[1][1]) + (v[2][1] + v[3][1])), mT, tau), \
            pack2((v[0][2] + v[1][2]) + (v[2][2] + v[3][2]), (v[0][3] + v[1][3]) + (v[2][3] + v[3][3])))
        #define V_MMA(i, o) do { mmaq(v[2 * ((i) & 1)], &T[8 * (i)], b[(o) + (i)][0], b[(o) + (i)][1]); mmaq(v[2 * ((i) & 1) + 1], &T[8 * (i) + 4], b[(o) + (i)][2], b[(o) + (i)][3]); } while (0)
        #define ST_R(i) do { \
                const uint32_t r0 = pack2((r[i][0][0] + r[i][1][0]) * i0, (r[i][0][1] + r[i][1][1]) * i1); \
                const uint32_t r1 = pack2((r[i][0][2] + r[i][1][2]) * i0, (r[i][0][3] + r[i][1][3]) * i1); \
                st_g64(at(ra ^ (i * 0x3000), rbhi), tagm(r0, mT, tau), r1); } while (0)
        #define LD_OB(i) ldsm4t(ob[4 * (i)], ob[4 * (i) + 1], ob[4 * (i) + 2], ob[4 * (i) + 3], OB + l16 + (i) * 512)
        #define WO_MMA(have, more, mid, tail) uint32_t ob[16], ra; float r[2][2][4] = {}; \
            LD_OB(0); __syncwarp(); LD_OB(1); __syncwarp(); if (OBA > 2) { LD_OB(2); __syncwarp(); } \
            _Pragma("unroll") for (int i = have; i < have + more; i++) { lds128u(&F[4 * i], WO + t16 + i * 4096); __syncwarp(); } \
            _Pragma("unroll") for (int i = 0; i < 16; i++) { \
                if (!(i & 1) || (i > 4 && i < 8)) CUT(pb); \
                if (i == 4) LD_OB(OBA); \
                if (i == 5 && OBA == 2) LD_OB(3); \
                { const int n = have + more + i - 8 + OBA; if (i >= 8 - OBA && n < 16) lds128u(&F[4 * n], WO + t16 + n * 4096); } \
                if (wg == 0 && i == 4) { const float2 su = lds64f(SUM + (l16 >> 1)); i0 = su.x; i1 = su.y; } \
                mmaq(r[(i >> 1) & 1][i & 1], &F[4 * i], ob[(i >> 2) * 4 + 2 * (i & 1)], ob[(i >> 2) * 4 + 2 * (i & 1) + 1]); \
                if (wg && i == 2) { i0 = opqf(rcpf(i0)); i1 = opqf(rcpf(i1)); } \
                if (i == PP) { mid; } \
                if (!wg && i == POL - 100) bulk_copy(ANB + w8 * 128, at(u_ta, rbhi), 128, MB_P); \
                if (!wg && i == KVP) bulk_copy(TK + w8 * 6144, kv_src(c, s + 1) + w8 * 6144, 6144, MB_KV); \
                if (i == 12) ra = opq(lop3<0x6A>((l16 >> 1) * 33, 0x1078, u_rs)); } \
            CUT(pb); tail; \
            if (!wg) { i0 = rcpf(i0); i1 = rcpf(i1); } \
            ST_R(0); ST_R(1)
        #define LD_X(r, o) do { ld_g64(r, xa + (o)); ld_g64(r + 2, xa + ((o) + 2048)); ld_g64(r + 4, xa + ((o) + 1024)); ld_g64(r + 6, xa + ((o) + 3072)); } while (0)
        #define REPORT(w, add) asm volatile("{ .reg .pred p; .reg .u32 t; setp.lt.u32 p, %1, 32; mov.u32 t, %1; @p mov.u32 t, %%globaltimer_lo; add.u32 t, t, %3; lop3.b32 t, t, 31, %2, 0xB8; @p st.relaxed.gpu.global.u32 [%0], t; }" \
            :: "l"(at(u_rp + (l16 << 8), rbhi)), "r"(t16 - (w) * 512), "r"(s), "r"(add) : "memory")
        #define CK() opq(t16 * 2 + ((l16 >> 4) & 0x1C))
        #define CHK_B(ck, tp, par) do { mbar_wait(MB_B, (par) & 1); \
            const uint32_t c0 = lds32(MEM - 4096 + ck), c1 = lds32(MEM + ck); barrive<B_START, 256>(); CUT(pa); \
            asm volatile("st.shared.u8 [%0], %1;" :: "r"(SUM + 252 + w8), "r"(late(lop3<0x7E>(c0, tp, c1), 0, bc < SPIN_LIMIT)) : "memory"); } while (0)
        #define GET_B(sl) do { const uint32_t a_ = u_bl ^ (sl); bulk_copy(MEM, at(a_, rbhi), 4096, MB_B); bulk_copy(MEM + 4096, at(a_ ^ 0x3000, rbhi), 4096, MB_B); } while (0)
        if constexpr (wg == 0) {
            float a[4][4], v[4][4] = {};
            uint32_t b[16][4];
            barrive_if<B_RD, 256>(redo);
            CUT(pa);
            bsync<B_START, 256>();
            LDB(8); __syncwarp(); LDB(9); __syncwarp(); LDB(10); __syncwarp(); LDB(11);
            PROF(0);
            #pragma unroll
            for (int n = 0; n < 16; n++) {
                const int i = n ^ 8;
                if (!(n & 1)) {
                    CUT(pa);
                    if (n == H0 + 2) { redo = lds32(SUM + 256 + opq(t16 >> 16)); __syncwarp(); }
                    if (n < 12) { LDB((n + 4) ^ 8); __syncwarp(); LDB((n + 5) ^ 8); __syncwarp(); }
                    if (n == H0) { bsync<B_H0, 256>(); CUT(pa); }
                }
                if (n < 2) { a[2 * n][0] = a[2 * n][1] = a[2 * n][2] = a[2 * n][3] = a[2 * n + 1][0] = a[2 * n + 1][1] = a[2 * n + 1][2] = a[2 * n + 1][3] = 0.f; }
                mmaq(a[2 * (i & 1)], &W[8 * i], b[i][0], b[i][1]); mmaq(a[2 * (i & 1) + 1], &W[8 * i + 4], b[i][2], b[i][3]);
            }
            CUT(pa);
            redo = late(redo, 0, ~0u);
            if (__builtin_expect(redo, 0)) { __syncwarp(); continue; }
            const uint32_t mG = (l16 & 0x1C0) ? 0 : 0x10001u, mT = (l16 & 0x30) ? 0 : 1;
            ST_X();
            CUT(pa);
            PROF(1);
            const char* const xa = at(u_x + (t16 >> 1), rbhi);
            float sc[4][4];
            uint32_t k[8], A[16], q[16], kf[16], qt[8];
            #define LD_Q() do { LD_X(q, 0); { const char* const xa = at((u_x + (opq(t16) >> 1)) ^ 256, rbhi); LD_X(q + 8, 0); } } while (0)
            #define LD_K() do { const uint32_t ka = opq(pa), kb = opq(ka ^ 0x400); \
                _Pragma("unroll") for (int i = 0; i < 4; i++) ldsm4t(kf[4 * i], kf[4 * i + 1], kf[4 * i + 2], kf[4 * i + 3], TK + 4096 + opq(((i & 1) ? kb : ka) ^ ((i >> 1) << 4))); \
                ldsm4t(qt[0], qt[1], qt[2], qt[3], TK + opq(ka ^ u_cq)); ldsm4t(qt[4], qt[5], qt[6], qt[7], TK + opq(kb ^ u_cq)); } while (0)
            #define USE_K() do { badk = opq(lop3<0xA8>(stale<8, 1>(kf, tau2), stale<8, 1>(qt, tau2), mG)); \
                _Pragma("unroll") for (int i = 0; i < 8; i++) A[2 * i + 1] = opq(qt[i] ^ prm.zero); } while (0)
            uint32_t badk;
            #pragma unroll
            for (int i = 7; i >= 0; i--) V_MMA(i, 0);
            if (QV) ST_V();
            CUT(pb);
            DELAY(QD);
            LD_Q();
            CUT(pb);
            if (!QV) { ST_V(); CUT(pb); }
            bsync<B_H2, 256>();
            LD_K();
            USE_K();
            CUT(pb);
            bsync<B_H3, 256>();
            LD_X(k, 4096);
            CUT(pb);
            PROF(3);
            AGAIN(1, if (late(badk, 0, ~0u)) { RETRY(0, 1); refetch_kv(c, s, l16 | (opq(n_) >> 24)); LD_K(); USE_K(); } LD_Q(); LD_X(k, 4096); sts32(SUM + 268, s + 1),
                  late(lop3<0xA8>(stale<4, 2>(q, tau), stale<4, 2>(q + 8, tau), mT), badk, ~0u))
            #pragma unroll
            for (int i = 0; i < 4; i++) {
                A[4 * i] = hadd2(q[4 * i], q[4 * i + 2]); A[4 * i + 2] = hadd2(q[4 * i + 1], q[4 * i + 3]);
                if (i < 2) { sc[i][0] = sc[i][1] = sc[i][2] = sc[i][3] = sc[2 + i][0] = sc[2 + i][1] = sc[2 + i][2] = sc[2 + i][3] = 0.f; }
                mmaq(sc[i & 1], A + 4 * i, kf[2 * i], kf[2 * i + 1]); mmaq(sc[2 + (i & 1)], A + 4 * i, kf[8 + 2 * i], kf[9 + 2 * i]);
            }
            sts128f(SC + t16, sc[0][0] + sc[1][0], sc[0][1] + sc[1][1], sc[2][0] + sc[3][0], sc[2][1] + sc[3][1]);
            barrive<B_S1, 256>();
            sts128f(SC + 3072 + t16, sc[0][2] + sc[1][2], sc[0][3] + sc[1][3], sc[2][2] + sc[3][2], sc[2][3] + sc[3][3]);
            load_frag<0, WB1>(WO + t16, F);
            const uint32_t sa = opq(l16 + u_sa);
            CUT(pb);
            PROF(4);
            float d[16];
            #pragma unroll 1
            for (int n_ = 0;; n_++) {
                #pragma unroll
                for (int i = 0; i < 4; i++) { d[4 * i] = d[4 * i + 1] = d[4 * i + 2] = d[4 * i + 3] = 0.f; mmaq(d + 4 * i, A + 4 * (i >> 1), k[2 * i], k[2 * i + 1]); }
                if (__builtin_expect(!late(stale<2, 2>(k, tau), stale<2, 2>(k + 4, tau), mT), 1) || n_ >= SPIN_LIMIT) break;
                RETRY(2, 1);
                LD_X(k, 4096);
            }
            sts64f(SC + 2048 + sa, (d[0] + d[4]) + (d[8] + d[12]), (d[1] + d[5]) + (d[9] + d[13]));
            barrive<B_SC, 256>();
            CUT(pb);
            sts64f(SC + 5120 + sa, (d[2] + d[6]) + (d[10] + d[14]), (d[3] + d[7]) + (d[11] + d[15]));
            PROF(5);
            if (w8 == 0) {
                float x[10];
                bsync<B_S0, 128>();
                tok_scores(x, SC + 3072 + l16); mem_scores(x, SC + 3072 + l16);
                __syncwarp();
                load_frag<WB1, WB2>(WO + t16, F);
                const int g = l16 >> 6, lim = 8 * (g >> 1) + 2 * (c & 3) + (g & 1) - ((l16 >> 1) & 0x18);
                #pragma unroll
                for (int i = 0; i < 8; i++) if (i > lim) x[i] = -INFINITY;
                const float ms = opqf(-SCL * max4lanes(fmaxf(max8(x), fmaxf(x[8], x[9]))));
                CUT(pb);
                #pragma unroll
                for (int i = 0; i < 10; i++) x[i] = ex2(fmaf(x[i], SCL, ms));
                load_frag<WB2, WB3>(WO + t16, F);
                sts128(PT + l16, make_uint4(pack2(x[0], x[1]), pack2(x[2], x[3]), pack2(x[4], x[5]), pack2(x[6], x[7])));
                sts32(PT + 512 + (l16 >> 2), pack2(x[8], x[9]));
                if (!ONE) barrive<B_PT, 160>();
            } else {
                if (ANN == 2) { bsync<B_S0, 128>(); const uint32_t f = lds32(SUM + 268 + opq(t16 >> 16)); REPORT(3, f == s + 1 ? P(2) : 0); } else barrive<B_S0, 128>();
                if (w8 == 1) { if (seg < NSEG) mbar_wait(MB_X, seg & 1); }
                else if (w8 == 2) {
                    const bool pp = kap && seg < NSEG;
                    bulk_expect(MB_P, pp ? 12800 : 512);
                    if (pp) bulk_copy(PB, pp_src(c, seg), 12288, MB_P);
                    bulk_expect(MB_B, 8192); bulk_expect(MB_R, 4096); bulk_expect(MB_KV, 24576);
                    __syncwarp();
                }
                bsync<B_SC2, 224>();
                load_frag<WB1, WB1 + 1>(WO + t16, F);
                if (ANN == 0) REPORT(3, 0);
                load_frag<WB1 + 1, WB3>(WO + t16, F);
                __syncwarp();
                if (POL < 100 && w8 == 3) {
                    DELAY(POL);
                    bulk_copy(ANB, at(u_ta, rbhi), 512, MB_P);
                    bulk_copy(TK, kv_src(c, s + 1), 24576, MB_KV);
                }
                if (XP == 0) load_x(tmX, c, seg + 1, (s & 1) ? XT : XT2, w8 == 3 && seg + 1 < NSEG);
                CUT(pb);
            }
            bsync<B_O2, 256>();
            PROF(6);
            float i0, i1;
            WO_MMA(WB3, 0, , );
        } else {
            float a[4][4], v[4][4] = {};
            uint32_t b[16][4];
            if (__builtin_expect(redo, 0)) {
                RETRY(6, 1);
                bsync<B_RD, 256>();
                if (w8 == 4) { bulk_expect(MB_B, 8192); GET_B(1 << 20); }
                const uint32_t ck = CK();
                CHK_B(ck, phase(s - 1), bc);
            }
            CUT(pa);
            bsync<B_H0, 256>();
            LDB(0); __syncwarp(); LDB(1); __syncwarp(); LDB(2); __syncwarp(); LDB(3); __syncwarp();
            redo = lds32(SUM + 256 + opq(t16 >> 16));
            PROF(0);
            #pragma unroll
            for (int i = 0; i < 16; i++) {
                if (!(i & 1)) {
                    CUT(pa);
                    if (i == 6) redo = late(redo, 0, ~0u);
                    if (i == H2) { barrive_if<B_H2, 256>(!redo); CUT(pa); }
                    if (i < 12) { LDB(i + 4); __syncwarp(); LDB(i + 5); __syncwarp(); }
                }
                if (i < 2) { a[2 * i][0] = a[2 * i][1] = a[2 * i][2] = a[2 * i][3] = a[2 * i + 1][0] = a[2 * i + 1][1] = a[2 * i + 1][2] = a[2 * i + 1][3] = 0.f; }
                mmaq(a[2 * (i & 1)], &W[8 * i], b[i][0], b[i][1]); mmaq(a[2 * (i & 1) + 1], &W[8 * i + 4], b[i][2], b[i][3]);
            }
            if (__builtin_expect(redo, 0)) { __syncwarp(); continue; }
            if (H3 == 0) { barrive<B_H3, 256>(); CUT(pb); }
            const uint32_t mG = (l16 & 0x1C0) ? 0 : 0x10001u, mT = (l16 & 0x30) ? 0 : 1;
            ST_X();
            if (H3 == 1) barrive<B_H3, 256>();
            CUT(pa);
            PROF(1);
            #pragma unroll
            for (int i = 7; i >= 0; i--) { V_MMA(i, 8); if (H3 == 9 - i) { CUT(pb); barrive<B_H3, 256>(); CUT(pb); } }
            ST_V();
            CUT(pb);
            if (H3 == 10) { DELAY(KD); barrive<B_H3, 256>(); CUT(pb); DELAY(6); }
            PROF(2);
            uint32_t vf[16], vm[16];
            const uint32_t va = opq(pa), vb = opq(va ^ 0x20);
            #define LD_V() do { _Pragma("unroll") for (int i = 0; i < 4; i++) ldsm4(vf[4 * i], vf[4 * i + 1], vf[4 * i + 2], vf[4 * i + 3], TK + 8192 + ((i & 1) ? vb : va) + (i >> 1) * 12288); } while (0)
            LD_V();
            __syncwarp();
            load_frag<0, WA0>(WO + t16, F);
            AGAIN(0, refetch_kv(c, s, l16 | (opq(n_) >> 24)); LD_V(), late(stale<4, 4>(vf, tau2), stale<4, 4>(vf + 1, tau2), mT))
            const char* const xa = at(u_x + (t16 >> 1), rbhi) + (8192 - 1024);
            DELAY(VD);
            LD_X(vm, 0); LD_X(vm + 8, 4096);
            __syncwarp();
            load_frag<WA0, WA1>(WO + t16, F);
            CUT(pb);
            float x[10];
            bsync<B_S1, 256>();
            const uint32_t qlate = lds32(SUM + 268 + opq(t16 >> 16));
            tok_scores(x, SC + l16);
            const float mt = opqf(max8(x));
            if (ANN == 3) REPORT(7, 0);
            CUT(pb);
            if (__builtin_expect(!late(qlate ^ (s + 1), 0, ~0u), 0)) {
                const char* const xa = at(u_x + (opq(t16) >> 1), rbhi) + (8192 - 1024);
                AGAIN(3, LD_X(vm, 0); LD_X(vm + 8, 4096), late(stale<4, 2>(vm, tau), stale<4, 2>(vm + 8, tau), mT))
            }
            PROF(3);
            bsync<B_SC, 256>();
            mem_scores(x, SC + l16);
            const float m1 = fmaxf(mt, fmaxf(x[8], x[9]));
            const float m2 = __shfl_xor_sync(~0u, m1, 1), m3 = __shfl_xor_sync(~0u, m1, 2), m4 = __shfl_xor_sync(~0u, m1, 3);
            CUT(pb);
            load_frag<WA1, WA2>(WO + t16, F);
            barrive<B_SC2, 224>();
            uint32_t p[5], vs[4];
            #define SUM_V() do { _Pragma("unroll") for (int i = 0; i < 4; i++) { const int e = (i >> 1) * 4 + (i & 1); vs[i] = hadd2(hadd2(vm[e], vm[e + 8]), hadd2(vm[e + 2], vm[e + 10])); } } while (0)
            CUT(pb);
            const float ms = -SCL * fmaxf(fmaxf(m1, m2), fmaxf(m3, m4));
            PROF(5);
            #pragma unroll
            for (int i = 0; i < 10; i++) x[i] = fmaf(x[i], SCL, ms);
            x[8] = opqf(ex2(x[8])); x[9] = opqf(ex2(x[9]));
            CUT(pb);
            uint32_t badv = late(stale<4, 2>(vm, tau), stale<4, 2>(vm + 8, tau), mT);
            SUM_V();
            #pragma unroll
            for (int i = 0; i < 4; i++) { x[i] = opqf(ex2(x[i])); vs[i] = opq(vs[i]); }
            const uint32_t z0 = t16 >> 16;
            uint32_t one[4] = {opq(ONES | z0), opq(ONES ^ z0), opq(ONES + z0), opq(ONES - z0)};
            CUT(pb);
            #pragma unroll
            for (int i = 4; i < 8; i++) x[i] = ex2(x[i]);
            #pragma unroll
            for (int i = 0; i < 5; i++) p[i] = pack2(x[2 * i], x[2 * i + 1]);
            float sm[4] = {};
            #define PV(also) do { float o[8] = {}; \
                mma8(o, vs[0], vs[1], p[4]); mma8(o + 4, vs[2], vs[3], p[4]); if (also) mma8(sm, one[0], one[1], p[4]); \
                mmaq(o, vf, p[0], p[1]); mmaq(o + 4, vf + 8, p[0], p[1]); if (also) mmaq(sm, one, p[0], p[1]); \
                mmaq(o, vf + 4, p[2], p[3]); mmaq(o + 4, vf + 12, p[2], p[3]); if (also) mmaq(sm, one, p[2], p[3]); \
                stsm4(OB - 2048 + opq(t16), pack2(o[0], o[1]), pack2(o[2], o[3]), pack2(o[4], o[5]), pack2(o[6], o[7])); } while (0)
            PV(true);
            if (w8 == 4) sts64f(SUM + (l16 >> 1), sm[0], sm[1]);
            if (__builtin_expect(badv, 0)) {
                int n_ = 0;
                uint32_t vm[16];
                const char* const xa = at(u_x + (8192 - 1024) + (opq(t16) >> 1), rbhi);
                do { RETRY(3, 1); LD_X(vm, 0); LD_X(vm + 8, 4096); } while (late(stale<4, 2>(vm, tau), stale<4, 2>(vm + 8, tau), mT) && ++n_ < SPIN_LIMIT);
                SUM_V();
                PV(false);
            }
            if (ONE) bsync<B_O2, 256>(); else { barrive<B_O2, 256>(); bsync<B_O, 128>(); }
            PROF(6);
            float i0 = sm[0], i1 = sm[1];
            #define GET_P() if (!ONE) bsync<B_PT, 160>(); lds128u(p, PT + l16); p[4] = lds32(PT + 512 + (l16 >> 2))
            #define TOK_PV() { const uint32_t z = t16 >> 17; one[0] = ONES | z; one[1] = ONES ^ z; one[2] = ONES + z; one[3] = ONES - z; } \
                _Pragma("unroll") for (int i = 0; i < 12; i++) ot[i >> 2][0][i & 3] = ot[i >> 2][1][i & 3] = 0.f; \
                mma8(ot[0][0], vs[0], vs[1], p[4]); mma8(ot[1][0], vs[2], vs[3], p[4]); mma8(ot[2][0], one[0], one[1], p[4]); \
                mmaq(ot[0][1], vf + 4, p[2], p[3]); mmaq(ot[1][1], vf + 12, p[2], p[3]); mmaq(ot[2][1], one, p[2], p[3]); CUT(pa)
            WO_MMA(WA2, WA3, GET_P(), TOK_PV());
            CUT(pa);
            mmaq(ot[0][0], vf, p[0], p[1]); mmaq(ot[1][0], vf + 8, p[0], p[1]); mmaq(ot[2][0], one, p[0], p[1]);
            CUT(pb);
            barrive<B_GO, 256>();
        }
        CUT(pb);
        PROF(7);
        #define PK_O() const float j0 = rcpf(ot[2][0][0] + ot[2][1][0]), j1 = rcpf(ot[2][0][1] + ot[2][1][1]); uint32_t ow[4]; \
            _Pragma("unroll") for (int i = 0; i < 4; i++) \
                ow[i] = opq(pack2((ot[i >> 1][0][2 * (i & 1)] + ot[i >> 1][1][2 * (i & 1)]) * j0, (ot[i >> 1][0][2 * (i & 1) + 1] + ot[i >> 1][1][2 * (i & 1) + 1]) * j1))
        #define ST_O() do { uint32_t* og = (uint32_t*)((char*)g_O + (u_og + (l16 >> 2))); \
            _Pragma("unroll") for (int i = 0; i < 4; i++) og[(i >> 1) * 256 + (i & 1) * 32] = ow[i]; } while (0)
        #define BSO() ((u_bs) ^ ((l16 & 0x10) + ((l16 >> 3) & 0xC) + (l16 & 0x80) * 0x20 + (l16 & 0x100) * 0x80))
        const bool pp = kap && seg < NSEG;
        const uint32_t taus = phase4(seg);
        const uint64_t* const dq = c_xd + (s & 1) * 32; const uint64_t* const dv = dq + (wg * 16 | (prm.zero & s));
        float acc[16], acv[16];
        uint32_t u[8], pq[8];
        #define LD_P(r, o) do { lds128u(r, PB + (o) + ps); lds128u(r + 4, PB + (o) + ps2); } while (0)
        #define RE_P(r, o) do { ld_g128(r, pp_src(c, seg) + (o) + ps); ld_g128(r + 4, pp_src(c, seg) + (o) + ps2); } while (0)
        if constexpr (wg == 0) {
            if (s == NSEG - 1) { bsync<B_GO, 256>(); st_g32(at(BSO(), rbhi), 0); mbar_wait(MB_KV, 0); break; }
            load_frag<16 - EV, 16, 2048>(VEB + t16, T);
            bsync<B_GO, 256>();
            PROF(8);
            wg_run<0, 16 - EV>(acv, T, dv);
            wg_run<16 - EV, 16>(acv, T, dv);
            wg_run<0, 5>(acc, W, dq); wg_wait<1>();
            qk_pack(acv, u);
            #pragma unroll
            for (int i = 0; i < 8; i++) u[i] = opq(u[i]);
            CUT(pa);
            wg_run<5, 8>(acc, W, dq);
            __syncwarp();
            sts128(SC + opq(t16), make_uint4(u[0], u[1], u[2], u[3])); sts128(SC + 2048 + opq(t16), make_uint4(u[4], u[5], u[6], u[7]));
            barrive<B_VX, 256>();
            __syncwarp();
            PROF(9);
            wg_run<8, 14>(acc, W, dq);
            CUT(pa);
            char* const bs = at(opq(BSO()), opq(rbhi));
            CUT(pa);
            wg_run<14, 20>(acc, W, dq);
            CUT(pa);
            const uint32_t ro = opq(l16 * 8 + ((l16 & 0x70) ^ ((w8 & 3) << 5))), ro2 = opq(ro ^ 0x10);
            const uint32_t mG = opq((l16 & 0x1C0) ? 0 : 0x10001u), mB = opq((((l16 >> 2) & 4) + ((l16 >> 5) & 3)) == ((u_bs >> 7) & 7) ? 1 : 0), zz = t16 >> 18;
            CUT(pa);
            wg_run<20, 26>(acc, W, dq);
            CUT(pa);
            const uint32_t one[4] = {opq(ONES | zz), opq(ONES ^ zz), opq(ONES + zz), opq(ONES - zz)};
            const uint32_t ps = opq(pb & 0xFFFF), ps2 = opq(ps ^ 0x220);
            CUT(pa);
            wg_run<26, 32>(acc, W, dq);
            CUT(pa);
            PROF(10);
            mbar_wait(MB_R, s & 1);
            PROF(14);
            uint32_t tb;
            #pragma unroll 1
            for (int n_ = 0;; n_++) {
                uint32_t x[8];
                float d[4][4] = {};
                ldsm4t(x[0], x[1], x[2], x[3], RS + ro); ldsm4t(x[4], x[5], x[6], x[7], RS + ro2);
                tb = lds32(SUM + 272 + 28 + zz);
                #pragma unroll
                for (int i = 0; i < 4; i++) mmaq(d[i], one, x[2 * i], x[2 * i + 1]);
                if (G2 == 0) barrive_if<B_BT, 256>(n_ == 0);
                const uint32_t p = late(stale<2, 1>(x, tau * 0x10001u), stale<2, 1>(x + 2, tau * 0x10001u), mG);
                const uint32_t w0 = pack2(d[0][0] + d[1][0], d[0][1] + d[1][1]), w1 = pack2(d[2][0] + d[3][0], d[2][1] + d[3][1]);
                asm volatile("{ .reg .pred p; setp.eq.b32 p, %2, 0; @p st.relaxed.gpu.global.u32 [%0], %1; }" :: "l"(bs), "r"(tagm((l16 & 0x40) ? w1 : w0, mB, tau)), "r"(p) : "memory");
                if (G2 == 1) barrive_if<B_BT, 256>(!p || n_ >= SPIN_LIMIT);
                if (__builtin_expect(!p, 1) || n_ >= SPIN_LIMIT) break;
                RETRY(5, 1);
                ld_g128(u, at(u_rl + ro, rbhi)); ld_g128(u + 4, at(u_rl + ro2, rbhi));
                sts128(RS + ro, make_uint4(u[0], u[1], u[2], u[3])); sts128(RS + ro2, make_uint4(u[4], u[5], u[6], u[7]));
                __syncwarp();
            }
            PROF(11);
            if (w8 == 3) {
                TRC(13, gtime() - tb);
                wait_g(tb, t16);
                GET_B(0);
                PROFW(13, 3);
            } else mbar_wait(MB_KV, ~s & 1);
            mbar_wait(MB_P, s & 1);
            LD_P(pq, 0);
            wg_wait<0>();
            qk_pack(acc, u);
            AGAIN(4, RE_P(pq, 0), late(stale<2, 4>(pq, taus), 0, pp))
            char* const qd0 = TOK_DST() + ps; char* const qd1 = TOK_DST() + ps2;
            add_part<8>(u, pq, taus);
            #pragma unroll
            for (int i = 0; i < 8; i++) pq[i] = opq(pq[i]);
            CUT(pa);
            bsync<B_S0, 128>();
            st_if(seg < NSEG, qd0, pq); st_if(seg < NSEG, qd1, pq + 4);
            if (XP == 1) load_x(tmX, c, seg + 1, (s & 1) ? XT : XT2, w8 == 1 && seg + 1 < NSEG);
            PROF(12);
        } else {
            const uint32_t ps = opq(pb & 0xFFFF), ps2 = opq(ps ^ 0x220);
            mbar_wait(MB_P, s & 1);
            if (w8 == 7 && s < NSEG - 1) {
                uint32_t a[4];
                lds128u(a, ANB + l16);
                #define LAST() __reduce_max_sync(~0u, max(max(a[0], a[1]), max(a[2], a[3])))
                uint32_t tr = LAST();
                AGAIN(8, ld_g128(a, at(u_ta + l16, rbhi)); tr = LAST(), late(stale<2, 1>(a, s), stale<2, 1>(a + 2, s), 31))
                tr = (tr & ~31u) + P(0);
                sts32(SUM + 272 + 28, tr + P(1));
                LD_P(pq, 0); LD_P(u, 4096);
                TRC(14, gtime() - tr);
                wait_g(tr, t16);
                if (R4) { for (int i = 0; i < 4; i++) bulk_copy(RS + i * 1024, at(u_rl + i * 1024, rbhi), 1024, MB_R); }
                else bulk_copy(RS, at(u_rl, rbhi), 4096, MB_R);
                PROFW(14, 3);
                if (XP == 3) load_x(tmX, c, seg + 1, (s & 1) ? XT : XT2, seg + 1 < NSEG);
            } else { DELAY(LD7); LD_P(pq, 0); LD_P(u, 4096); }
            CUT(pa);
            PK_O();
            CUT(pa);
            if (s == NSEG - 1) { ST_O(); break; }
            PROF(8);
            AGAIN(4, RE_P(pq, 0); RE_P(u, 4096), late(stale<2, 4>(pq, taus), stale<2, 4>(u, taus), pp))
            load_frag<16 - EV, 16 - EV + TA0, 2048>(VEB + t16, T);
            acc_init(acc, pq);
            #pragma unroll
            for (int i = 0; i < 16; i++) acc[i] = opqf(acc[i]);
            CUT(pa);
            bsync<B_VX, 256>();
            lds128u(pq, SC - 2048 + opq(t16)); lds128u(pq + 4, SC + opq(t16));
            CUT(pa);
            ST_O();
            CUT(pa);
            load_frag<16 - EV + TA0, 16 - EV + TA, 2048>(VEB + t16, T);
            if (VH) {
                #pragma unroll
                for (int i = 0; i < 8; i++) u[i] = hadd2(u[i], pq[i]);
                acc_init(acv, u);
            } else { acc_init(acv, u); acc_add(acv, pq); }
            #pragma unroll
            for (int i = 0; i < 16; i++) acv[i] = opqf(acv[i]);
            CUT(pa);
            PROF(9);
            bsync<B_BT, 256>();
            CUT(pa);
            wg_run<0, 3, true>(acc, W, dq);
            PROF(11);
            wg_run<3, NT, true>(acc, W, dq);
            __syncwarp();
            load_frag<16 - EV + TA, 16, 2048>(VEB + t16, T);
            __syncwarp();
            wg_run<NT, NB>(acc, W, dq);
            char* const qd0 = TOK_DST() + ps; char* const qd1 = TOK_DST() + ps2;
            const uint32_t ck = CK();
            wg_run<NB, 32>(acc, W, dq);
            wg_run<0, 5, true>(acv, T, dv);
            wg_wait<1>();
            PROF(12);
            pack_tag(acc, u, taus);
            #pragma unroll
            for (int i = 0; i < 8; i++) u[i] = opq(u[i]);
            CUT(pa);
            wg_run<5, 16 - EV>(acv, T, dv);
            __syncwarp();
            st_if(seg < NSEG, qd0, u); st_if(seg < NSEG, qd1, u + 4);
            __syncwarp();
            wg_run<16 - EV, 16>(acv, T, dv);
            CUT(pa);
            CHK_B(ck, tau, ~bc);
            CUT(pa);
            wg_wait<0>();
            PROF(13);
            pack_tag(acv, u, taus);
            if (XP == 2) load_x(tmX, c, seg + 1, (s & 1) ? XT : XT2, w8 == 5 && seg + 1 < NSEG);
            st_if(seg < NSEG, qd0 + 4096, u); st_if(seg < NSEG, qd1 + 4096, u + 4);
        }
        s++;
        u_rs ^= 1 << 20; u_rl ^= 1 << 20; u_bs ^= 1 << 20; u_bl ^= 1 << 20; u_x ^= 1 << 20; u_xs ^= 1 << 20; u_ta ^= 1 << 20; u_rp ^= 1 << 20; u_og += 262144;
    }
}

__device__ __forceinline__ uint32_t round_trips(char* line, int n) {
    uint32_t best[2] = {0xFFFFu, 0xFFFFu};
    #pragma unroll 1
    for (int i = 0; i < n; i++) {
        uint32_t v; const uint32_t t0 = clk();
        asm volatile("atom.relaxed.gpu.global.exch.b32 %0, [%1], %2;" : "=r"(v) : "l"(line + (i & 1) * 4096), "r"(i) : "memory");
        if (v == 0x7FC1A5A5u) g_err = 2;
        const uint32_t dt = clk() - t0;
        if (i & 1) best[1] = min(best[1], dt); else best[0] = min(best[0], dt);
    }
    return (__popc((uint32_t)(uintptr_t)line & HOME_BITS) & 1) ? best[1] | best[0] << 16 : best[0] | best[1] << 16;
}
__device__ __forceinline__ int role(char* rb) {
    const int b = blockIdx.x, t = threadIdx.x;
    if (!(t & 31)) { const int i = b * 8 + (t >> 5); sts32(mk::SUM + (t >> 3), round_trips(rb + RB_P + (i & 31) * 128 + (i >> 5) * 8192, NPR)); }
    __syncthreads();
    if (t == 0) {
        const uint4 x = lds128(mk::SUM), y = lds128(mk::SUM + 16);
        const uint32_t m = __vminu2(__vminu2(__vminu2(x.x, x.y), __vminu2(x.z, x.w)), __vminu2(__vminu2(y.x, y.y), __vminu2(y.z, y.w)));
        uint32_t sm; asm volatile("mov.u32 %0, %%smid;" : "=r"(sm));
        const uint32_t g = sm < 64 ? (sm & 15) >> 1 : 1 + (sm - 64) % 14 / 2, i = sm < 64 ? sm >> 4 : 4 + (sm - 64) / 14;
        const uint32_t pos = sm < 120 ? g * 16 + i * 2 + (sm & 1) : sm + 8;
        st_g32(g_cls + b, 0x80000000u | (m >> 16 < (m & 0xFFFF)) << 24 | pos << 8 | b);
    }
    uint32_t e = ~0u, own;
    int n = 0;
    do { own = ld_g32(g_cls + b); if (t < NCTA) e = ld_g32(g_cls + t); } while (!((e & own) >> 31) && ++n < SPIN_LIMIT);
    const int below = __syncthreads_count(e < own), n0 = __syncthreads_count(!(e >> 24 & 1));
    const int c0 = 4 * min(max(16, 32 - (NCTA - n0) / 4), n0 / 4);
    return below < c0 ? below : below < n0 ? 128 + below - c0 : below - n0 + c0 < 128 ? below - n0 + c0 : below;
}

__global__ void __launch_bounds__(256, 1)
main_kernel(const __grid_constant__ CUtensorMap tmWq, const __grid_constant__ CUtensorMap tmWk, const __grid_constant__ CUtensorMap tmWv,
            const __grid_constant__ CUtensorMap tmWo, const __grid_constant__ CUtensorMap tmX, const bf16* __restrict__ mem0,
            const bf16* Wo, const __grid_constant__ MainParams prm) {
    using namespace mk;
    extern __shared__ __align__(1024) uint8_t smem_raw[];
    if (smem_u32(smem_raw) != SB) __trap();
    TL(2);
    const int tid0 = threadIdx.x, w8 = __shfl_sync(~0u, tid0 >> 5, 0), wg = w8 >> 2;
    asm volatile("griddepcontrol.wait;" ::: "memory");
    const int c = __shfl_sync(~0u, role(prm.rb), 0), kap = c & 1;
    if (c >= 128) return;
    if (tid0 == 0) {
        for (int i = 0; i < 9; i++) mbar_init(BAR + i * 8, 1);
        sts32(BAR + 120, 0); sts32(SUM + 256, 0); sts32(SUM + 264, TRIES); sts32(SUM + 268, 0);
        asm volatile("fence.mbarrier_init.release.cluster;" ::: "memory");
        asm volatile("fence.proxy.async.shared::cta;" ::: "memory");
        const int col = (c >> 1) * 64, k0 = kap * 512;
        mbar_expect(MB_WQ, 65536); tma2d(WO, &tmWq, col, k0, MB_WQ); tma2d(WO + 32768, &tmWq, col, k0 + 256, MB_WQ);
        mbar_expect(MB_WK, 65536); tma2d(WV, &tmWk, col, k0, MB_WK); tma2d(WV + 32768, &tmWk, col, k0 + 256, MB_WK);
    }
    __syncwarp();
    load_x(&tmX, c, 0, XT, w8 == 0);
    for (int i = tid0; i < 4096; i += 256) {
        const int row = i >> 9, col = i & 511;
        const unsigned short v = __bfloat16_as_ushort(mem0[row * DM + kap * 512 + col]);
        asm volatile("st.shared.u16 [%0], %1;" :: "r"(MEM + col * 16 + row * 2), "h"(v) : "memory");
    }
    for (int i = 0; i < 3; i++) sts128(PB + i * 4096 + tid0 * 16, make_uint4(0, 0, 0, 0));
    asm volatile("fence.proxy.async.shared::cta;" ::: "memory");
    __syncthreads();
    uint32_t W[128], T[64];
    mbar_wait(wg ? MB_WK : MB_WQ, 0);
    load_tile<0, 32>(tile_off(tid0 & 31, 2 * (w8 & 3)) + (wg ? WV : WO), W);
    __syncthreads();
    if (tid0 == 0) {
        mbar_expect(MB_WV, 65536); tma2d(WV, &tmWv, (c >> 1) * 64, kap * 512, MB_WV); tma2d(WV + 32768, &tmWv, (c >> 1) * 64, kap * 512 + 256, MB_WV);
        mbar_expect(MB_WO, 65536);
        for (int i = 0; i < 4; i++) tma2d(WO + i * 16384, &tmWo, (c & 3) * 256 + i * 64, (c >> 2) * DH, MB_WO);
    }
    asm volatile("griddepcontrol.launch_dependents;" ::: "memory");
    uint32_t t16 = tid0 * 16, pa, pb;
    {
        const int lane = tid0 & 31, w = w8 & 3, g = lane >> 2, t = lane & 3;
        auto vec = [](int hf, int gg, int ch) { return hf * 512 + (gg >> 1) * 128 + (gg & 1) * 64 + ((ch ^ (gg >> 1) ^ (hf << 1)) << 4); };
        const int kg = ((lane >> 3) & 1) * 4 + ((lane & 7) >> 1);
        pa = ((lane >> 4) * 12288 + w * 1024 + vec(lane & 1, kg, 2 * (w & 1)))
             | (w * 1024 + vec((lane >> 3) & 1, lane & 7, lane >> 4)) << 16;
        pb = (w8 * 1024 + vec(0, g, t)) | (w * 256 + t * 64 + (g & 3) * 8 + (g >> 2) * 4) << 16;
    }
    mbar_wait(MB_WV, 0);
    load_tile<0, 16>(tile_off(tid0 & 31, 2 * (w8 & 3)) + wg * 32768 + WV, T);
    __syncthreads();
    #pragma unroll
    for (int i = 0; i < 16; i++) sts128(WV + i * 4096 + t16, make_uint4(T[4 * i], T[4 * i + 1], T[4 * i + 2], T[4 * i + 3]));
    int budget = SPIN_LIMIT;
    #pragma unroll 1
    for (int seg = 0; seg < 3 - kap; seg++) {
        const uint32_t tau = phase4(seg), ps = pb & 0xFFFF;
        float acc[16], acv[16];
        uint32_t u[8];
        mbar_wait(MB_X, seg & 1);
        wg_run<0, 32>(acc, W, c_xd + (prm.zero & seg));
        wg_run<0, 16>(acv, T, c_xd + (wg * 16 | (prm.zero & (seg + 1))));
        wg_wait<0>();
        if (!wg) { qk_pack(acv, u); sts128(SC + t16, make_uint4(u[0], u[1], u[2], u[3])); sts128(SC + 2048 + t16, make_uint4(u[4], u[5], u[6], u[7])); }
        __syncthreads();
        load_x(&tmX, c, seg + 1, XT, w8 == 0);
        if (wg) { lds128u(u, SC - 2048 + t16); lds128u(u + 4, SC + t16); acc_add(acv, u); }
        #pragma unroll 1
        for (int m = 0; m <= wg; m++) {
            if (kap) {
                const char* src = pp_src(c, seg) + m * 4096;
                do { ld_g128(u, src + ps); ld_g128(u + 4, src + (ps ^ 0x220)); } while (late(stale<2, 4>(u, tau), 0, 1) && --budget > 0);
                acc_add(acc, u);
            }
            pack_tag(acc, u, tau);
            st_qk(true, c, seg, ps + m * 4096, u);
            #pragma unroll
            for (int i = 0; i < 16; i++) acc[i] = acv[i];
        }
        __syncthreads();
    }
    {
        mbar_wait(MB_WO, 0);
        const int lane = tid0 & 31;
        const uint32_t a = (tid0 >> 6) * 16384 + tile_off(lane, (w8 & 1) * 4) + WO;
        #pragma unroll
        for (int i = 0; i < 16; i++) ldsm4t(T[4 * i], T[4 * i + 1], T[4 * i + 2], T[4 * i + 3], ((i & 2) ? a ^ 32 : a) + ((i >> 2) + 4 * (i & 1)) * 2048);
        __syncthreads();
        const uint32_t d = WO + w8 * 512 + ((lane >> 3) * 4 + (lane & 3)) * 16 + ((lane >> 2) & 1) * 4;
        #pragma unroll
        for (int i = 0; i < 64; i++) sts32(d + (i >> 2) * 4096 + (i & 1) * 256 + (i & 2) * 4, T[i]);
        load_frag<0, 16>(WV + t16, T);
    }
    uint32_t u_rs, u_rl, u_bs, u_bl;
    const uint32_t rbhi = (uint32_t)((uintptr_t)prm.rb >> 32);
    {
        const int lane = tid0 & 31, h = c >> 2, j = c & 3;
        uint32_t cl;
        const int G = h >> 4, rk = h & 15;
        auto half = [&](uint32_t off) { return (uint32_t)(uintptr_t)prm.rb + off + ((__popc(off & HOME_BITS) ^ G) & 1) * 4096; };
        auto rpair = [&](int m) { return RB_R + (j << 16) + ((m & 1) << 13) + (((m >> 1) & 3) << 14) + ((m >> 3) << 18); };
        u_rs = (half(rpair(2 * w8)) ^ (G << 12)) + h * 128 + (h & 7) * 16;
        u_rl = half(rpair(rk));
        u_bs = (uint32_t)(uintptr_t)prm.rb + RB_B + ((j & 1) << 13) + ((j >> 1) << 16) + rk * 256 + G * 128 + (w8 & 3) * 32;
        u_bl = half(RB_B + (kap << 16));
        if (w8 == 0) {
            do cl = ld_g32(kv_src(c, 0) + 8192 + lane * 128) & ld_g32(kv_src(c, 0) + 20480 + lane * 128); while (__any_sync(~0u, !(cl & 1)) && --budget > 0);
            kv_expect(24576); kv_copy(TK, kv_src(c, 0), 24576);
        }
    }
    mbar_wait(MB_KV, 0);
    asm volatile("fence.proxy.async.shared::cta;" ::: "memory");
    TLX(7);
    __syncwarp();
    const Ctx cx = {u_rs, u_rl, u_bs, u_bl, (uint32_t)(uintptr_t)prm.rb, rbhi, w8, c};
    if (wg) steps<1>(W, T, t16, pa >> 16, pb, cx, &tmX, prm); else steps<0>(W, T, t16, pa & 0xFFFF, pb, cx, &tmX, prm);
    TLX(3);
}

namespace ck {
constexpr uint32_t U = 0;
constexpr uint32_t UPL = 136 * 16 + 64;
constexpr uint32_t UCH = 2 * UPL;
constexpr uint32_t F = 8 * UCH;
constexpr uint32_t FCP = 4160;
constexpr uint32_t FCH = 2 * FCP;
constexpr uint32_t SK = F + 8 * FCH;
constexpr uint32_t SKP = 257 * 16;
constexpr uint32_t SV = SK + 8 * SKP;
constexpr uint32_t SQ = SV + 32768;
constexpr uint32_t TOTAL = SQ + 32768;
}
__global__ void __launch_bounds__(288, 1)
conv_kernel(const bf16* __restrict__ q, const bf16* __restrict__ k, const bf16* __restrict__ v, const bf16* __restrict__ shift_k,
            const bf16* __restrict__ ssm_k, const bf16* __restrict__ ssm_D, const bf16* __restrict__ gate_w,
            const bf16* Wq, const bf16* Wk, const bf16* Wv, const bf16* Wo,
            const __grid_constant__ CUtensorMap tmWq, const __grid_constant__ CUtensorMap tmWk, const __grid_constant__ CUtensorMap tmWv,
            const __grid_constant__ CUtensorMap tmWo, char* rb) {
    using namespace ck;
    extern __shared__ uint8_t smem_raw[];
    const uint32_t sb = smem_u32(smem_raw);
    const int tid = threadIdx.x, w = tid >> 5, lane = tid & 31, c = blockIdx.x;
    TL(0);
    const int d0 = c * 8, t0 = tid * 8;
    if (w == 8) {
        bsync<1, 288>();
        if (lane < 10) {
            const CUtensorMap* m = lane < 2 ? &tmWq : lane < 4 ? &tmWk : lane < 6 ? &tmWv : &tmWo;
            const int c0 = lane < 6 ? (c >> 1) * 64 : (c & 3) * 256 + (lane - 6) * 64, c1 = lane < 6 ? (c & 1) * 512 + (lane & 1) * 256 : (c >> 2) * DH;
            asm volatile("cp.async.bulk.prefetch.tensor.2d.L2.global [%0, {%1, %2}];" :: "l"(m), "r"(c0), "r"(c1) : "memory");
        }
        return;
    }
    #pragma unroll
    for (int i = 0; i < 8; i++) {
        cpa16(sb + SK + i * SKP + (tid + 1) * 16, k + (size_t)(t0 + i) * DM + d0);
        cpa16(sb + SV + i * 4096 + tid * 16, v + (size_t)(t0 + i) * DM + d0);
    }
    cpa_commit();
    #pragma unroll
    for (int i = 0; i < 8; i++) cpa16(sb + SQ + i * 4096 + tid * 16, q + (size_t)(t0 + i) * DM + d0);
    cpa_commit();
    uint4 fx[8], gw[4], x0[4], x1[4], skr[4];
    const uint4* fp = (const uint4*)(ssm_k + (size_t)(d0 + w) * SEQ);
    #pragma unroll
    for (int i = 0; i < 8; i++) fx[i] = fp[lane + 32 * i];
    const int gr = c * 16 + w * 2;
    #pragma unroll
    for (int i = 0; i < 4; i++) {
        gw[i] = ((const uint4*)gate_w)[lane + 32 * i];
        x0[i] = ((const uint4*)(q + (size_t)gr * DM))[lane + 32 * i];
        x1[i] = ((const uint4*)(q + (size_t)(gr + 1) * DM))[lane + 32 * i];
        skr[i] = ((const uint4*)(shift_k + d0 * 4))[i];
    }
    if (c == 0 && tid < 160) g_cls[tid] = 0;
    if (tid < 128) sts128(sb + U + (tid >> 4) * UCH + ((tid >> 3) & 1) * UPL + (tid & 7) * 16, make_uint4(0, 0, 0, 0));
    else if (tid < 136) sts128(sb + SK + (tid & 7) * SKP, make_uint4(0, 0, 0, 0));
    {
        const uint32_t fb = sb + F + w * FCH;
        if (lane < 8) { sts32(fb + 4128 + lane * 4, 0); if (lane) sts32(fb + FCP + 4128 + lane * 4, 0); }
        #pragma unroll
        for (int i = 0; i < 8; i++) {
            const int vi = lane + 32 * i;
            const uint4 x = fx[i];
            const uint32_t a = __shfl_down_sync(~0u, x.x, 1), b = __shfl_sync(~0u, i < 7 ? fx[i < 7 ? i + 1 : 7].x : 0u, 0);
            const uint32_t nxt = lane == 31 ? b : a;
            const uint32_t ea = fb + (2056 - 8 * vi) * 2;
            sts128(ea, make_uint4(__byte_perm(x.w, 0, 0x1032), __byte_perm(x.z, 0, 0x1032), __byte_perm(x.y, 0, 0x1032), __byte_perm(x.x, 0, 0x1032)));
            sts128(ea + FCP, make_uint4(__byte_perm(nxt, x.w, 0x7610), __byte_perm(x.w, x.z, 0x7610), __byte_perm(x.z, x.y, 0x7610), __byte_perm(x.y, x.x, 0x7610)));
            if (vi == 0) sts32(fb + FCP + 4128, x.x & 0xFFFFu);
        }
    }
    {
        float a0 = 0.f, a1 = 0.f;
        #pragma unroll
        for (int i = 0; i < 16; i++) {
            const uint32_t gg = ((const uint32_t*)gw)[i], u0 = ((const uint32_t*)x0)[i], u1 = ((const uint32_t*)x1)[i];
            a0 = fmaf(bflo(u0), bflo(gg), fmaf(bfhi(u0), bfhi(gg), a0));
            a1 = fmaf(bflo(u1), bflo(gg), fmaf(bfhi(u1), bfhi(gg), a1));
        }
        #pragma unroll
        for (int o = 16; o; o >>= 1) { a0 += __shfl_xor_sync(~0u, a0, o); a1 += __shfl_xor_sync(~0u, a1, o); }
        if (lane < 2) g_gate[gr + lane] = 1.f / (1.f + __expf(lane ? -a1 : -a0));
    }
    cpa_wait();
    bsync<1, 288>();
    TLX(14);
    const uint4 dd = *(const uint4*)(ssm_D + d0);
    {
        uint4 kr[11], vr[8];
        #pragma unroll
        for (int i = 0; i < 11; i++) kr[i] = lds128(sb + SK + ((i + 5) & 7) * SKP + (tid + (i >= 3)) * 16);
        #pragma unroll
        for (int i = 0; i < 8; i++) vr[i] = lds128(sb + SV + i * 4096 + tid * 16);
        #pragma unroll
        for (int ch = 0; ch < 8; ch++) {
            const uint32_t s01 = ((const uint32_t*)skr)[2 * ch], s23 = ((const uint32_t*)skr)[2 * ch + 1];
            const float sk[4] = {bflo(s01), bfhi(s01), bflo(s23), bfhi(s23)};
            float kf[11], kv[8];
            #pragma unroll
            for (int i = 0; i < 11; i++) { const uint32_t wd = ((const uint32_t*)&kr[i])[ch >> 1]; kf[i] = (ch & 1) ? bfhi(wd) : bflo(wd); }
            #pragma unroll
            for (int i = 0; i < 8; i++) {
                const uint32_t wv = ((const uint32_t*)&vr[i])[ch >> 1];
                kv[i] = fmaf(kf[i + 3], sk[0], fmaf(kf[i + 2], sk[1], fmaf(kf[i + 1], sk[2], kf[i] * sk[3]))) * ((ch & 1) ? bfhi(wv) : bflo(wv));
            }
            sts128(sb + U + ch * UCH + (tid & 1) * UPL + (8 + (tid >> 1)) * 16,
                   make_uint4(pack2(kv[0], kv[1]), pack2(kv[2], kv[3]), pack2(kv[4], kv[5]), pack2(kv[6], kv[7])));
        }
    }
    bsync<2, 256>();
    TL(9);
    {
        const int g = lane >> 2, t = lane & 3;
        float acc[16][4];
        #pragma unroll
        for (int i = 0; i < 16; i++) acc[i][0] = acc[i][1] = acc[i][2] = acc[i][3] = 0.f;
        const uint32_t fa = sb + F + w * FCH + ((g & 1) ? (2063 - g + 2 * t) * 2 : FCP + (2064 - g + 2 * t) * 2);
        const uint32_t ua = sb + U + w * UCH + ((lane >> 3) & 1) * UPL + (8 + (lane >> 4) * 8 + (lane & 7)) * 16;
        #pragma unroll 1
        for (int r = 0; r < 8; r++) {
            uint32_t Fr[32];
            #pragma unroll
            for (int m = 0; m < 8; m++) ldsm4(Fr[4 * m], Fr[4 * m + 1], Fr[4 * m + 2], Fr[4 * m + 3], ua - r * 16 + m * 256);
            #pragma unroll
            for (int qq = 0; qq < 16; qq++) {
                const uint32_t o = fa - r * 32 - qq * 256;
                const uint32_t f0 = lds32(o), fp8 = lds32(o - 16), fm8 = lds32(o + 16);
                #pragma unroll
                for (int nt = qq; nt < 16; nt++) mma16(acc[nt], f0, fp8, fm8, f0, Fr[2 * (nt - qq)], Fr[2 * (nt - qq) + 1]);
            }
        }
        __syncwarp();
        const uint32_t ya = sb + F + w * FCH + ((lane >> 3) & 1) * 2048 + ((lane >> 4) * 8 + (lane & 7)) * 16;
        #pragma unroll
        for (int nt = 0; nt < 16; nt += 2)
            stsm4t(ya + nt * 128, pack2(acc[nt][0], acc[nt][1]), pack2(acc[nt][2], acc[nt][3]), pack2(acc[nt + 1][0], acc[nt + 1][1]), pack2(acc[nt + 1][2], acc[nt + 1][3]));
    }
    TL(11);
    bsync<2, 256>();
    {
        uint32_t outw[8][4];
        uint4 qr[8];
        #pragma unroll
        for (int i = 0; i < 8; i++) qr[i] = lds128(sb + SQ + i * 4096 + tid * 16);
        #pragma unroll
        for (int cp = 0; cp < 4; cp++) {
            const uint4 y0 = lds128(sb + F + (2 * cp) * FCH + (tid & 1) * 2048 + (tid >> 1) * 16), y1 = lds128(sb + F + (2 * cp + 1) * FCH + (tid & 1) * 2048 + (tid >> 1) * 16);
            const uint4 u0 = lds128(sb + U + (2 * cp) * UCH + (tid & 1) * UPL + (8 + (tid >> 1)) * 16), u1 = lds128(sb + U + (2 * cp + 1) * UCH + (tid & 1) * UPL + (8 + (tid >> 1)) * 16);
            const uint32_t dw = ((const uint32_t*)&dd)[cp];
            const float D0 = bflo(dw), D1 = bfhi(dw);
            #pragma unroll
            for (int i = 0; i < 8; i++) {
                const uint32_t a0 = ((const uint32_t*)&y0)[i >> 1], a1 = ((const uint32_t*)&y1)[i >> 1], b0 = ((const uint32_t*)&u0)[i >> 1], b1 = ((const uint32_t*)&u1)[i >> 1];
                const float yy0 = fmaf((i & 1) ? bfhi(b0) : bflo(b0), D0, (i & 1) ? bfhi(a0) : bflo(a0));
                const float yy1 = fmaf((i & 1) ? bfhi(b1) : bflo(b1), D1, (i & 1) ? bfhi(a1) : bflo(a1));
                const uint32_t qw = ((const uint32_t*)&qr[i])[cp];
                outw[i][cp] = pack2(bflo(qw) * yy0, bfhi(qw) * yy1);
            }
        }
        #pragma unroll
        for (int i = 0; i < 8; i++) g_A[c * 2048 + i * 256 + tid] = make_uint4(outw[i][0], outw[i][1], outw[i][2], outw[i][3]);
    }
    TL(1);
}

namespace ok {
constexpr int STAGES = 4;
constexpr uint32_t STG = 49152, TOTAL = STAGES * STG + 32768 + 256;
}
#define R8(o) F4(d, o), F4(d, o + 4)
__device__ __forceinline__ void wgmma_n256_ss_tt(float* d, uint64_t da, uint64_t db, int accum) {
    asm volatile("{.reg .pred p; setp.ne.b32 p, %130, 0;\n"
        "wgmma.mma_async.sync.aligned.m64n256k16.f32.bf16.bf16 {%0,%1,%2,%3,%4,%5,%6,%7,%8,%9,%10,%11,%12,%13,%14,%15,"
        "%16,%17,%18,%19,%20,%21,%22,%23,%24,%25,%26,%27,%28,%29,%30,%31,%32,%33,%34,%35,%36,%37,%38,%39,%40,%41,%42,%43,%44,%45,%46,%47,"
        "%48,%49,%50,%51,%52,%53,%54,%55,%56,%57,%58,%59,%60,%61,%62,%63,%64,%65,%66,%67,%68,%69,%70,%71,%72,%73,%74,%75,%76,%77,%78,%79,"
        "%80,%81,%82,%83,%84,%85,%86,%87,%88,%89,%90,%91,%92,%93,%94,%95,%96,%97,%98,%99,%100,%101,%102,%103,%104,%105,%106,%107,%108,%109,%110,%111,"
        "%112,%113,%114,%115,%116,%117,%118,%119,%120,%121,%122,%123,%124,%125,%126,%127}, %128, %129, p, 1, 1, 1, 1;}"
        : R8(0), R8(8), R8(16), R8(24), R8(32), R8(40), R8(48), R8(56), R8(64), R8(72), R8(80), R8(88), R8(96), R8(104), R8(112), R8(120)
        : "l"(da), "l"(db), "r"(accum));
}
#undef R8
__global__ void __cluster_dims__(2, 1, 1) __launch_bounds__(288, 1)
out_kernel(const __grid_constant__ CUtensorMap tmO, const __grid_constant__ CUtensorMap tmWo, const __grid_constant__ CUtensorMap tmA,
           const __grid_constant__ CUtensorMap tmOut, const __grid_constant__ MainParams prm) {
    using namespace ok;
    extern __shared__ __align__(1024) uint8_t smem_raw[];
    const uint32_t SB = smem_u32(smem_raw), AT = SB + STAGES * STG, BAR = AT + 32768;
    if (SB & 1023) __trap();
    const int tid = threadIdx.x, w = tid >> 5, lane = tid & 31;
    const int rank = blockIdx.x & 1, mt = blockIdx.x >> 3, nt = (blockIdx.x >> 1) & 3;
    const uint32_t full = BAR, empty = BAR + 64, afull = BAR + 128;
    if (tid == 0) {
        for (int i = 0; i < STAGES; i++) { mbar_init(full + i * 8, 1); mbar_init(empty + i * 8, 8); }
        mbar_init(afull, 1);
        asm volatile("fence.mbarrier_init.release.cluster;" ::: "memory");
    }
    __syncthreads();
    asm volatile("griddepcontrol.wait;" ::: "memory");
    TL(4);
    if (w == 8) {
        if (lane == 0) {
            int st = 0, ph = 1;
            for (int kb = 0; kb < 32; kb++) {
                if (kb >= STAGES) mbar_wait(empty + st * 8, ph);
                mbar_expect(full + st * 8, STG);
                tma3d(SB + st * STG, &tmO, 0, (rank * 32 + kb) * 2, mt * 16, full + st * 8);
                tma3d(SB + st * STG + 16384, &tmWo, 0, (rank * 32 + kb) * 64, nt * 4, full + st * 8);
                if (kb == STAGES - 1) { mbar_expect(afull, 32768); tma3d(AT, &tmA, mt * 128, 0, (nt * 2 + rank) * 16, afull); }
                if (++st == STAGES) { st = 0; ph ^= 1; }
            }
        }
        __syncwarp();
        asm volatile("barrier.cluster.arrive.aligned; barrier.cluster.wait.aligned;" ::: "memory");
        asm volatile("barrier.cluster.arrive.aligned; barrier.cluster.wait.aligned;" ::: "memory");
    } else {
        const int wg = w >> 2, g = lane >> 2;
        float acc[128];
        const int tok0 = 32 * (4 * mt + (w >> 1)) + 8 * (g >> 1) + 4 * (w & 1) + (g & 1);
        const float g0 = g_gate[tok0], g1 = g_gate[tok0 + 2];
        int st = 0, ph = 0, pst = 0;
        #pragma unroll 1
        for (int kb = 0; kb < 32; kb++) {
            mbar_wait(full + st * 8, ph);
            const uint64_t da = mkdesc(SB + st * STG + wg * 8192, 128, 1024, 0), db = mkdesc(SB + st * STG + 16384, 8192, 1024, 1);
            wg_fence();
            #pragma unroll
            for (int ks = 0; ks < 4; ks++) wgmma_n256_ss_tt(acc, da + ks * 16, db + ks * 128, (kb | ks) != 0);
            wg_commit();
            wg_wait<1>();
            if (kb > 0 && lane == 0) mbar_arrive(empty + pst * 8);
            pst = st;
            if (++st == STAGES) { st = 0; ph ^= 1; }
        }
        wg_wait<0>();
        TLX(12);
        asm volatile("barrier.cluster.arrive.aligned; barrier.cluster.wait.aligned;" ::: "memory");
        uint32_t peer;
        asm volatile("mapa.shared::cluster.u32 %0, %1, %2;" : "=r"(peer) : "r"(SB + 65536 + tid * 16), "r"(rank ^ 1));
        #define SND(e) pack2(rank ? acc[8 * i + (e)] : acc[64 + 8 * i + (e)], rank ? acc[8 * i + (e) + 1] : acc[65 + 8 * i + (e)])
        #pragma unroll
        for (int i = 0; i < 8; i++)
            asm volatile("st.shared::cluster.v4.b32 [%0], {%1,%2,%3,%4};" :: "r"(peer + i * 4096), "r"(SND(0)), "r"(SND(2)), "r"(SND(4)), "r"(SND(6)) : "memory");
        #undef SND
        asm volatile("barrier.cluster.arrive.aligned; barrier.cluster.wait.aligned;" ::: "memory");
        mbar_wait(afull, 0);
        const float h0 = 1.f - g0, h1 = 1.f - g1;
        const uint32_t la = AT + (lane >> 4) * 2048 + (4 * (w & 1) + 2 * ((lane >> 3) & 1) + (lane & 1)) * 256 + (4 * (w >> 1) + ((lane & 7) >> 1)) * 16;
        const uint32_t ra = SB + (w * 16 + (lane & 15)) * 128;
        #pragma unroll
        for (int i = 0; i < 8; i++) {
            const uint32_t a = ra + (i >> 2) * 16384 + ((((i & 3) * 2 + (lane >> 4)) ^ (lane & 7)) << 4);
            uint32_t r0, r1, r2, r3;
            ldsm4(r0, r1, r2, r3, la + i * 4096);
            const uint4 u = lds128(SB + 65536 + tid * 16 + i * 4096);
            float p[8];
            #pragma unroll
            for (int e = 0; e < 8; e++) { const uint32_t x = ((const uint32_t*)&u)[e >> 1]; p[e] = (rank ? acc[64 + 8 * i + e] : acc[8 * i + e]) + ((e & 1) ? bfhi(x) : bflo(x)); }
            stsm4(a, pack2(fmaf(g0, bflo(r0), h0 * p[0]), fmaf(g0, bfhi(r0), h0 * p[1])), pack2(fmaf(g1, bflo(r1), h1 * p[2]), fmaf(g1, bfhi(r1), h1 * p[3])),
                     pack2(fmaf(g0, bflo(r2), h0 * p[4]), fmaf(g0, bfhi(r2), h0 * p[5])), pack2(fmaf(g1, bflo(r3), h1 * p[6]), fmaf(g1, bfhi(r3), h1 * p[7])));
        }
        asm volatile("fence.proxy.async.shared::cta;" ::: "memory");
        bsync<1, 256>();
        if (tid == 0) {
            for (int hf = 0; hf < 2; hf++)
                asm volatile("cp.async.bulk.tensor.5d.global.shared::cta.bulk_group [%0, {%2, %3, %3, %3, %4}], [%1];"
                    :: "l"(&tmOut), "r"(SB + hf * 16384), "r"(nt * 256 + rank * 128 + hf * 64), "r"(0), "r"(mt * 4) : "memory");
            asm volatile("cp.async.bulk.commit_group;" ::: "memory");
            asm volatile("cp.async.bulk.wait_group 0;" ::: "memory");
        }
        TL(5);
    }
}

typedef CUresult (*EncodeFn)(CUtensorMap*, CUtensorMapDataType, cuuint32_t, void*, const cuuint64_t*, const cuuint64_t*, const cuuint32_t*,
                             const cuuint32_t*, CUtensorMapInterleave, CUtensorMapSwizzle, CUtensorMapL2promotion, CUtensorMapFloatOOBfill);
static void enc(EncodeFn fn, CUtensorMap* m, void* base, int rank, const cuuint64_t* dims, const cuuint64_t* strides, const cuuint32_t* box, CUtensorMapSwizzle sw) {
    cuuint32_t es[5] = {1, 1, 1, 1, 1};
    fn(m, CU_TENSOR_MAP_DATA_TYPE_BFLOAT16, rank, base, dims, strides, box, es, CU_TENSOR_MAP_INTERLEAVE_NONE, sw,
       CU_TENSOR_MAP_L2_PROMOTION_L2_128B, CU_TENSOR_MAP_FLOAT_OOB_FILL_NONE);
}
static MainParams h_prm = {{800, 512, 384, 0, 0, 0, 0, 0, 0, 0, 0, 0}, 0, nullptr};

extern "C" void kernel_launch(void* const* d_in, const int* in_sizes, int n_in, void* d_out, int out_size) {
    const bf16* q = (const bf16*)d_in[0];
    const bf16* k = (const bf16*)d_in[1];
    const bf16* v = (const bf16*)d_in[2];
    const bf16* shift_k = (const bf16*)d_in[3];
    const bf16* ssm_k = (const bf16*)d_in[4];
    const bf16* ssm_D = (const bf16*)d_in[5];
    const bf16* mem0 = (const bf16*)d_in[7];
    const bf16* gate_w = (const bf16*)d_in[13];

    static EncodeFn fn = nullptr;
    static void* pO = nullptr;
    static void* pA = nullptr;
    if (!fn) {
        cudaDriverEntryPointQueryResult qr;
        cudaGetDriverEntryPoint("cuTensorMapEncodeTiled", (void**)&fn, cudaEnableDefault, &qr);
        cudaGetSymbolAddress(&pO, g_O);
        cudaGetSymbolAddress(&pA, g_A);
        void* pRB; cudaGetSymbolAddress(&pRB, g_RB);
        h_prm.rb = (char*)(((uintptr_t)pRB + (4u << 20) - 1) & ~(uintptr_t)((4u << 20) - 1));
        cudaFuncSetAttribute(main_kernel, cudaFuncAttributeMaxDynamicSharedMemorySize, mk::TOTAL);
        cudaFuncSetAttribute(conv_kernel, cudaFuncAttributeMaxDynamicSharedMemorySize, ck::TOTAL);
        cudaFuncSetAttribute(out_kernel, cudaFuncAttributeMaxDynamicSharedMemorySize, ok::TOTAL);
    }
    CUtensorMap mWq, mWk, mWv, mWo, mX, mO, mWo2, mA, mOut;
    {
        cuuint64_t d[2] = {4096, 1024}, s[1] = {8192}; cuuint32_t b[2] = {64, 256};
        enc(fn, &mWq, d_in[8], 2, d, s, b, CU_TENSOR_MAP_SWIZZLE_128B);
        enc(fn, &mWk, d_in[9], 2, d, s, b, CU_TENSOR_MAP_SWIZZLE_128B);
        enc(fn, &mWv, d_in[10], 2, d, s, b, CU_TENSOR_MAP_SWIZZLE_128B);
    }
    {
        cuuint64_t d[2] = {1024, 4096}, s[1] = {2048}; cuuint32_t b[2] = {64, 128};
        enc(fn, &mWo, d_in[11], 2, d, s, b, CU_TENSOR_MAP_SWIZZLE_128B);
        cuuint64_t d2[3] = {64, 4096, 16}, s2[2] = {2048, 128}; cuuint32_t b2[3] = {64, 64, 4};
        enc(fn, &mWo2, d_in[11], 3, d2, s2, b2, CU_TENSOR_MAP_SWIZZLE_128B);
    }
    {
        cuuint64_t d[3] = {64, 2048, 16}, s[2] = {2048, 128}; cuuint32_t b[3] = {64, 32, 8};
        enc(fn, &mX, d_in[0], 3, d, s, b, CU_TENSOR_MAP_SWIZZLE_128B);
    }
    {
        cuuint64_t d[3] = {256, 128, 256}, s[2] = {512, 65536}; cuuint32_t b[3] = {256, 2, 16};
        enc(fn, &mO, pO, 3, d, s, b, CU_TENSOR_MAP_SWIZZLE_NONE);
    }
    {
        cuuint64_t d[5] = {1024, 2, 4, 4, 64}, s[4] = {2048, 16384, 4096, 65536}; cuuint32_t b[5] = {64, 2, 4, 4, 4};
        cuuint64_t da[3] = {2048, 8, 128}, sa[2] = {4096, 32768}; cuuint32_t ba[3] = {128, 8, 16};
        enc(fn, &mA, pA, 3, da, sa, ba, CU_TENSOR_MAP_SWIZZLE_NONE);
        enc(fn, &mOut, d_out, 5, d, s, b, CU_TENSOR_MAP_SWIZZLE_128B);
    }
    cudaStream_t st = cudaStreamPerThread;
    conv_kernel<<<128, 288, ck::TOTAL, st>>>(q, k, v, shift_k, ssm_k, ssm_D, gate_w, (const bf16*)d_in[8], (const bf16*)d_in[9],
                                             (const bf16*)d_in[10], (const bf16*)d_in[11], mWq, mWk, mWv, mWo, h_prm.rb);
    cudaLaunchAttribute at[1];
    at[0].id = cudaLaunchAttributeProgrammaticStreamSerialization;
    at[0].val.programmaticStreamSerializationAllowed = 1;
    cudaLaunchConfig_t cfg = {};
    cfg.stream = st; cfg.attrs = at; cfg.numAttrs = PDL;
    cfg.gridDim = dim3(NCTA); cfg.blockDim = dim3(256); cfg.dynamicSmemBytes = mk::TOTAL;
    cudaLaunchKernelEx(&cfg, main_kernel, mWq, mWk, mWv, mWo, mX, mem0, (const bf16*)d_in[11], h_prm);
    cfg.gridDim = dim3(128); cfg.blockDim = dim3(288); cfg.dynamicSmemBytes = ok::TOTAL;
    cudaLaunchKernelEx(&cfg, out_kernel, mO, mWo2, mA, mOut, h_prm);
}
```

```cpp
#include <cuda_runtime.h>
#include <cuda_bf16.h>
#include <cuda.h>
#include <stdint.h>

typedef __nv_bfloat16 bf16;

constexpr int SEQ = 2048, DM = 1024, NH = 32, DH = 128, NSEG = 64;
constexpr int SPIN_LIMIT = 1 << 13, NCTA = 132;
#define NPR 6
#define PDL 1
#define TPF 1

constexpr uint32_t HOME_BITS = 0xB3000;
constexpr uint32_t RB_R = 0;
constexpr uint32_t RB_B = 0x80000;
constexpr uint32_t RB_T = RB_B + 0x4000;
constexpr uint32_t RB_P = RB_B + 0x20000;
constexpr uint32_t RB_X = 2u << 20;
__device__ uint4 g_RB[(8 << 20) / 16];
__device__ uint32_t g_cls[160];
__device__ uint4 g_T[2 * NH * 3072];
__device__ uint4 g_O[NSEG * 4 * 4096];
__device__ uint4 g_A[SEQ * DM / 8];
__device__ float g_gate[SEQ];
__device__ uint32_t g_err;
#define TL(i)
#define TLX(i)

__device__ __forceinline__ uint32_t smem_u32(const void* p) { return (uint32_t)__cvta_generic_to_shared(p); }
__device__ __forceinline__ uint32_t clk() { uint32_t c; asm volatile("mov.u32 %0, %%clock;" : "=r"(c) :: "memory"); return c; }
__device__ __forceinline__ void ldsm4(uint32_t& r0, uint32_t& r1, uint32_t& r2, uint32_t& r3, uint32_t a) {
    asm volatile("ldmatrix.sync.aligned.m8n8.x4.shared.b16 {%0,%1,%2,%3}, [%4];" : "=r"(r0), "=r"(r1), "=r"(r2), "=r"(r3) : "r"(a) : "memory");
}
__device__ __forceinline__ void ldsm4t(uint32_t& r0, uint32_t& r1, uint32_t& r2, uint32_t& r3, uint32_t a) {
    asm volatile("ldmatrix.sync.aligned.m8n8.x4.trans.shared.b16 {%0,%1,%2,%3}, [%4];" : "=r"(r0), "=r"(r1), "=r"(r2), "=r"(r3) : "r"(a) : "memory");
}
__device__ __forceinline__ void ldsm2(uint32_t& r0, uint32_t& r1, uint32_t a) {
    asm volatile("ldmatrix.sync.aligned.m8n8.x2.shared.b16 {%0,%1}, [%2];" : "=r"(r0), "=r"(r1) : "r"(a) : "memory");
}
__device__ __forceinline__ void stsm4t(uint32_t a, uint32_t r0, uint32_t r1, uint32_t r2, uint32_t r3) {
    asm volatile("stmatrix.sync.aligned.m8n8.x4.trans.shared.b16 [%0], {%1,%2,%3,%4};" :: "r"(a), "r"(r0), "r"(r1), "r"(r2), "r"(r3) : "memory");
}
__device__ __forceinline__ void mma16(float* c, uint32_t a0, uint32_t a1, uint32_t a2, uint32_t a3, uint32_t b0, uint32_t b1) {
    asm volatile("mma.sync.aligned.m16n8k16.row.col.f32.bf16.bf16.f32 {%0,%1,%2,%3}, {%4,%5,%6,%7}, {%8,%9}, {%0,%1,%2,%3};"
        : "+f"(c[0]), "+f"(c[1]), "+f"(c[2]), "+f"(c[3]) : "r"(a0), "r"(a1), "r"(a2), "r"(a3), "r"(b0), "r"(b1));
}
__device__ __forceinline__ void mma8(float* c, uint32_t a0, uint32_t a1, uint32_t b0) {
    asm volatile("mma.sync.aligned.m16n8k8.row.col.f32.bf16.bf16.f32 {%0,%1,%2,%3}, {%4,%5}, {%6}, {%0,%1,%2,%3};"
        : "+f"(c[0]), "+f"(c[1]), "+f"(c[2]), "+f"(c[3]) : "r"(a0), "r"(a1), "r"(b0));
}
__device__ __forceinline__ uint32_t pack2(float lo, float hi) {
    uint32_t r; asm("cvt.rn.bf16x2.f32 %0, %1, %2;" : "=r"(r) : "f"(hi), "f"(lo)); return r;
}
__device__ __forceinline__ uint32_t hadd2(uint32_t a, uint32_t b) {
    uint32_t r; asm("add.rn.bf16x2 %0, %1, %2;" : "=r"(r) : "r"(a), "r"(b)); return r;
}
__device__ __forceinline__ float bflo(uint32_t w) { return __uint_as_float(w << 16); }
__device__ __forceinline__ float bfhi(uint32_t w) { return __uint_as_float(w & 0xFFFF0000u); }
__device__ __forceinline__ void st_g32(void* p, uint32_t v) { asm volatile("st.relaxed.gpu.global.u32 [%0], %1;" :: "l"(p), "r"(v) : "memory"); }
__device__ __forceinline__ void st_g128(void* p, uint32_t a, uint32_t b, uint32_t c, uint32_t d) {
    asm volatile("st.relaxed.gpu.global.v4.u32 [%0], {%1,%2,%3,%4};" :: "l"(p), "r"(a), "r"(b), "r"(c), "r"(d) : "memory");
}
__device__ __forceinline__ uint4 lds128(uint32_t a) { uint4 v; asm volatile("ld.shared.v4.u32 {%0,%1,%2,%3}, [%4];" : "=r"(v.x), "=r"(v.y), "=r"(v.z), "=r"(v.w) : "r"(a) : "memory"); return v; }
__device__ __forceinline__ void sts128(uint32_t a, uint4 v) { asm volatile("st.shared.v4.u32 [%0], {%1,%2,%3,%4};" :: "r"(a), "r"(v.x), "r"(v.y), "r"(v.z), "r"(v.w) : "memory"); }
__device__ __forceinline__ float2 lds64f(uint32_t a) { float2 v; asm volatile("ld.shared.v2.f32 {%0,%1}, [%2];" : "=f"(v.x), "=f"(v.y) : "r"(a) : "memory"); return v; }
__device__ __forceinline__ void sts64f(uint32_t a, float x, float y) { asm volatile("st.shared.v2.f32 [%0], {%1,%2};" :: "r"(a), "f"(x), "f"(y) : "memory"); }
__device__ __forceinline__ void sts32f(uint32_t a, float x) { asm volatile("st.shared.f32 [%0], %1;" :: "r"(a), "f"(x) : "memory"); }
__device__ __forceinline__ void sts32(uint32_t a, uint32_t x) { asm volatile("st.shared.u32 [%0], %1;" :: "r"(a), "r"(x) : "memory"); }
__device__ __forceinline__ uint32_t lds32(uint32_t a) { uint32_t v; asm volatile("ld.shared.u32 %0, [%1];" : "=r"(v) : "r"(a) : "memory"); return v; }
__device__ __forceinline__ void cpa16(uint32_t dst, const void* src) { asm volatile("cp.async.cg.shared.global [%0], [%1], 16;" :: "r"(dst), "l"(src) : "memory"); }
__device__ __forceinline__ void cpa_commit() { asm volatile("cp.async.commit_group;" ::: "memory"); }
__device__ __forceinline__ void cpa_wait() { asm volatile("cp.async.wait_all;" ::: "memory"); }
template <int ID, int N> __device__ __forceinline__ void bsync() { asm volatile("bar.sync %0, %1;" :: "n"(ID), "n"(N) : "memory"); }
template <int ID, int N> __device__ __forceinline__ void barrive() { asm volatile("bar.arrive %0, %1;" :: "n"(ID), "n"(N) : "memory"); }
template <int ID, int N> __device__ __forceinline__ void bsync_if(bool on) { asm volatile("{ .reg .pred p; setp.ne.b32 p, %2, 0; @p bar.sync %0, %1; }" :: "n"(ID), "n"(N), "r"((int)on) : "memory"); }
template <int ID, int N> __device__ __forceinline__ void barrive_if(bool on) { asm volatile("{ .reg .pred p; setp.ne.b32 p, %2, 0; @p bar.arrive %0, %1; }" :: "n"(ID), "n"(N), "r"((int)on) : "memory"); }
__device__ __forceinline__ void mbar_init(uint32_t mb, uint32_t n) { asm volatile("mbarrier.init.shared::cta.b64 [%0], %1;" :: "r"(mb), "r"(n) : "memory"); }
__device__ __forceinline__ void mbar_expect(uint32_t mb, uint32_t bytes) { asm volatile("mbarrier.arrive.expect_tx.shared::cta.b64 _, [%0], %1;" :: "r"(mb), "r"(bytes) : "memory"); }
__device__ __forceinline__ void mbar_arrive(uint32_t mb) { asm volatile("mbarrier.arrive.shared::cta.b64 _, [%0];" :: "r"(mb) : "memory"); }
__device__ __forceinline__ void mbar_wait(uint32_t mb, uint32_t ph) {
    asm volatile("{ .reg .pred p; .reg .u32 n; mov.u32 n, 0;\n"
                 "MW_%=: mbarrier.try_wait.parity.shared::cta.b64 p, [%0], %1; add.u32 n, n, 1; setp.lt.and.u32 p, n, %2, !p; @p bra.uni MW_%=; }"
                 :: "r"(mb), "r"(ph), "n"(SPIN_LIMIT) : "memory");
}
__device__ __forceinline__ void tma2d(uint32_t dst, const CUtensorMap* m, int c0, int c1, uint32_t mb) {
    asm volatile("cp.async.bulk.tensor.2d.shared::cluster.global.mbarrier::complete_tx::bytes [%0], [%1, {%3, %4}], [%2];"
        :: "r"(dst), "l"(m), "r"(mb), "r"(c0), "r"(c1) : "memory");
}
__device__ __forceinline__ void tma3d(uint32_t dst, const CUtensorMap* m, int c0, int c1, int c2, uint32_t mb) {
    asm volatile("cp.async.bulk.tensor.3d.shared::cluster.global.mbarrier::complete_tx::bytes [%0], [%1, {%3, %4, %5}], [%2];"
        :: "r"(dst), "l"(m), "r"(mb), "r"(c0), "r"(c1), "r"(c2) : "memory");
}
__device__ __forceinline__ void bulk_ld(uint32_t dst, const void* src, uint32_t bytes, uint32_t mb) {
    asm volatile("cp.async.bulk.shared::cluster.global.mbarrier::complete_tx::bytes [%0], [%1], %2, [%3];" :: "r"(dst), "l"(src), "r"(bytes), "r"(mb) : "memory");
}
__device__ __forceinline__ uint64_t mkdesc(uint32_t addr, uint32_t lbo, uint32_t sbo, uint32_t swz) {
    return (uint64_t)((addr & 0x3FFFF) >> 4) | ((uint64_t)(lbo >> 4) << 16) | ((uint64_t)(sbo >> 4) << 32) | ((uint64_t)swz << 62);
}
__device__ __forceinline__ void wg_fence() { asm volatile("wgmma.fence.sync.aligned;" ::: "memory"); }
__device__ __forceinline__ void wg_commit() { asm volatile("wgmma.commit_group.sync.aligned;" ::: "memory"); }
template <int N> __device__ __forceinline__ void wg_wait() { asm volatile("wgmma.wait_group.sync.aligned %0;" :: "n"(N) : "memory"); }
#define F4(d, o) "+f"(d[o]), "+f"(d[o + 1]), "+f"(d[o + 2]), "+f"(d[o + 3])
__device__ __forceinline__ void wgmma_n32_rs(float* d, const uint32_t* a, uint64_t db, int accum) {
    asm volatile("{.reg .pred p; setp.ne.b32 p, %21, 0;\n"
        "wgmma.mma_async.sync.aligned.m64n32k16.f32.bf16.bf16 {%0,%1,%2,%3,%4,%5,%6,%7,%8,%9,%10,%11,%12,%13,%14,%15}, {%16,%17,%18,%19}, %20, p, 1, 1, 0;}"
        : F4(d, 0), F4(d, 4), F4(d, 8), F4(d, 12) : "r"(a[0]), "r"(a[1]), "r"(a[2]), "r"(a[3]), "l"(db), "r"(accum));
}
__device__ __forceinline__ void wait_until(uint32_t tgt, uint32_t any) {
    asm volatile("{ .reg .pred p, q; .reg .u32 t; .reg .s32 d; mov.u32 t, %0; setp.ne.u32 q, %1, 0xFFFFFFFF;\n"
                 "WU_%=: @q mov.u32 t, %%clock; sub.s32 d, t, %0; setp.lt.s32 p, d, 0; @p bra.uni WU_%=; }" :: "r"(tgt), "r"(any) : "memory");
}

namespace mk {
constexpr uint32_t SB = 1024;
constexpr uint32_t WV = SB, WO = SB + 65536, XT = SB + 131072, TK = SB + 163840  , TQ = TK + 32768, MEM = TQ + 4096,
                   SC = MEM + 8192  , PT = SC + 6144,
                   OB = SC + 8192, SUM = OB + 2048, BAR = SUM + 512, GRP = BAR + 128, PROFB = BAR + 192,
                   TOTAL = PROFB - SB;
static_assert(TOTAL <= 232448, "shared memory");
constexpr uint32_t MB_WQ = BAR, MB_WK = BAR + 8, MB_WV = BAR + 16, MB_WO = BAR + 24, MB_X = BAR + 32, MB_KV = BAR + 40, MB_R = BAR + 48, MB_B = BAR + 56;
constexpr uint32_t XT2 = WV, RS = WV + 32768, VE = RS + 4096;
enum { B_START = 1, B_H0, B_H2, B_H3, B_S1, B_SC, B_SC2, B_S0, B_O, B_O2, B_PT, B_GO, B_VX, B_RD, B_BT };
constexpr uint64_t XD0 = (uint64_t)(XT >> 4) | ((uint64_t)1 << 16) | ((uint64_t)64 << 32) | ((uint64_t)1 << 62);
constexpr uint32_t TSLOT = NH * 49152;
}
struct MainParams { int d[12]; uint32_t zero; char* rb; };
#define XD(i) (mk::XD0 - ((i) >> 5) * ((mk::XT - mk::XT2) >> 4) + (((i) & 31) >> 2) * 256 + ((i) & 3) * 2)
#define XD4(i) XD(i), XD(i + 1), XD(i + 2), XD(i + 3)
#define XD16(i) XD4(i), XD4(i + 4), XD4(i + 8), XD4(i + 12)
__constant__ __align__(256) uint64_t c_xd[64] = {XD16(0), XD16(16), XD16(32), XD16(48)};
#define CUT(r) asm volatile("{ .reg .pred q; setp.eq.u32 q, %1, 0xFFFFFFFF; @q mov.u32 %0, %%clock; }" : "+r"(r) : "r"(t16) : "memory")
__device__ __forceinline__ uint32_t opq(uint32_t x) { asm volatile("" : "+r"(x)); return x; }
__device__ __forceinline__ float opqf(float x) { asm volatile("" : "+f"(x)); return x; }
#define PROF(i)
#define PROFW(i, w)
#define TRC(i, v)
#define RETRY(i, on)
#define P(i) prm.d[i]
#define DELAY(n) do { if (n) { _Pragma("unroll") for (int i_ = 0; i_ < n; i_++) asm volatile("mad.lo.u32 %0, %0, %1, %0;" : "+r"(pb) : "r"(prm.zero)); CUT(pa); } } while (0)

__device__ __forceinline__ uint32_t tagw(uint32_t w, uint32_t tau) { return (w & ~1u) | tau; }
__device__ __forceinline__ uint32_t ld_g32(const void* p) { uint32_t v; asm volatile("ld.relaxed.gpu.global.u32 %0, [%1];" : "=r"(v) : "l"(p) : "memory"); return v; }
__device__ __forceinline__ void ld_g64(uint32_t* v, const void* p) { asm volatile("ld.relaxed.gpu.global.v2.u32 {%0,%1}, [%2];" : "=r"(v[0]), "=r"(v[1]) : "l"(p) : "memory"); }
__device__ __forceinline__ void ld_g128(uint32_t* v, const void* p) {
    asm volatile("ld.relaxed.gpu.global.v4.u32 {%0,%1,%2,%3}, [%4];" : "=r"(v[0]), "=r"(v[1]), "=r"(v[2]), "=r"(v[3]) : "l"(p) : "memory");
}
__device__ __forceinline__ void st_g64(void* p, uint32_t a, uint32_t b) { asm volatile("st.relaxed.gpu.global.v2.u32 [%0], {%1,%2};" :: "l"(p), "r"(a), "r"(b) : "memory"); }
__device__ __forceinline__ void lds128f(float* v, uint32_t a) { asm volatile("ld.shared.v4.f32 {%0,%1,%2,%3}, [%4];" : "=f"(v[0]), "=f"(v[1]), "=f"(v[2]), "=f"(v[3]) : "r"(a) : "memory"); }
__device__ __forceinline__ void sts128f(uint32_t a, float x, float y, float z, float w) { asm volatile("st.shared.v4.f32 [%0], {%1,%2,%3,%4};" :: "r"(a), "f"(x), "f"(y), "f"(z), "f"(w) : "memory"); }
__device__ __forceinline__ void stsm4(uint32_t a, uint32_t r0, uint32_t r1, uint32_t r2, uint32_t r3) {
    asm volatile("stmatrix.sync.aligned.m8n8.x4.shared.b16 [%0], {%1,%2,%3,%4};" :: "r"(a), "r"(r0), "r"(r1), "r"(r2), "r"(r3) : "memory");
}
__device__ __forceinline__ void mmaq(float* c, const uint32_t* a, uint32_t b0, uint32_t b1) { mma16(c, a[0], a[1], a[2], a[3], b0, b1); }
template <int LUT> __device__ __forceinline__ uint32_t lop3(uint32_t a, uint32_t b, uint32_t c) { uint32_t r; asm("lop3.b32 %0, %1, %2, %3, %4;" : "=r"(r) : "r"(a), "r"(b), "r"(c), "n"(LUT)); return r; }
template <int N, int S> __device__ __forceinline__ uint32_t stale(const uint32_t* x, uint32_t tau) {
    if constexpr (N == 2) return lop3<0x7E>(x[0], tau, x[S]);
    else if constexpr (N == 3) return lop3<0xF6>(stale<2, S>(x, tau), x[2 * S], tau);
    else if constexpr (N == 4 || N == 16) return lop3<0xFC>(stale<N / 2, S>(x, tau), stale<N / 2, S>(x + N / 2 * S, tau), 0);
    else return lop3<0xFE>(stale<3, S>(x, tau), stale<3, S>(x + 3 * S, tau), stale<2, S>(x + 6 * S, tau));
}
__device__ __forceinline__ uint32_t late(uint32_t a, uint32_t b, uint32_t mask) {
    uint32_t r;
    asm volatile("{ .reg .pred p; .reg .b32 t; lop3.b32 t, %1, %2, %3, 0xA8; setp.ne.b32 p, t, 0; vote.sync.any.pred p, p, 0xFFFFFFFF; selp.u32 %0, 1, 0, p; }" : "=r"(r) : "r"(a), "r"(b), "r"(mask));
    return r;
}
#define AGAIN(id, reload, ...) _Pragma("unroll 1") for (int n_ = 0; __builtin_expect(__VA_ARGS__, 0) && n_ < SPIN_LIMIT; n_++) { RETRY(id, 1); reload; }
__device__ __forceinline__ uint32_t tile_off(int lane, int chunk0) {
    return ((lane >> 4) * 8 + (lane & 7)) * 128 + (((chunk0 + ((lane >> 3) & 1)) ^ (lane & 7)) << 4);
}
template <int K0, int K1>
__device__ __forceinline__ void load_tile(uint32_t a, uint32_t* T) {
    #pragma unroll
    for (int ks = K0; ks < K1; ks++) ldsm4t(T[4 * ks], T[4 * ks + 1], T[4 * ks + 2], T[4 * ks + 3], a + ks * 2048);
}
__device__ __forceinline__ void lds128u(uint32_t* v, uint32_t a) { asm volatile("ld.shared.v4.u32 {%0,%1,%2,%3}, [%4];" : "=r"(v[0]), "=r"(v[1]), "=r"(v[2]), "=r"(v[3]) : "r"(a) : "memory"); }
template <int K0, int K1, int STRIDE = 4096>
__device__ __forceinline__ void load_frag(uint32_t a, uint32_t* T) {
    #pragma unroll
    for (int ks = K0; ks < K1; ks++) lds128u(&T[4 * ks], a + ks * STRIDE);
}
template <int L0, int L1, bool INIT = false>
__device__ __forceinline__ void wg_run(float* acc, const uint32_t* A, const uint64_t* d) {
    if (L1 > L0) {
        wg_fence();
        #pragma unroll
        for (int l = L0; l < L1; l++) wgmma_n32_rs(acc, &A[4 * l], d[l], INIT || l != 0);
        wg_commit();
    }
}
__device__ __forceinline__ void load_x(const CUtensorMap* tmX, int c, int seg, uint32_t dst, bool on) {
    asm volatile("{ .reg .pred p; elect.sync _|p, 0xFFFFFFFF; setp.ne.and.b32 p, %6, 0, p;\n"
        "@p mbarrier.arrive.expect_tx.shared::cta.b64 _, [%3], 32768;\n"
        "@p cp.async.bulk.tensor.3d.shared::cluster.global.mbarrier::complete_tx::bytes [%4], [%0, {%5, %1, %2}], [%3]; }"
        :: "l"(tmX), "r"(seg * 32), "r"((c & 1) * 8), "r"(mk::MB_X), "r"(dst), "r"(0), "r"((int)on) : "memory");
}
__device__ __forceinline__ void bulk_expect(uint32_t mb, uint32_t bytes) {
    asm volatile("{ .reg .pred p; elect.sync _|p, 0xFFFFFFFF; @p mbarrier.arrive.expect_tx.shared::cta.b64 _, [%0], %1; }" :: "r"(mb), "r"(bytes) : "memory");
}
__device__ __forceinline__ void bulk_copy(uint32_t dst, const void* src, uint32_t bytes, uint32_t mb) {
    asm volatile("{ .reg .pred p; elect.sync _|p, 0xFFFFFFFF; @p cp.async.bulk.shared::cluster.global.mbarrier::complete_tx::bytes [%0], [%1], %2, [%3]; }"
        :: "r"(dst), "l"(src), "r"(bytes), "r"(mb) : "memory");
    __syncwarp();
}
__device__ __forceinline__ void bulk_copy_if(bool on, uint32_t dst, const void* src, uint32_t bytes, uint32_t mb) {
    asm volatile("{ .reg .pred p; elect.sync _|p, 0xFFFFFFFF; setp.ne.and.b32 p, %4, 0, p; @p cp.async.bulk.shared::cluster.global.mbarrier::complete_tx::bytes [%0], [%1], %2, [%3]; }"
        :: "r"(dst), "l"(src), "r"(bytes), "r"(mb), "r"((int)on) : "memory");
    __syncwarp();
}
__device__ __forceinline__ void kv_expect(uint32_t bytes) { bulk_expect(mk::MB_KV, bytes); }
__device__ __forceinline__ void kv_copy(uint32_t dst, const void* src, uint32_t bytes) { bulk_copy(dst, src, bytes, mk::MB_KV); }
__device__ __forceinline__ uint32_t gtime() { uint32_t c; asm volatile("mov.u32 %0, %%globaltimer_lo;" : "=r"(c) :: "memory"); return c; }
__device__ __forceinline__ void wait_g(uint32_t tgt, uint32_t any) {
    asm volatile("{ .reg .pred p, q; .reg .u32 t; mov.u32 t, %0; setp.ne.u32 q, %1, 0xFFFFFFFF;\n"
                 "WG_%=: @q mov.u32 t, %%globaltimer_lo; sub.u32 t, t, %0; setp.gt.u32 p, t, 0xFFFF0000; @p bra.uni WG_%=; }" :: "r"(tgt), "r"(any) : "memory");
    __syncwarp();
}
__device__ __forceinline__ uint32_t clkv(uint32_t any) {
    uint32_t c; asm volatile("{ .reg .pred q; setp.ne.u32 q, %1, 0xFFFFFFFF; mov.u32 %0, 0; @q mov.u32 %0, %%clock; }" : "=r"(c) : "r"(any) : "memory"); return c;
}
__device__ __forceinline__ char* kv_src(int c, int seg) { return (char*)g_T + ((seg & 1) * mk::TSLOT + (c >> 2) * 49152); }
__device__ __forceinline__ void prefetch_l2(const void* p, uint32_t bytes) {
    asm volatile("{ .reg .pred p; elect.sync _|p, 0xFFFFFFFF; @p cp.async.bulk.prefetch.L2.global [%0], %1; }" :: "l"(p), "r"(bytes) : "memory");
}
__device__ __forceinline__ void refetch_kv(int c, int seg, uint32_t l16) {
    const char* src = kv_src(c, seg);
    #pragma unroll 1
    for (int i = 0; i < 72; i++) {
        uint32_t v[4];
        ld_g128(v, src + (i * 512 + (i >> 6) * (c & 3) * 4096) + l16);
        sts128(mk::TK + i * 512 + l16, make_uint4(v[0], v[1], v[2], v[3]));
    }
    __syncwarp();
}
__device__ __forceinline__ uint32_t phase(int i) { return (~i >> 1) & 1; }
__device__ __forceinline__ void qk_pack(const float* acc, uint32_t* p) {
    #pragma unroll
    for (int i = 0; i < 4; i++) { p[i] = pack2(acc[4 * i], acc[4 * i + 1]); p[4 + i] = pack2(acc[4 * i + 2], acc[4 * i + 3]); }
}
__device__ __forceinline__ void sts128_if(bool on, uint32_t a, const uint32_t* p) {
    asm volatile("{ .reg .pred p; setp.ne.b32 p, %5, 0; @p st.shared.v4.u32 [%0], {%1,%2,%3,%4}; }" :: "r"(a), "r"(p[0]), "r"(p[1]), "r"(p[2]), "r"(p[3]), "r"((int)on) : "memory");
}
__device__ __forceinline__ void st_if(bool on, char* a, const uint32_t* p) {
    asm volatile("{ .reg .pred p; setp.ne.b32 p, %5, 0; @p st.relaxed.gpu.global.v4.u32 [%0], {%1,%2,%3,%4}; }" :: "l"(a), "r"(p[0]), "r"(p[1]), "r"(p[2]), "r"(p[3]), "r"((int)on) : "memory");
}
__device__ __forceinline__ char* tok_dst(int c, int seg, int wg) { return kv_src(c, seg) + (wg ? (c & 1) * 8192 + (c & 2) * 2048 : 32768 + (c & 1) * 2048 + (c & 2) * 512); }
#define HI8 (wg ? 0x220 : 0xC0)
__device__ __forceinline__ void acc_init(float* acc, const uint32_t* p) {
    #pragma unroll
    for (int i = 0; i < 4; i++) { acc[4 * i] = bflo(p[i]); acc[4 * i + 1] = bfhi(p[i]); acc[4 * i + 2] = bflo(p[4 + i]); acc[4 * i + 3] = bfhi(p[4 + i]); }
}
__device__ __forceinline__ void acc_add(float* acc, const uint32_t* p) {
    #pragma unroll
    for (int i = 0; i < 4; i++) { acc[4 * i] += bflo(p[i]); acc[4 * i + 1] += bfhi(p[i]); acc[4 * i + 2] += bflo(p[4 + i]); acc[4 * i + 3] += bfhi(p[4 + i]); }
}
__device__ __forceinline__ void pack_tag(const float* acc, uint32_t* p, uint32_t tau) { qk_pack(acc, p); p[0] = tagw(p[0], tau); p[4] = tagw(p[4], tau); }
constexpr uint32_t ONES = 0x3F803F80u;
__device__ __forceinline__ float rcpf(float x) { float r; asm("rcp.approx.ftz.f32 %0, %1;" : "=f"(r) : "f"(x)); return r; }

#define ANN 2
#define POL 10
#define KM 0
#define NLDS 2
#define AL 2
#define RP 22
#define RQ 2
#define RL 29
#define R4 1
#define KVP 12
#define LD7 8
#define XP 3
#define G2 0
#define NB 26
#define BD 8
#define NP 22
#define TA 4
#define TA0 2
#define NT 19
#define VH 1
#define TRIES 200
#define NPW 3
#define EV0 4
#define EV1 8
#define WA1 6
#define WA2 9
#define H2 12
#define QV 1
#define QD 0
#define KD 0
#define VD 0
#define WA0 4
#define ONE 0
#define PP 12
#define OBA 3
#define WA3 1
#define WB1 0
#define WB2 12
#define WB3 12
#define H0 10
#define H3 10
__device__ __forceinline__ uint32_t tagm(uint32_t w, uint32_t mask, uint32_t tau) { return lop3<0xB8>(w, mask, tau); }
__device__ __forceinline__ char* at(uint32_t lo, uint32_t hi) { char* p; asm("mov.b64 %0, {%1,%2};" : "=l"(p) : "r"(lo), "r"(hi)); return p; }
__device__ __forceinline__ float ex2(float x) { float r; asm("ex2.approx.ftz.f32 %0, %1;" : "=f"(r) : "f"(x)); return r; }
__device__ __forceinline__ float max8(const float* x) { return fmaxf(fmaxf(fmaxf(x[0], x[1]), fmaxf(x[2], x[3])), fmaxf(fmaxf(x[4], x[5]), fmaxf(x[6], x[7]))); }
__device__ __forceinline__ float max4lanes(float m) { return fmaxf(fmaxf(m, __shfl_xor_sync(~0u, m, 1)), fmaxf(__shfl_xor_sync(~0u, m, 2), __shfl_xor_sync(~0u, m, 3))); }
constexpr float SCL = 0.08838834764831845f * 1.4426950408889634f;
__device__ __forceinline__ void tok_scores(float* x, uint32_t sa) {
    float y[8];
    lds128f(x, sa); lds128f(y, sa + 1024); lds128f(x + 4, sa + 512); lds128f(y + 4, sa + 1536);
    #pragma unroll
    for (int i = 0; i < 8; i++) x[i] += y[i];
}
__device__ __forceinline__ void mem_scores(float* x, uint32_t sa) {
    float z[8];
    lds128f(z, sa + 2048); lds128f(z + 4, sa + 2560);
    x[8] = (z[0] + z[2]) + (z[4] + z[6]); x[9] = (z[1] + z[3]) + (z[5] + z[7]);
}

struct Ctx { uint32_t u_rs, u_rl, u_bs, u_bl, rblo, rbhi; int w8, c; };
template <int wg>
__device__ __forceinline__ void steps(uint32_t* W, uint32_t* T, uint32_t t16, uint32_t pa, uint32_t pb, const Ctx& cx, const CUtensorMap* tmX, const MainParams& prm) {
    using namespace mk;
    const int c = cx.c, kap = c & 1, w8 = cx.w8;
    const uint32_t rbhi = cx.rbhi;
    uint32_t u_rs = cx.u_rs, u_rl = cx.u_rl, u_bs = cx.u_bs, u_bl = cx.u_bl ^ ((c & 2) << 14);
    uint32_t u_x = cx.rblo + RB_X + (c >> 2) * 16384, u_xs = u_x + kap * 2048 + (c & 2) * 512;
    uint32_t u_ta = ((cx.u_bl & ~0x10000u) ^ (kap << 12)) + (RB_T - RB_B) + 1024;
    uint32_t u_rp = cx.rblo + RB_T + 1024 + c * 4;
    uint32_t u_og = (c & 3) * 65536 + (c >> 2) * 2048 + (w8 & 3) * 256;
    const uint32_t u_sa = (w8 & 2) * 256 + (w8 & 1) * 8;
    #define TOK_DST() tok_dst(c, seg, wg)
    constexpr int EV = wg ? EV1 : EV0;
    constexpr uint32_t VEB = VE + (wg ? EV0 * 2048 - 2048 : 0) - (16 - EV) * 2048;
    static_assert((EV0 + EV1) * 2048 <= 28672, "");
    __syncthreads();
    #pragma unroll
    for (int i = 16 - EV; i < 16; i++) sts128(VEB + i * 2048 + t16, make_uint4(T[4 * i], T[4 * i + 1], T[4 * i + 2], T[4 * i + 3]));
    asm volatile("fence.proxy.async.shared::cta;" ::: "memory");
    if (wg) barrive<B_START, 256>();
    #pragma unroll 1
    for (int s = 0, bc = 0, redo = 0;;) {
        bc = opq(bc + 1);
        t16 |= prm.zero & bc;
        const int seg = s + 2;
        const uint32_t tau = phase(s), tau2 = tau * 0x10001u;
        const uint32_t l16 = opq(t16 & 0x1F0);
        uint32_t F[64];
        float ot[3][2][4];
        uint32_t an[4];
        #define LDB(i) ldsm4t(b[i][0], b[i][1], b[i][2], b[i][3], MEM + l16 + (i) * 512)
        #define ST_X() do { char* xs = at(u_xs + (pb >> 16), rbhi) + wg * 4096; \
            st_g32(xs, tagm(pack2((a[0][0] + a[1][0]) + (a[2][0] + a[3][0]), (a[0][2] + a[1][2]) + (a[2][2] + a[3][2])), mG, tau * 0x10001u)); \
            st_g32(xs + 32, tagm(pack2((a[0][1] + a[1][1]) + (a[2][1] + a[3][1]), (a[0][3] + a[1][3]) + (a[2][3] + a[3][3])), mG, tau * 0x10001u)); } while (0)
        #define ST_V() st_g64(at(u_xs + (t16 >> 1), rbhi) + (8192 + wg * 3072), \
            tagm(pack2((v[0][0] + v[1][0]) + (v[2][0] + v[3][0]), (v[0][1] + v[1][1]) + (v[2][1] + v[3][1])), mT, tau), \
            pack2((v[0][2] + v[1][2]) + (v[2][2] + v[3][2]), (v[0][3] + v[1][3]) + (v[2][3] + v[3][3])))
        #define V_MMA(i, o) do { mmaq(v[2 * ((i) & 1)], &T[8 * (i)], b[(o) + (i)][0], b[(o) + (i)][1]); mmaq(v[2 * ((i) & 1) + 1], &T[8 * (i) + 4], b[(o) + (i)][2], b[(o) + (i)][3]); } while (0)
        #define ST_R(i) do { \
                const uint32_t r0 = pack2((r[i][0][0] + r[i][1][0]) * i0, (r[i][0][1] + r[i][1][1]) * i1); \
                const uint32_t r1 = pack2((r[i][0][2] + r[i][1][2]) * i0, (r[i][0][3] + r[i][1][3]) * i1); \
                st_g64(at(ra ^ (i * 0x3000), rbhi), tagm(r0, mT, tau), r1); } while (0)
        #define LD_OB(i) ldsm4t(ob[4 * (i)], ob[4 * (i) + 1], ob[4 * (i) + 2], ob[4 * (i) + 3], OB + l16 + (i) * 512)
        #define WO_MMA(have, more, mid, tail) uint32_t ob[16], ra; float r[2][2][4] = {}; \
            LD_OB(0); __syncwarp(); LD_OB(1); __syncwarp(); if (OBA > 2) { LD_OB(2); __syncwarp(); } \
            _Pragma("unroll") for (int i = have; i < have + more; i++) { lds128u(&F[4 * i], WO + t16 + i * 4096); __syncwarp(); } \
            _Pragma("unroll") for (int i = 0; i < 16; i++) { \
                if (!(i & 1) || (i > 4 && i < 8)) CUT(pb); \
                if (i == 4) LD_OB(OBA); \
                if (i == 5 && OBA == 2) LD_OB(3); \
                { const int n = have + more + i - 8 + OBA; if (i >= 8 - OBA && n < 16) lds128u(&F[4 * n], WO + t16 + n * 4096); } \
                if (wg == 0 && i == 4) { const float2 su = lds64f(SUM + (l16 >> 1)); i0 = su.x; i1 = su.y; } \
                mmaq(r[(i >> 1) & 1][i & 1], &F[4 * i], ob[(i >> 2) * 4 + 2 * (i & 1)], ob[(i >> 2) * 4 + 2 * (i & 1) + 1]); \
                if (wg && i == 2) { i0 = opqf(rcpf(i0)); i1 = opqf(rcpf(i1)); } \
                if (i == PP) { mid; } \
                if (wg && i == POL) POLL(); \
                if (!wg && i == KVP) bulk_copy(TK + 16384 + w8 * 4096, kv_src(c, s + 1) + (16384 + w8 * 4096), 4096, MB_KV); \
                if (i == 12) ra = opq(lop3<0x6A>((l16 >> 1) * 33, 0x1078, u_rs)); } \
            CUT(pb); tail; \
            if (!wg) { i0 = rcpf(i0); i1 = rcpf(i1); } \
            ST_R(0); ST_R(1)
        #define LD_X(r, o) do { ld_g64(r, xa + (o)); ld_g64(r + 2, xa + ((o) + 2048)); ld_g64(r + 4, xa + ((o) + 1024)); ld_g64(r + 6, xa + ((o) + 3072)); } while (0)
        #define REPORT(w, add) asm volatile("{ .reg .pred p; .reg .u32 t; setp.lt.u32 p, %1, 32; mov.u32 t, %1; @p mov.u32 t, %%globaltimer_lo; add.u32 t, t, %3; lop3.b32 t, t, 31, %2, 0xB8; @p st.relaxed.gpu.global.u32 [%0], t; }" \
            :: "l"(at(u_rp + (l16 << 8), rbhi)), "r"(t16 - (w) * 512), "r"(s), "r"(add) : "memory")
        #define POLL() asm volatile("{ .reg .pred p; setp.ge.u32 p, %5, 3584; mov.u32 %0, 0; mov.u32 %1, 0; mov.u32 %2, 0; mov.u32 %3, 0; @p ld.relaxed.gpu.global.v4.u32 {%0,%1,%2,%3}, [%4]; }" \
            : "=&r"(an[0]), "=&r"(an[1]), "=&r"(an[2]), "=&r"(an[3]) : "l"(at(u_ta + l16, rbhi)), "r"(t16) : "memory")
        #define CK() opq(t16 * 2 + ((l16 >> 4) & 0x1C))
        #define CHK_B(ck, tp, par) do { mbar_wait(MB_B, (par) & 1); \
            const uint32_t c0 = lds32(MEM - 4096 + ck), c1 = lds32(MEM + ck); barrive<B_START, 256>(); CUT(pa); \
            asm volatile("st.shared.u8 [%0], %1;" :: "r"(SUM + 252 + w8), "r"(late(lop3<0x7E>(c0, tp, c1), 0, bc < SPIN_LIMIT)) : "memory"); } while (0)
        #define GET_B(sl) do { const uint32_t a_ = u_bl ^ (sl); bulk_copy(MEM, at(a_, rbhi), 4096, MB_B); bulk_copy(MEM + 4096, at(a_ ^ 0x3000, rbhi), 4096, MB_B); } while (0)
        if constexpr (wg == 0) {
            float a[4][4], v[4][4] = {};
            uint32_t b[16][4];
            barrive_if<B_RD, 256>(redo);
            CUT(pa);
            bsync<B_START, 256>();
            LDB(8); __syncwarp(); LDB(9); __syncwarp(); LDB(10); __syncwarp(); LDB(11);
            PROF(0);
            #pragma unroll
            for (int n = 0; n < 16; n++) {
                const int i = n ^ 8;
                if (!(n & 1)) {
                    CUT(pa);
                    if (n == H0 + 2) { redo = lds32(SUM + 256 + opq(t16 >> 16)); __syncwarp(); }
                    if (n < 12) { LDB((n + 4) ^ 8); __syncwarp(); LDB((n + 5) ^ 8); __syncwarp(); }
                    if (n == H0) { bsync<B_H0, 256>(); CUT(pa); }
                }
                if (n < 2) { a[2 * n][0] = a[2 * n][1] = a[2 * n][2] = a[2 * n][3] = a[2 * n + 1][0] = a[2 * n + 1][1] = a[2 * n + 1][2] = a[2 * n + 1][3] = 0.f; }
                mmaq(a[2 * (i & 1)], &W[8 * i], b[i][0], b[i][1]); mmaq(a[2 * (i & 1) + 1], &W[8 * i + 4], b[i][2], b[i][3]);
            }
            CUT(pa);
            redo = late(redo, 0, ~0u);
            if (__builtin_expect(redo, 0)) { __syncwarp(); continue; }
            const uint32_t mG = (l16 & 0x1C0) ? 0 : 0x10001u, mT = (l16 & 0x30) ? 0 : 1;
            ST_X();
            CUT(pa);
            PROF(1);
            const char* const xa = at(u_x + (t16 >> 1), rbhi);
            float sc[4][4];
            uint32_t k[8], A[16], q[16], kf[16];
            #define LD_Q() do { LD_X(q, 0); { const char* const xa = at((u_x + (opq(t16) >> 1)) ^ 256, rbhi); LD_X(q + 8, 0); } } while (0)
            #define LD_A(i) ldsm4t(A[4 * i], A[4 * i + 1], A[4 * i + 2], A[4 * i + 3], TQ + (i & 1) * 1024 + ((i & 2) ? qb : qa))
            #define LD_K(mid) do { const uint32_t ka = opq(pa & 0xFFFF), kb = opq(ka ^ 0x400), qa = opq(pa >> 16), qb = opq(qa ^ 0x100); uint32_t k1[16]; \
                _Pragma("unroll") for (int i = 0; i < 4; i++) { const uint32_t a_ = opq(((i & 1) ? kb : ka) ^ ((i >> 1) << 4)); \
                    ldsm4t(kf[4 * i], kf[4 * i + 1], kf[4 * i + 2], kf[4 * i + 3], TK + a_); ldsm4t(k1[4 * i], k1[4 * i + 1], k1[4 * i + 2], k1[4 * i + 3], TK + 8192 + a_); __syncwarp(); } \
                LD_A(0); LD_A(1); if (KM) { LD_A(2); LD_A(3); CUT(pb); } if (KM == 2) { mid; } \
                badk = opq(stale<8, 1>(kf, tau2) | stale<8, 1>(k1, tau2)); \
                _Pragma("unroll") for (int i = 0; i < 8; i++) kf[i] = opq(hadd2(kf[i], k1[i])); \
                if (!KM) { CUT(pb); LD_A(2); LD_A(3); } \
                _Pragma("unroll") for (int i = 8; i < 16; i++) kf[i] = opq(hadd2(kf[i], k1[i])); \
                if (KM < 2) { mid; } \
                badk = opq(lop3<0xA8>(badk | stale<8, 1>(A, tau2), stale<8, 1>(A + 8, tau2), mG)); \
                _Pragma("unroll") for (int i = 0; i < 8; i++) A[2 * i + 1] = opq(hadd2(A[2 * i], A[2 * i + 1])); } while (0)
            uint32_t badk;
            #pragma unroll
            for (int i = 7; i >= 0; i--) V_MMA(i, 0);
            if (QV) ST_V();
            CUT(pb);
            DELAY(QD);
            LD_Q();
            CUT(pb);
            if (!QV) { ST_V(); CUT(pb); }
            bsync<B_H2, 256>();
            #define GET_K() CUT(pb); bsync<B_H3, 256>(); LD_X(k, 4096); CUT(pb); PROF(3)
            LD_K(GET_K());
            AGAIN(1, if (late(badk, 0, ~0u)) { RETRY(0, 1); refetch_kv(c, s, l16 | (opq(n_) >> 24)); LD_K(;); } LD_Q(); LD_X(k, 4096); sts32(SUM + 268, s + 1),
                  late(lop3<0xA8>(stale<4, 2>(q, tau), stale<4, 2>(q + 8, tau), mT), badk, ~0u))
            #pragma unroll
            for (int i = 0; i < 4; i++) {
                A[4 * i] = hadd2(q[4 * i], q[4 * i + 2]); A[4 * i + 2] = hadd2(q[4 * i + 1], q[4 * i + 3]);
                if (i < 2) { sc[i][0] = sc[i][1] = sc[i][2] = sc[i][3] = sc[2 + i][0] = sc[2 + i][1] = sc[2 + i][2] = sc[2 + i][3] = 0.f; }
                mmaq(sc[i & 1], A + 4 * i, kf[2 * i], kf[2 * i + 1]); mmaq(sc[2 + (i & 1)], A + 4 * i, kf[8 + 2 * i], kf[9 + 2 * i]);
            }
            sts128f(SC + t16, sc[0][0] + sc[1][0], sc[0][1] + sc[1][1], sc[2][0] + sc[3][0], sc[2][1] + sc[3][1]);
            barrive<B_S1, 256>();
            sts128f(SC + 3072 + t16, sc[0][2] + sc[1][2], sc[0][3] + sc[1][3], sc[2][2] + sc[3][2], sc[2][3] + sc[3][3]);
            load_frag<0, WB1>(WO + t16, F);
            const uint32_t sa = opq(l16 + u_sa);
            CUT(pb);
            PROF(4);
            float d[16];
            #pragma unroll 1
            for (int n_ = 0;; n_++) {
                #pragma unroll
                for (int i = 0; i < 4; i++) { d[4 * i] = d[4 * i + 1] = d[4 * i + 2] = d[4 * i + 3] = 0.f; mmaq(d + 4 * i, A + 4 * (i >> 1), k[2 * i], k[2 * i + 1]); }
                if (__builtin_expect(!late(stale<2, 2>(k, tau), stale<2, 2>(k + 4, tau), mT), 1) || n_ >= SPIN_LIMIT) break;
                RETRY(2, 1);
                LD_X(k, 4096);
            }
            sts64f(SC + 2048 + sa, (d[0] + d[4]) + (d[8] + d[12]), (d[1] + d[5]) + (d[9] + d[13]));
            barrive<B_SC, 256>();
            CUT(pb);
            sts64f(SC + 5120 + sa, (d[2] + d[6]) + (d[10] + d[14]), (d[3] + d[7]) + (d[11] + d[15]));
            PROF(5);
            if (w8 == 0) {
                float x[10];
                bsync<B_S0, 128>();
                tok_scores(x, SC + 3072 + l16); mem_scores(x, SC + 3072 + l16);
                __syncwarp();
                load_frag<WB1, WB2>(WO + t16, F);
                const int g = l16 >> 6, lim = 8 * (g >> 1) + 2 * (c & 3) + (g & 1) - ((l16 >> 1) & 0x18);
                #pragma unroll
                for (int i = 0; i < 8; i++) if (i > lim) x[i] = -INFINITY;
                const float ms = opqf(-SCL * max4lanes(fmaxf(max8(x), fmaxf(x[8], x[9]))));
                CUT(pb);
                #pragma unroll
                for (int i = 0; i < 10; i++) x[i] = ex2(fmaf(x[i], SCL, ms));
                load_frag<WB2, WB3>(WO + t16, F);
                sts128(PT + l16, make_uint4(pack2(x[0], x[1]), pack2(x[2], x[3]), pack2(x[4], x[5]), pack2(x[6], x[7])));
                sts32(PT + 512 + (l16 >> 2), pack2(x[8], x[9]));
                if (!ONE) barrive<B_PT, 160>();
            } else {
                if (ANN == 2) { bsync<B_S0, 128>(); const uint32_t f = lds32(SUM + 268 + opq(t16 >> 16)); REPORT(3, f == s + 1 ? P(2) : 0); } else barrive<B_S0, 128>();
                if (w8 == 1) { if (seg < NSEG) mbar_wait(MB_X, seg & 1); }
                else if (w8 == 2) {
                    bulk_expect(MB_KV, 36864);
                    bulk_copy(TK, kv_src(c, s + 1), 16384, MB_KV); bulk_copy(TQ, kv_src(c, s + 1) + (32768 + (c & 3) * 4096), 4096, MB_KV);
                    bulk_expect(MB_B, 8192); bulk_expect(MB_R, 4096);
                    __syncwarp();
                }
                bsync<B_SC2, 224>();
                load_frag<WB1, WB3>(WO + t16, F);
                __syncwarp();
                CUT(pb);
            }
            bsync<B_O2, 256>();
            PROF(6);
            float i0, i1;
            WO_MMA(WB3, 0, , );
        } else {
            float a[4][4], v[4][4] = {};
            uint32_t b[16][4];
            if (__builtin_expect(redo, 0)) {
                RETRY(6, 1);
                bsync<B_RD, 256>();
                if (w8 == 4) { bulk_expect(MB_B, 8192); GET_B(1 << 20); }
                const uint32_t ck = CK();
                CHK_B(ck, phase(s - 1), bc);
            }
            CUT(pa);
            bsync<B_H0, 256>();
            LDB(0); __syncwarp(); LDB(1); __syncwarp(); LDB(2); __syncwarp(); LDB(3); __syncwarp();
            redo = lds32(SUM + 256 + opq(t16 >> 16));
            PROF(0);
            #pragma unroll
            for (int i = 0; i < 16; i++) {
                if (!(i & 1)) {
                    CUT(pa);
                    if (i == 6) redo = late(redo, 0, ~0u);
                    if (i == H2) { barrive_if<B_H2, 256>(!redo); CUT(pa); }
                    if (i < 12) { LDB(i + 4); __syncwarp(); LDB(i + 5); __syncwarp(); }
                }
                if (i < 2) { a[2 * i][0] = a[2 * i][1] = a[2 * i][2] = a[2 * i][3] = a[2 * i + 1][0] = a[2 * i + 1][1] = a[2 * i + 1][2] = a[2 * i + 1][3] = 0.f; }
                mmaq(a[2 * (i & 1)], &W[8 * i], b[i][0], b[i][1]); mmaq(a[2 * (i & 1) + 1], &W[8 * i + 4], b[i][2], b[i][3]);
            }
            if (__builtin_expect(redo, 0)) { __syncwarp(); continue; }
            if (H3 == 0) { barrive<B_H3, 256>(); CUT(pb); }
            const uint32_t mG = (l16 & 0x1C0) ? 0 : 0x10001u, mT = (l16 & 0x30) ? 0 : 1;
            ST_X();
            if (H3 == 1) barrive<B_H3, 256>();
            CUT(pa);
            PROF(1);
            #pragma unroll
            for (int i = 7; i >= 0; i--) { V_MMA(i, 8); if (H3 == 9 - i) { CUT(pb); barrive<B_H3, 256>(); CUT(pb); } }
            ST_V();
            CUT(pb);
            if (H3 == 10) { DELAY(KD); barrive<B_H3, 256>(); CUT(pb); DELAY(6); }
            PROF(2);
            uint32_t vf[16], vm[16];
            const uint32_t va = opq(pa), vb = opq(va ^ 0x20);
            #define LD_V() do { _Pragma("unroll") for (int i = 0; i < 4; i++) { const uint32_t a_ = TK + 16384 + ((i & 1) ? vb : va) + (i >> 1) * 4096; \
                ldsm4(vf[4 * i], vf[4 * i + 1], vf[4 * i + 2], vf[4 * i + 3], a_); ldsm4(vm[4 * i], vm[4 * i + 1], vm[4 * i + 2], vm[4 * i + 3], a_ + 8192); } } while (0)
            LD_V();
            __syncwarp();
            load_frag<0, WA0>(WO + t16, F);
            AGAIN(0, refetch_kv(c, s, l16 | (opq(n_) >> 24)); LD_V(), late(stale<4, 4>(vf, tau2) | stale<4, 4>(vf + 1, tau2), stale<4, 4>(vm, tau2) | stale<4, 4>(vm + 1, tau2), mT))
            #pragma unroll
            for (int i = 0; i < 16; i++) vf[i] = opq(hadd2(vf[i], vm[i]));
            const char* const xa = at(u_x + (t16 >> 1), rbhi) + (8192 - 1024);
            DELAY(VD);
            LD_X(vm, 0); LD_X(vm + 8, 4096);
            __syncwarp();
            load_frag<WA0, WA1>(WO + t16, F);
            CUT(pb);
            float x[10];
            bsync<B_S1, 256>();
            const uint32_t qlate = lds32(SUM + 268 + opq(t16 >> 16));
            tok_scores(x, SC + l16);
            const float mt = opqf(max8(x));
            if (ANN == 3) REPORT(7, 0);
            CUT(pb);
            if (__builtin_expect(!late(qlate ^ (s + 1), 0, ~0u), 0)) {
                const char* const xa = at(u_x + (opq(t16) >> 1), rbhi) + (8192 - 1024);
                AGAIN(3, LD_X(vm, 0); LD_X(vm + 8, 4096), late(stale<4, 2>(vm, tau), stale<4, 2>(vm + 8, tau), mT))
            }
            PROF(3);
            bsync<B_SC, 256>();
            mem_scores(x, SC + l16);
            const float m1 = fmaxf(mt, fmaxf(x[8], x[9]));
            const float m2 = __shfl_xor_sync(~0u, m1, 1), m3 = __shfl_xor_sync(~0u, m1, 2), m4 = __shfl_xor_sync(~0u, m1, 3);
            CUT(pb);
            load_frag<WA1, WA2>(WO + t16, F);
            barrive<B_SC2, 224>();
            uint32_t p[5], vs[4];
            #define SUM_V() do { _Pragma("unroll") for (int i = 0; i < 4; i++) { const int e = (i >> 1) * 4 + (i & 1); vs[i] = hadd2(hadd2(vm[e], vm[e + 8]), hadd2(vm[e + 2], vm[e + 10])); } } while (0)
            CUT(pb);
            const float ms = -SCL * fmaxf(fmaxf(m1, m2), fmaxf(m3, m4));
            PROF(5);
            #pragma unroll
            for (int i = 0; i < 10; i++) x[i] = fmaf(x[i], SCL, ms);
            x[8] = opqf(ex2(x[8])); x[9] = opqf(ex2(x[9]));
            CUT(pb);
            uint32_t badv = late(stale<4, 2>(vm, tau), stale<4, 2>(vm + 8, tau), mT);
            SUM_V();
            #pragma unroll
            for (int i = 0; i < 4; i++) { x[i] = opqf(ex2(x[i])); vs[i] = opq(vs[i]); }
            const uint32_t z0 = t16 >> 16;
            uint32_t one[4] = {opq(ONES | z0), opq(ONES ^ z0), opq(ONES + z0), opq(ONES - z0)};
            CUT(pb);
            #pragma unroll
            for (int i = 4; i < 8; i++) x[i] = ex2(x[i]);
            #pragma unroll
            for (int i = 0; i < 5; i++) p[i] = pack2(x[2 * i], x[2 * i + 1]);
            float sm[4] = {};
            #define PV(also) do { float o[8] = {}; \
                mma8(o, vs[0], vs[1], p[4]); mma8(o + 4, vs[2], vs[3], p[4]); if (also) mma8(sm, one[0], one[1], p[4]); \
                mmaq(o, vf, p[0], p[1]); mmaq(o + 4, vf + 8, p[0], p[1]); if (also) mmaq(sm, one, p[0], p[1]); \
                mmaq(o, vf + 4, p[2], p[3]); mmaq(o + 4, vf + 12, p[2], p[3]); if (also) mmaq(sm, one, p[2], p[3]); \
                stsm4(OB - 2048 + opq(t16), pack2(o[0], o[1]), pack2(o[2], o[3]), pack2(o[4], o[5]), pack2(o[6], o[7])); } while (0)
            PV(true);
            if (w8 == 4) sts64f(SUM + (l16 >> 1), sm[0], sm[1]);
            if (__builtin_expect(badv, 0)) {
                int n_ = 0;
                uint32_t vm[16];
                const char* const xa = at(u_x + (8192 - 1024) + (opq(t16) >> 1), rbhi);
                do { RETRY(3, 1); LD_X(vm, 0); LD_X(vm + 8, 4096); } while (late(stale<4, 2>(vm, tau), stale<4, 2>(vm + 8, tau), mT) && ++n_ < SPIN_LIMIT);
                SUM_V();
                PV(false);
            }
            if (ONE) bsync<B_O2, 256>(); else { barrive<B_O2, 256>(); bsync<B_O, 128>(); }
            PROF(6);
            float i0 = sm[0], i1 = sm[1];
            #define GET_P() if (!ONE) bsync<B_PT, 160>(); lds128u(p, PT + l16); p[4] = lds32(PT + 512 + (l16 >> 2))
            #define TOK_PV() { const uint32_t z = t16 >> 17; one[0] = ONES | z; one[1] = ONES ^ z; one[2] = ONES + z; one[3] = ONES - z; } \
                _Pragma("unroll") for (int i = 0; i < 12; i++) ot[i >> 2][0][i & 3] = ot[i >> 2][1][i & 3] = 0.f; \
                mma8(ot[0][0], vs[0], vs[1], p[4]); mma8(ot[1][0], vs[2], vs[3], p[4]); mma8(ot[2][0], one[0], one[1], p[4]); \
                mmaq(ot[0][1], vf + 4, p[2], p[3]); mmaq(ot[1][1], vf + 12, p[2], p[3]); mmaq(ot[2][1], one, p[2], p[3]); CUT(pa)
            WO_MMA(WA2, WA3, GET_P(), TOK_PV());
            CUT(pa);
            mmaq(ot[0][0], vf, p[0], p[1]); mmaq(ot[1][0], vf + 8, p[0], p[1]); mmaq(ot[2][0], one, p[0], p[1]);
            CUT(pb);
            barrive<B_GO, 256>();
        }
        CUT(pb);
        PROF(7);
        #define PK_O() const float j0 = rcpf(ot[2][0][0] + ot[2][1][0]), j1 = rcpf(ot[2][0][1] + ot[2][1][1]); uint32_t ow[4]; \
            _Pragma("unroll") for (int i = 0; i < 4; i++) \
                ow[i] = opq(pack2((ot[i >> 1][0][2 * (i & 1)] + ot[i >> 1][1][2 * (i & 1)]) * j0, (ot[i >> 1][0][2 * (i & 1) + 1] + ot[i >> 1][1][2 * (i & 1) + 1]) * j1))
        #define ST_O() do { uint32_t* og = (uint32_t*)((char*)g_O + (u_og + (l16 >> 2))); \
            _Pragma("unroll") for (int i = 0; i < 4; i++) og[(i >> 1) * 256 + (i & 1) * 32] = ow[i]; } while (0)
        #define BSO() ((u_bs) ^ ((l16 & 0x10) + ((l16 >> 3) & 0xC) + (l16 & 0x80) * 0x20 + (l16 & 0x100) * 0x80))
        const uint32_t taus = phase(seg);
        const uint64_t* const dq = c_xd + (s & 1) * 32; const uint64_t* const dv = dq + (wg * 16 | (prm.zero & s));
        float acc[16], acv[16];
        uint32_t u[8];
        if constexpr (wg == 0) {
            if (s == NSEG - 1) { bsync<B_GO, 256>(); st_g32(at(BSO(), rbhi), 0); mbar_wait(MB_KV, 0); break; }
            load_frag<16 - EV, 16, 2048>(VEB + t16, T);
            bsync<B_GO, 256>();
            PROF(8);
            wg_run<0, 16 - EV>(acv, T, dv);
            wg_run<16 - EV, 16>(acv, T, dv);
            wg_run<0, 5>(acc, W, dq); wg_wait<1>();
            qk_pack(acv, u);
            #pragma unroll
            for (int i = 0; i < 8; i++) u[i] = opq(u[i]);
            CUT(pa);
            wg_run<5, 8>(acc, W, dq);
            __syncwarp();
            sts128(SC + opq(t16), make_uint4(u[0], u[1], u[2], u[3])); sts128(SC + 2048 + opq(t16), make_uint4(u[4], u[5], u[6], u[7]));
            barrive<B_VX, 256>();
            __syncwarp();
            PROF(9);
            wg_run<8, 12>(acc, W, dq);
            CUT(pa);
            char* const bs = at(opq(BSO()), opq(rbhi));
            CUT(pa);
            wg_run<12, 15>(acc, W, dq);
            CUT(pa);
            const uint32_t ro = opq(l16 * 8 + ((l16 & 0x70) ^ ((w8 & 3) << 5))), ro2 = opq(ro ^ 0x10);
            const uint32_t mG = opq((l16 & 0x1C0) ? 0 : 0x10001u), mB = opq((((l16 >> 2) & 4) + ((l16 >> 5) & 3)) == ((u_bs >> 7) & 7) ? 1 : 0), zz = t16 >> 18;
            CUT(pa);
            wg_run<15, 18>(acc, W, dq);
            CUT(pa);
            const uint32_t one[4] = {opq(ONES | zz), opq(ONES ^ zz), opq(ONES + zz), opq(ONES - zz)};
            const uint32_t par = s & 1, tt = tau * 0x10001u;
            CUT(pa);
            wg_run<18, RP>(acc, W, dq);
            CUT(pa);
            PROF(10);
            mbar_wait(MB_R, par);
            PROF(14);
            uint32_t x[8], bad;
            float d[4][4];
            #define SUM_R() do { ldsm4t(x[0], x[1], x[2], x[3], RS + ro); ldsm4t(x[4], x[5], x[6], x[7], RS + ro2); \
                _Pragma("unroll") for (int i = 0; i < 4; i++) { d[i][0] = d[i][1] = d[i][2] = d[i][3] = 0.f; mmaq(d[i], one, x[2 * i], x[2 * i + 1]); } } while (0)
            #define PUT_B() do { bad = late(stale<2, 1>(x, tt), stale<2, 1>(x + 2, tt), mG); \
                const uint32_t w0 = pack2(d[0][0] + d[1][0], d[0][1] + d[1][1]), w1 = pack2(d[2][0] + d[3][0], d[2][1] + d[3][1]); \
                asm volatile("{ .reg .pred p; setp.eq.b32 p, %2, 0; @p st.relaxed.gpu.global.u32 [%0], %1; }" :: "l"(bs), "r"(tagm((l16 & 0x40) ? w1 : w0, mB, tt)), "r"(bad) : "memory"); } while (0)
            SUM_R();
            CUT(pa);
            wg_run<RP, (RP + RQ < 32 ? RP + RQ : 32)>(acc, W, dq);
            if (RP + RQ >= RL) barrive<B_BT, 256>();
            CUT(pa);
            PUT_B();
            const uint32_t tb = lds32(SUM + 272 + 28 + zz);
            CUT(pa);
            PROF(11);
            if (RP + RQ < RL) { wg_run<RP + RQ, RL>(acc, W, dq); __syncwarp(); barrive<B_BT, 256>(); __syncwarp(); }
            wg_run<(RP + RQ < RL ? RL : RP + RQ), 32>(acc, W, dq);
            CUT(pa);
            AGAIN(5, ld_g128(x, at(u_rl + opq(ro), rbhi)); ld_g128(x + 4, at(u_rl + opq(ro2), rbhi)); sts128(RS + ro, make_uint4(x[0], x[1], x[2], x[3])); sts128(RS + ro2, make_uint4(x[4], x[5], x[6], x[7]));
                     CUT(pa); __syncwarp(); SUM_R(); PUT_B(), bad)
            if (w8 == 3) {
                TRC(13, gtime() - tb);
                wait_g(tb, t16);
                GET_B(0);
                PROFW(13, 3);
            } else mbar_wait(MB_KV, ~s & 1);
            const uint32_t ps = opq(pb & 0xFFFF), ps2 = opq(ps ^ HI8);
            char* const qd0 = TOK_DST() + ps; char* const qd1 = TOK_DST() + ps2;
            wg_wait<0>();
            pack_tag(acc, u, taus);
            #pragma unroll
            for (int i = 0; i < 8; i++) u[i] = opq(u[i]);
            CUT(pa);
            bsync<B_S0, 128>();
            st_if(seg < NSEG, qd0, u); st_if(seg < NSEG, qd1, u + 4);
            if (XP == 1) load_x(tmX, c, seg + 1, (s & 1) ? XT : XT2, w8 == 1 && seg + 1 < NSEG);
            PROF(12);
        } else {
            #define LAST() __reduce_max_sync(~0u, max(max(an[0], an[1]), max(an[2], an[3])))
            PK_O();
            CUT(pa);
            if (s == NSEG - 1) { ST_O(); break; }
            PROF(8);
            if (w8 != 7) load_frag<16 - EV, 16 - EV + TA0, 2048>(VEB + t16, T);
            else {
                uint32_t tr = LAST();
                AGAIN(8, ld_g128(an, at(u_ta + l16, rbhi)); tr = LAST(), late(stale<2, 1>(an, s), stale<2, 1>(an + 2, s), 31))
                tr = (tr & ~31u) + P(0);
                TRC(14, gtime() - tr);
                wait_g(tr, t16);
                if (R4) { for (int i = 0; i < 4; i++) bulk_copy(RS + i * 1024, at(u_rl + i * 1024, rbhi), 1024, MB_R); }
                else bulk_copy(RS, at(u_rl, rbhi), 4096, MB_R);
                PROFW(14, 3);
                if (XP == 3) load_x(tmX, c, seg + 1, (s & 1) ? XT : XT2, seg + 1 < NSEG);
                sts32(SUM + 272 + 28, tr + P(1));
                load_frag<16 - EV, 16 - EV + TA0, 2048>(VEB + t16, T);
            }
            CUT(pa);
            bsync<B_VX, 256>();
            lds128u(u, SC - 2048 + opq(t16)); lds128u(u + 4, SC + opq(t16));
            CUT(pa);
            ST_O();
            CUT(pa);
            load_frag<16 - EV + TA0, 16 - EV + TA, 2048>(VEB + t16, T);
            acc_init(acv, u);
            #pragma unroll
            for (int i = 0; i < 16; i++) acv[i] = opqf(acv[i]);
            const uint32_t ps = opq(pb & 0xFFFF), ps2 = opq(ps ^ HI8);
            CUT(pa);
            PROF(9);
            bsync<B_BT, 256>();
            CUT(pa);
            wg_run<0, 3>(acc, W, dq);
            PROF(11);
            wg_run<3, NT, true>(acc, W, dq);
            __syncwarp();
            load_frag<16 - EV + TA, 16, 2048>(VEB + t16, T);
            __syncwarp();
            wg_run<NT, NB>(acc, W, dq);
            char* const qd0 = TOK_DST() + ps; char* const qd1 = TOK_DST() + ps2;
            const uint32_t ck = CK();
            wg_run<NB, 32>(acc, W, dq);
            wg_run<0, 5, true>(acv, T, dv);
            wg_wait<1>();
            PROF(12);
            pack_tag(acc, u, taus);
            #pragma unroll
            for (int i = 0; i < 8; i++) u[i] = opq(u[i]);
            CUT(pa);
            wg_run<5, 16 - EV>(acv, T, dv);
            __syncwarp();
            st_if(seg < NSEG, qd0, u); st_if(seg < NSEG, qd1, u + 4);
            __syncwarp();
            wg_run<16 - EV, 16>(acv, T, dv);
            CUT(pa);
            PROF(10);
            CHK_B(ck, tau, ~bc);
            CUT(pa);
            wg_wait<0>();
            PROF(13);
            pack_tag(acv, u, taus);
            if (XP == 2) load_x(tmX, c, seg + 1, (s & 1) ? XT : XT2, w8 == 5 && seg + 1 < NSEG);
            st_if(seg < NSEG, qd0 + 16384, u); st_if(seg < NSEG, qd1 + 16384, u + 4);
        }
        s++;
        u_rs ^= 1 << 20; u_rl ^= 1 << 20; u_bs ^= 1 << 20; u_bl ^= 1 << 20; u_x ^= 1 << 20; u_xs ^= 1 << 20; u_ta ^= 1 << 20; u_rp ^= 1 << 20; u_og += 262144;
    }
}

__device__ __forceinline__ uint32_t round_trips(char* line, int n) {
    uint32_t best[2] = {0xFFFFu, 0xFFFFu};
    #pragma unroll 1
    for (int i = 0; i < n; i++) {
        uint32_t v; const uint32_t t0 = clk();
        asm volatile("atom.relaxed.gpu.global.exch.b32 %0, [%1], %2;" : "=r"(v) : "l"(line + (i & 1) * 4096), "r"(i) : "memory");
        if (v == 0x7FC1A5A5u) g_err = 2;
        const uint32_t dt = clk() - t0;
        if (i & 1) best[1] = min(best[1], dt); else best[0] = min(best[0], dt);
    }
    return (__popc((uint32_t)(uintptr_t)line & HOME_BITS) & 1) ? best[1] | best[0] << 16 : best[0] | best[1] << 16;
}
__device__ __forceinline__ int role(char* rb) {
    const int b = blockIdx.x, t = threadIdx.x;
    if (!(t & 31)) { const int i = b * 8 + (t >> 5); sts32(mk::SUM + (t >> 3), round_trips(rb + RB_P + (i & 31) * 128 + (i >> 5) * 8192, NPR)); }
    __syncthreads();
    if (t == 0) {
        const uint4 x = lds128(mk::SUM), y = lds128(mk::SUM + 16);
        const uint32_t m = __vminu2(__vminu2(__vminu2(x.x, x.y), __vminu2(x.z, x.w)), __vminu2(__vminu2(y.x, y.y), __vminu2(y.z, y.w)));
        uint32_t sm; asm volatile("mov.u32 %0, %%smid;" : "=r"(sm));
        const uint32_t g = sm < 64 ? (sm & 15) >> 1 : 1 + (sm - 64) % 14 / 2, i = sm < 64 ? sm >> 4 : 4 + (sm - 64) / 14;
        const uint32_t pos = sm < 120 ? g * 16 + i * 2 + (sm & 1) : sm + 8;
        st_g32(g_cls + b, 0x80000000u | (m >> 16 < (m & 0xFFFF)) << 24 | pos << 8 | b);
    }
    uint32_t e = ~0u, own;
    int n = 0;
    do { own = ld_g32(g_cls + b); if (t < NCTA) e = ld_g32(g_cls + t); } while (!((e & own) >> 31) && ++n < SPIN_LIMIT);
    const int below = __syncthreads_count(e < own), n0 = __syncthreads_count(!(e >> 24 & 1));
    const int c0 = 4 * min(max(16, 32 - (NCTA - n0) / 4), n0 / 4);
    return below < c0 ? below : below < n0 ? 128 + below - c0 : below - n0 + c0 < 128 ? below - n0 + c0 : below;
}

__global__ void __launch_bounds__(256, 1)
main_kernel(const __grid_constant__ CUtensorMap tmWq, const __grid_constant__ CUtensorMap tmWk, const __grid_constant__ CUtensorMap tmWv,
            const __grid_constant__ CUtensorMap tmWo, const __grid_constant__ CUtensorMap tmX, const bf16* __restrict__ mem0,
            const bf16* Wo, const __grid_constant__ MainParams prm) {
    using namespace mk;
    extern __shared__ __align__(1024) uint8_t smem_raw[];
    if (smem_u32(smem_raw) != SB) __trap();
    TL(2);
    const int tid0 = threadIdx.x, w8 = __shfl_sync(~0u, tid0 >> 5, 0), wg = w8 >> 2;
    asm volatile("griddepcontrol.wait;" ::: "memory");
    const int c = __shfl_sync(~0u, role(prm.rb), 0), kap = c & 1;
    if (c >= 128) return;
    if (tid0 == 0) {
        for (int i = 0; i < 8; i++) mbar_init(BAR + i * 8, 1);
        sts32(BAR + 120, 0); sts32(SUM + 256, 0); sts32(SUM + 264, TRIES); sts32(SUM + 268, 0);
        asm volatile("fence.mbarrier_init.release.cluster;" ::: "memory");
        asm volatile("fence.proxy.async.shared::cta;" ::: "memory");
        const int col = (c >> 1) * 64, k0 = kap * 512;
        mbar_expect(MB_WQ, 65536); tma2d(WO, &tmWq, col, k0, MB_WQ); tma2d(WO + 32768, &tmWq, col, k0 + 256, MB_WQ);
        mbar_expect(MB_WK, 65536); tma2d(WV, &tmWk, col, k0, MB_WK); tma2d(WV + 32768, &tmWk, col, k0 + 256, MB_WK);
    }
    __syncwarp();
    load_x(&tmX, c, 0, XT, w8 == 0);
    for (int i = tid0; i < 4096; i += 256) {
        const int row = i >> 9, col = i & 511;
        const unsigned short v = __bfloat16_as_ushort(mem0[row * DM + kap * 512 + col]);
        asm volatile("st.shared.u16 [%0], %1;" :: "r"(MEM + col * 16 + row * 2), "h"(v) : "memory");
    }
    asm volatile("fence.proxy.async.shared::cta;" ::: "memory");
    __syncthreads();
    uint32_t W[128], T[64];
    mbar_wait(wg ? MB_WK : MB_WQ, 0);
    load_tile<0, 32>(tile_off(tid0 & 31, 2 * (w8 & 3)) + (wg ? WV : WO), W);
    __syncthreads();
    if (tid0 == 0) {
        mbar_expect(MB_WV, 65536); tma2d(WV, &tmWv, (c >> 1) * 64, kap * 512, MB_WV); tma2d(WV + 32768, &tmWv, (c >> 1) * 64, kap * 512 + 256, MB_WV);
        mbar_expect(MB_WO, 65536);
        for (int i = 0; i < 4; i++) tma2d(WO + i * 16384, &tmWo, (c & 3) * 256 + i * 64, (c >> 2) * DH, MB_WO);
    }
    asm volatile("griddepcontrol.launch_dependents;" ::: "memory");
    uint32_t t16 = tid0 * 16, pa, pb;
    {
        const int lane = tid0 & 31, w = w8 & 3, g = lane >> 2, t = lane & 3;
        auto vec = [](int hf, int gg, int ch) { return hf * 512 + (gg >> 1) * 128 + (gg & 1) * 64 + ((ch ^ (gg >> 1) ^ (hf << 1)) << 4); };
        const int kg = ((lane >> 3) & 1) * 4 + ((lane & 7) >> 1);
        pa = wg ? w * 1024 + vec((lane >> 3) & 1, lane & 7, lane >> 4)
                : ((lane >> 4) * 4096 + w * 1024 + vec(lane & 1, kg, 2 * (w & 1))) | ((lane & 8) * 256 + w * 256 + (lane & 1) * 128 + ((((lane >> 4) ^ (lane & 1)) * 4 + ((lane & 7) >> 1)) << 4)) << 16;
        pb = (wg ? w * 1024 + vec(0, g, t) : t * 4096 + w * 256 + g * 16) | (w * 256 + t * 64 + (g & 3) * 8 + (g >> 2) * 4) << 16;
    }
    mbar_wait(MB_WV, 0);
    load_tile<0, 16>(tile_off(tid0 & 31, 2 * (w8 & 3)) + wg * 32768 + WV, T);
    __syncthreads();
    #pragma unroll
    for (int i = 0; i < 16; i++) sts128(WV + i * 4096 + t16, make_uint4(T[4 * i], T[4 * i + 1], T[4 * i + 2], T[4 * i + 3]));
    int budget = SPIN_LIMIT;
    #pragma unroll 1
    for (int seg = 0; seg < 2; seg++) {
        const uint32_t tau = phase(seg), ps = pb & 0xFFFF;
        float acc[16], acv[16];
        uint32_t u[8];
        mbar_wait(MB_X, seg & 1);
        wg_run<0, 32>(acc, W, c_xd + (prm.zero & seg));
        wg_run<0, 16>(acv, T, c_xd + (wg * 16 | (prm.zero & (seg + 1))));
        wg_wait<0>();
        if (!wg) { qk_pack(acv, u); sts128(SC + t16, make_uint4(u[0], u[1], u[2], u[3])); sts128(SC + 2048 + t16, make_uint4(u[4], u[5], u[6], u[7])); }
        __syncthreads();
        load_x(&tmX, c, seg + 1, XT, w8 == 0);
        if (wg) { lds128u(u, SC - 2048 + t16); lds128u(u + 4, SC + t16); acc_add(acv, u); }
        #pragma unroll 1
        for (int m = 0; m <= wg; m++) {
            pack_tag(acc, u, tau);
            st_if(true, tok_dst(c, seg, wg) + (m * 16384 + ps), u); st_if(true, tok_dst(c, seg, wg) + (m * 16384 + (ps ^ HI8)), u + 4);
            #pragma unroll
            for (int i = 0; i < 16; i++) acc[i] = acv[i];
        }
        __syncthreads();
    }
    {
        mbar_wait(MB_WO, 0);
        const int lane = tid0 & 31;
        const uint32_t a = (tid0 >> 6) * 16384 + tile_off(lane, (w8 & 1) * 4) + WO;
        #pragma unroll
        for (int i = 0; i < 16; i++) ldsm4t(T[4 * i], T[4 * i + 1], T[4 * i + 2], T[4 * i + 3], ((i & 2) ? a ^ 32 : a) + ((i >> 2) + 4 * (i & 1)) * 2048);
        __syncthreads();
        const uint32_t d = WO + w8 * 512 + ((lane >> 3) * 4 + (lane & 3)) * 16 + ((lane >> 2) & 1) * 4;
        #pragma unroll
        for (int i = 0; i < 64; i++) sts32(d + (i >> 2) * 4096 + (i & 1) * 256 + (i & 2) * 4, T[i]);
        load_frag<0, 16>(WV + t16, T);
    }
    uint32_t u_rs, u_rl, u_bs, u_bl;
    const uint32_t rbhi = (uint32_t)((uintptr_t)prm.rb >> 32);
    {
        const int lane = tid0 & 31, h = c >> 2, j = c & 3;
        uint32_t cl;
        const int G = h >> 4, rk = h & 15;
        auto half = [&](uint32_t off) { return (uint32_t)(uintptr_t)prm.rb + off + ((__popc(off & HOME_BITS) ^ G) & 1) * 4096; };
        auto rpair = [&](int m) { return RB_R + (j << 16) + ((m & 1) << 13) + (((m >> 1) & 3) << 14) + ((m >> 3) << 18); };
        u_rs = (half(rpair(2 * w8)) ^ (G << 12)) + h * 128 + (h & 7) * 16;
        u_rl = half(rpair(rk));
        u_bs = (uint32_t)(uintptr_t)prm.rb + RB_B + ((j & 1) << 13) + ((j >> 1) << 16) + rk * 256 + G * 128 + (w8 & 3) * 32;
        u_bl = half(RB_B + (kap << 16));
        if (w8 == 0) {
            const char* v0 = kv_src(c, 0) + 16384 + lane * 128;
            do cl = ld_g32(v0) & ld_g32(v0 + 4096) & ld_g32(v0 + 8192) & ld_g32(v0 + 12288); while (__any_sync(~0u, !(cl & 1)) && --budget > 0);
            kv_expect(36864); kv_copy(TK, kv_src(c, 0), 32768); kv_copy(TQ, kv_src(c, 0) + 32768 + j * 4096, 4096);
        }
    }
    mbar_wait(MB_KV, 0);
    asm volatile("fence.proxy.async.shared::cta;" ::: "memory");
    TLX(7);
    __syncwarp();
    const Ctx cx = {u_rs, u_rl, u_bs, u_bl, (uint32_t)(uintptr_t)prm.rb, rbhi, w8, c};
    if (wg) steps<1>(W, T, t16, pa, pb, cx, &tmX, prm); else steps<0>(W, T, t16, pa, pb, cx, &tmX, prm);
    TLX(3);
}

namespace ck {
constexpr uint32_t U = 0;
constexpr uint32_t UPL = 136 * 16 + 64;
constexpr uint32_t UCH = 2 * UPL;
constexpr uint32_t F = 8 * UCH;
constexpr uint32_t FCP = 4160;
constexpr uint32_t FCH = 2 * FCP;
constexpr uint32_t SK = F + 8 * FCH;
constexpr uint32_t SKP = 257 * 16;
constexpr uint32_t SV = SK + 8 * SKP;
constexpr uint32_t SQ = SV + 32768;
constexpr uint32_t TOTAL = SQ + 32768;
}
__global__ void __launch_bounds__(288, 1)
conv_kernel(const bf16* __restrict__ q, const bf16* __restrict__ k, const bf16* __restrict__ v, const bf16* __restrict__ shift_k,
            const bf16* __restrict__ ssm_k, const bf16* __restrict__ ssm_D, const bf16* __restrict__ gate_w,
            const bf16* Wq, const bf16* Wk, const bf16* Wv, const bf16* Wo,
            const __grid_constant__ CUtensorMap tmWq, const __grid_constant__ CUtensorMap tmWk, const __grid_constant__ CUtensorMap tmWv,
            const __grid_constant__ CUtensorMap tmWo, char* rb) {
    using namespace ck;
    extern __shared__ uint8_t smem_raw[];
    const uint32_t sb = smem_u32(smem_raw);
    const int tid = threadIdx.x, w = tid >> 5, lane = tid & 31, c = blockIdx.x;
    TL(0);
    const int d0 = c * 8, t0 = tid * 8;
    if (w == 8) {
        bsync<1, 288>();
        if (lane < 10) {
            const CUtensorMap* m = lane < 2 ? &tmWq : lane < 4 ? &tmWk : lane < 6 ? &tmWv : &tmWo;
            const int c0 = lane < 6 ? (c >> 1) * 64 : (c & 3) * 256 + (lane - 6) * 64, c1 = lane < 6 ? (c & 1) * 512 + (lane & 1) * 256 : (c >> 2) * DH;
            asm volatile("cp.async.bulk.prefetch.tensor.2d.L2.global [%0, {%1, %2}];" :: "l"(m), "r"(c0), "r"(c1) : "memory");
        }
        return;
    }
    #pragma unroll
    for (int i = 0; i < 8; i++) {
        cpa16(sb + SK + i * SKP + (tid + 1) * 16, k + (size_t)(t0 + i) * DM + d0);
        cpa16(sb + SV + i * 4096 + tid * 16, v + (size_t)(t0 + i) * DM + d0);
    }
    cpa_commit();
    #pragma unroll
    for (int i = 0; i < 8; i++) cpa16(sb + SQ + i * 4096 + tid * 16, q + (size_t)(t0 + i) * DM + d0);
    cpa_commit();
    uint4 fx[8], gw[4], x0[4], x1[4], skr[4];
    const uint4* fp = (const uint4*)(ssm_k + (size_t)(d0 + w) * SEQ);
    #pragma unroll
    for (int i = 0; i < 8; i++) fx[i] = fp[lane + 32 * i];
    const int gr = c * 16 + w * 2;
    #pragma unroll
    for (int i = 0; i < 4; i++) {
        gw[i] = ((const uint4*)gate_w)[lane + 32 * i];
        x0[i] = ((const uint4*)(q + (size_t)gr * DM))[lane + 32 * i];
        x1[i] = ((const uint4*)(q + (size_t)(gr + 1) * DM))[lane + 32 * i];
        skr[i] = ((const uint4*)(shift_k + d0 * 4))[i];
    }
    if (c == 0 && tid < 160) g_cls[tid] = 0;
    if (tid < 128) sts128(sb + U + (tid >> 4) * UCH + ((tid >> 3) & 1) * UPL + (tid & 7) * 16, make_uint4(0, 0, 0, 0));
    else if (tid < 136) sts128(sb + SK + (tid & 7) * SKP, make_uint4(0, 0, 0, 0));
    {
        const uint32_t fb = sb + F + w * FCH;
        if (lane < 8) { sts32(fb + 4128 + lane * 4, 0); if (lane) sts32(fb + FCP + 4128 + lane * 4, 0); }
        #pragma unroll
        for (int i = 0; i < 8; i++) {
            const int vi = lane + 32 * i;
            const uint4 x = fx[i];
            const uint32_t a = __shfl_down_sync(~0u, x.x, 1), b = __shfl_sync(~0u, i < 7 ? fx[i < 7 ? i + 1 : 7].x : 0u, 0);
            const uint32_t nxt = lane == 31 ? b : a;
            const uint32_t ea = fb + (2056 - 8 * vi) * 2;
            sts128(ea, make_uint4(__byte_perm(x.w, 0, 0x1032), __byte_perm(x.z, 0, 0x1032), __byte_perm(x.y, 0, 0x1032), __byte_perm(x.x, 0, 0x1032)));
            sts128(ea + FCP, make_uint4(__byte_perm(nxt, x.w, 0x7610), __byte_perm(x.w, x.z, 0x7610), __byte_perm(x.z, x.y, 0x7610), __byte_perm(x.y, x.x, 0x7610)));
            if (vi == 0) sts32(fb + FCP + 4128, x.x & 0xFFFFu);
        }
    }
    {
        float a0 = 0.f, a1 = 0.f;
        #pragma unroll
        for (int i = 0; i < 16; i++) {
            const uint32_t gg = ((const uint32_t*)gw)[i], u0 = ((const uint32_t*)x0)[i], u1 = ((const uint32_t*)x1)[i];
            a0 = fmaf(bflo(u0), bflo(gg), fmaf(bfhi(u0), bfhi(gg), a0));
            a1 = fmaf(bflo(u1), bflo(gg), fmaf(bfhi(u1), bfhi(gg), a1));
        }
        #pragma unroll
        for (int o = 16; o; o >>= 1) { a0 += __shfl_xor_sync(~0u, a0, o); a1 += __shfl_xor_sync(~0u, a1, o); }
        if (lane < 2) g_gate[gr + lane] = 1.f / (1.f + __expf(lane ? -a1 : -a0));
    }
    cpa_wait();
    bsync<1, 288>();
    TLX(14);
    const uint4 dd = *(const uint4*)(ssm_D + d0);
    {
        uint4 kr[11], vr[8];
        #pragma unroll
        for (int i = 0; i < 11; i++) kr[i] = lds128(sb + SK + ((i + 5) & 7) * SKP + (tid + (i >= 3)) * 16);
        #pragma unroll
        for (int i = 0; i < 8; i++) vr[i] = lds128(sb + SV + i * 4096 + tid * 16);
        #pragma unroll
        for (int ch = 0; ch < 8; ch++) {
            const uint32_t s01 = ((const uint32_t*)skr)[2 * ch], s23 = ((const uint32_t*)skr)[2 * ch + 1];
            const float sk[4] = {bflo(s01), bfhi(s01), bflo(s23), bfhi(s23)};
            float kf[11], kv[8];
            #pragma unroll
            for (int i = 0; i < 11; i++) { const uint32_t wd = ((const uint32_t*)&kr[i])[ch >> 1]; kf[i] = (ch & 1) ? bfhi(wd) : bflo(wd); }
            #pragma unroll
            for (int i = 0; i < 8; i++) {
                const uint32_t wv = ((const uint32_t*)&vr[i])[ch >> 1];
                kv[i] = fmaf(kf[i + 3], sk[0], fmaf(kf[i + 2], sk[1], fmaf(kf[i + 1], sk[2], kf[i] * sk[3]))) * ((ch & 1) ? bfhi(wv) : bflo(wv));
            }
            sts128(sb + U + ch * UCH + (tid & 1) * UPL + (8 + (tid >> 1)) * 16,
                   make_uint4(pack2(kv[0], kv[1]), pack2(kv[2], kv[3]), pack2(kv[4], kv[5]), pack2(kv[6], kv[7])));
        }
    }
    bsync<2, 256>();
    TL(9);
    {
        const int g = lane >> 2, t = lane & 3;
        float acc[16][4];
        #pragma unroll
        for (int i = 0; i < 16; i++) acc[i][0] = acc[i][1] = acc[i][2] = acc[i][3] = 0.f;
        const uint32_t fa = sb + F + w * FCH + ((g & 1) ? (2063 - g + 2 * t) * 2 : FCP + (2064 - g + 2 * t) * 2);
        const uint32_t ua = sb + U + w * UCH + ((lane >> 3) & 1) * UPL + (8 + (lane >> 4) * 8 + (lane & 7)) * 16;
        #pragma unroll 1
        for (int r = 0; r < 8; r++) {
            uint32_t Fr[32];
            #pragma unroll
            for (int m = 0; m < 8; m++) ldsm4(Fr[4 * m], Fr[4 * m + 1], Fr[4 * m + 2], Fr[4 * m + 3], ua - r * 16 + m * 256);
            #pragma unroll
            for (int qq = 0; qq < 16; qq++) {
                const uint32_t o = fa - r * 32 - qq * 256;
                const uint32_t f0 = lds32(o), fp8 = lds32(o - 16), fm8 = lds32(o + 16);
                #pragma unroll
                for (int nt = qq; nt < 16; nt++) mma16(acc[nt], f0, fp8, fm8, f0, Fr[2 * (nt - qq)], Fr[2 * (nt - qq) + 1]);
            }
        }
        __syncwarp();
        const uint32_t ya = sb + F + w * FCH + ((lane >> 3) & 1) * 2048 + ((lane >> 4) * 8 + (lane & 7)) * 16;
        #pragma unroll
        for (int nt = 0; nt < 16; nt += 2)
            stsm4t(ya + nt * 128, pack2(acc[nt][0], acc[nt][1]), pack2(acc[nt][2], acc[nt][3]), pack2(acc[nt + 1][0], acc[nt + 1][1]), pack2(acc[nt + 1][2], acc[nt + 1][3]));
    }
    TL(11);
    bsync<2, 256>();
    {
        uint32_t outw[8][4];
        uint4 qr[8];
        #pragma unroll
        for (int i = 0; i < 8; i++) qr[i] = lds128(sb + SQ + i * 4096 + tid * 16);
        #pragma unroll
        for (int cp = 0; cp < 4; cp++) {
            const uint4 y0 = lds128(sb + F + (2 * cp) * FCH + (tid & 1) * 2048 + (tid >> 1) * 16), y1 = lds128(sb + F + (2 * cp + 1) * FCH + (tid & 1) * 2048 + (tid >> 1) * 16);
            const uint4 u0 = lds128(sb + U + (2 * cp) * UCH + (tid & 1) * UPL + (8 + (tid >> 1)) * 16), u1 = lds128(sb + U + (2 * cp + 1) * UCH + (tid & 1) * UPL + (8 + (tid >> 1)) * 16);
            const uint32_t dw = ((const uint32_t*)&dd)[cp];
            const float D0 = bflo(dw), D1 = bfhi(dw);
            #pragma unroll
            for (int i = 0; i < 8; i++) {
                const uint32_t a0 = ((const uint32_t*)&y0)[i >> 1], a1 = ((const uint32_t*)&y1)[i >> 1], b0 = ((const uint32_t*)&u0)[i >> 1], b1 = ((const uint32_t*)&u1)[i >> 1];
                const float yy0 = fmaf((i & 1) ? bfhi(b0) : bflo(b0), D0, (i & 1) ? bfhi(a0) : bflo(a0));
                const float yy1 = fmaf((i & 1) ? bfhi(b1) : bflo(b1), D1, (i & 1) ? bfhi(a1) : bflo(a1));
                const uint32_t qw = ((const uint32_t*)&qr[i])[cp];
                outw[i][cp] = pack2(bflo(qw) * yy0, bfhi(qw) * yy1);
            }
        }
        #pragma unroll
        for (int i = 0; i < 8; i++) g_A[c * 2048 + i * 256 + tid] = make_uint4(outw[i][0], outw[i][1], outw[i][2], outw[i][3]);
    }
    TL(1);
}

namespace ok {
constexpr int STAGES = 4;
constexpr uint32_t STG = 49152, TOTAL = STAGES * STG + 32768 + 256;
}
#define R8(o) F4(d, o), F4(d, o + 4)
__device__ __forceinline__ void wgmma_n256_ss_tt(float* d, uint64_t da, uint64_t db, int accum) {
    asm volatile("{.reg .pred p; setp.ne.b32 p, %130, 0;\n"
        "wgmma.mma_async.sync.aligned.m64n256k16.f32.bf16.bf16 {%0,%1,%2,%3,%4,%5,%6,%7,%8,%9,%10,%11,%12,%13,%14,%15,"
        "%16,%17,%18,%19,%20,%21,%22,%23,%24,%25,%26,%27,%28,%29,%30,%31,%32,%33,%34,%35,%36,%37,%38,%39,%40,%41,%42,%43,%44,%45,%46,%47,"
        "%48,%49,%50,%51,%52,%53,%54,%55,%56,%57,%58,%59,%60,%61,%62,%63,%64,%65,%66,%67,%68,%69,%70,%71,%72,%73,%74,%75,%76,%77,%78,%79,"
        "%80,%81,%82,%83,%84,%85,%86,%87,%88,%89,%90,%91,%92,%93,%94,%95,%96,%97,%98,%99,%100,%101,%102,%103,%104,%105,%106,%107,%108,%109,%110,%111,"
        "%112,%113,%114,%115,%116,%117,%118,%119,%120,%121,%122,%123,%124,%125,%126,%127}, %128, %129, p, 1, 1, 1, 1;}"
        : R8(0), R8(8), R8(16), R8(24), R8(32), R8(40), R8(48), R8(56), R8(64), R8(72), R8(80), R8(88), R8(96), R8(104), R8(112), R8(120)
        : "l"(da), "l"(db), "r"(accum));
}
#undef R8
__global__ void __cluster_dims__(2, 1, 1) __launch_bounds__(288, 1)
out_kernel(const __grid_constant__ CUtensorMap tmO, const __grid_constant__ CUtensorMap tmWo, const __grid_constant__ CUtensorMap tmA,
           const __grid_constant__ CUtensorMap tmOut, const __grid_constant__ MainParams prm) {
    using namespace ok;
    extern __shared__ __align__(1024) uint8_t smem_raw[];
    const uint32_t SB = smem_u32(smem_raw), AT = SB + STAGES * STG, BAR = AT + 32768;
    if (SB & 1023) __trap();
    const int tid = threadIdx.x, w = tid >> 5, lane = tid & 31;
    const int rank = blockIdx.x & 1, mt = blockIdx.x >> 3, nt = (blockIdx.x >> 1) & 3;
    const uint32_t full = BAR, empty = BAR + 64, afull = BAR + 128;
    if (tid == 0) {
        for (int i = 0; i < STAGES; i++) { mbar_init(full + i * 8, 1); mbar_init(empty + i * 8, 8); }
        mbar_init(afull, 1);
        asm volatile("fence.mbarrier_init.release.cluster;" ::: "memory");
    }
    __syncthreads();
    asm volatile("griddepcontrol.wait;" ::: "memory");
    TL(4);
    if (w == 8) {
        if (lane == 0) {
            int st = 0, ph = 1;
            for (int kb = 0; kb < 32; kb++) {
                if (kb >= STAGES) mbar_wait(empty + st * 8, ph);
                mbar_expect(full + st * 8, STG);
                tma3d(SB + st * STG, &tmO, 0, (rank * 32 + kb) * 2, mt * 16, full + st * 8);
                tma3d(SB + st * STG + 16384, &tmWo, 0, (rank * 32 + kb) * 64, nt * 4, full + st * 8);
                if (kb == STAGES - 1) { mbar_expect(afull, 32768); tma3d(AT, &tmA, mt * 128, 0, (nt * 2 + rank) * 16, afull); }
                if (++st == STAGES) { st = 0; ph ^= 1; }
            }
        }
        __syncwarp();
        asm volatile("barrier.cluster.arrive.aligned; barrier.cluster.wait.aligned;" ::: "memory");
        asm volatile("barrier.cluster.arrive.aligned; barrier.cluster.wait.aligned;" ::: "memory");
    } else {
        const int wg = w >> 2, g = lane >> 2;
        float acc[128];
        const int tok0 = 32 * (4 * mt + (w >> 1)) + 8 * (g >> 1) + 4 * (w & 1) + (g & 1);
        const float g0 = g_gate[tok0], g1 = g_gate[tok0 + 2];
        int st = 0, ph = 0, pst = 0;
        #pragma unroll 1
        for (int kb = 0; kb < 32; kb++) {
            mbar_wait(full + st * 8, ph);
            const uint64_t da = mkdesc(SB + st * STG + wg * 8192, 128, 1024, 0), db = mkdesc(SB + st * STG + 16384, 8192, 1024, 1);
            wg_fence();
            #pragma unroll
            for (int ks = 0; ks < 4; ks++) wgmma_n256_ss_tt(acc, da + ks * 16, db + ks * 128, (kb | ks) != 0);
            wg_commit();
            wg_wait<1>();
            if (kb > 0 && lane == 0) mbar_arrive(empty + pst * 8);
            pst = st;
            if (++st == STAGES) { st = 0; ph ^= 1; }
        }
        wg_wait<0>();
        TLX(12);
        asm volatile("barrier.cluster.arrive.aligned; barrier.cluster.wait.aligned;" ::: "memory");
        uint32_t peer;
        asm volatile("mapa.shared::cluster.u32 %0, %1, %2;" : "=r"(peer) : "r"(SB + 65536 + tid * 16), "r"(rank ^ 1));
        #define SND(e) pack2(rank ? acc[8 * i + (e)] : acc[64 + 8 * i + (e)], rank ? acc[8 * i + (e) + 1] : acc[65 + 8 * i + (e)])
        #pragma unroll
        for (int i = 0; i < 8; i++)
            asm volatile("st.shared::cluster.v4.b32 [%0], {%1,%2,%3,%4};" :: "r"(peer + i * 4096), "r"(SND(0)), "r"(SND(2)), "r"(SND(4)), "r"(SND(6)) : "memory");
        #undef SND
        asm volatile("barrier.cluster.arrive.aligned; barrier.cluster.wait.aligned;" ::: "memory");
        mbar_wait(afull, 0);
        const float h0 = 1.f - g0, h1 = 1.f - g1;
        const uint32_t la = AT + (lane >> 4) * 2048 + (4 * (w & 1) + 2 * ((lane >> 3) & 1) + (lane & 1)) * 256 + (4 * (w >> 1) + ((lane & 7) >> 1)) * 16;
        const uint32_t ra = SB + (w * 16 + (lane & 15)) * 128;
        #pragma unroll
        for (int i = 0; i < 8; i++) {
            const uint32_t a = ra + (i >> 2) * 16384 + ((((i & 3) * 2 + (lane >> 4)) ^ (lane & 7)) << 4);
            uint32_t r0, r1, r2, r3;
            ldsm4(r0, r1, r2, r3, la + i * 4096);
            const uint4 u = lds128(SB + 65536 + tid * 16 + i * 4096);
            float p[8];
            #pragma unroll
            for (int e = 0; e < 8; e++) { const uint32_t x = ((const uint32_t*)&u)[e >> 1]; p[e] = (rank ? acc[64 + 8 * i + e] : acc[8 * i + e]) + ((e & 1) ? bfhi(x) : bflo(x)); }
            stsm4(a, pack2(fmaf(g0, bflo(r0), h0 * p[0]), fmaf(g0, bfhi(r0), h0 * p[1])), pack2(fmaf(g1, bflo(r1), h1 * p[2]), fmaf(g1, bfhi(r1), h1 * p[3])),
                     pack2(fmaf(g0, bflo(r2), h0 * p[4]), fmaf(g0, bfhi(r2), h0 * p[5])), pack2(fmaf(g1, bflo(r3), h1 * p[6]), fmaf(g1, bfhi(r3), h1 * p[7])));
        }
        asm volatile("fence.proxy.async.shared::cta;" ::: "memory");
        bsync<1, 256>();
        if (tid == 0) {
            for (int hf = 0; hf < 2; hf++)
                asm volatile("cp.async.bulk.tensor.5d.global.shared::cta.bulk_group [%0, {%2, %3, %3, %3, %4}], [%1];"
                    :: "l"(&tmOut), "r"(SB + hf * 16384), "r"(nt * 256 + rank * 128 + hf * 64), "r"(0), "r"(mt * 4) : "memory");
            asm volatile("cp.async.bulk.commit_group;" ::: "memory");
            asm volatile("cp.async.bulk.wait_group 0;" ::: "memory");
        }
        TL(5);
    }
}

typedef CUresult (*EncodeFn)(CUtensorMap*, CUtensorMapDataType, cuuint32_t, void*, const cuuint64_t*, const cuuint64_t*, const cuuint32_t*,
                             const cuuint32_t*, CUtensorMapInterleave, CUtensorMapSwizzle, CUtensorMapL2promotion, CUtensorMapFloatOOBfill);
static void enc(EncodeFn fn, CUtensorMap* m, void* base, int rank, const cuuint64_t* dims, const cuuint64_t* strides, const cuuint32_t* box, CUtensorMapSwizzle sw) {
    cuuint32_t es[5] = {1, 1, 1, 1, 1};
    fn(m, CU_TENSOR_MAP_DATA_TYPE_BFLOAT16, rank, base, dims, strides, box, es, CU_TENSOR_MAP_INTERLEAVE_NONE, sw,
       CU_TENSOR_MAP_L2_PROMOTION_L2_128B, CU_TENSOR_MAP_FLOAT_OOB_FILL_NONE);
}
static MainParams h_prm = {{800, 512, 384, 0, 0, 0, 0, 0, 0, 0, 0, 0}, 0, nullptr};

extern "C" void kernel_launch(void* const* d_in, const int* in_sizes, int n_in, void* d_out, int out_size) {
    const bf16* q = (const bf16*)d_in[0];
    const bf16* k = (const bf16*)d_in[1];
    const bf16* v = (const bf16*)d_in[2];
    const bf16* shift_k = (const bf16*)d_in[3];
    const bf16* ssm_k = (const bf16*)d_in[4];
    const bf16* ssm_D = (const bf16*)d_in[5];
    const bf16* mem0 = (const bf16*)d_in[7];
    const bf16* gate_w = (const bf16*)d_in[13];

    static EncodeFn fn = nullptr;
    static void* pO = nullptr;
    static void* pA = nullptr;
    if (!fn) {
        cudaDriverEntryPointQueryResult qr;
        cudaGetDriverEntryPoint("cuTensorMapEncodeTiled", (void**)&fn, cudaEnableDefault, &qr);
        cudaGetSymbolAddress(&pO, g_O);
        cudaGetSymbolAddress(&pA, g_A);
        void* pRB; cudaGetSymbolAddress(&pRB, g_RB);
        h_prm.rb = (char*)(((uintptr_t)pRB + (4u << 20) - 1) & ~(uintptr_t)((4u << 20) - 1));
        cudaFuncSetAttribute(main_kernel, cudaFuncAttributeMaxDynamicSharedMemorySize, mk::TOTAL);
        cudaFuncSetAttribute(conv_kernel, cudaFuncAttributeMaxDynamicSharedMemorySize, ck::TOTAL);
        cudaFuncSetAttribute(out_kernel, cudaFuncAttributeMaxDynamicSharedMemorySize, ok::TOTAL);
    }
    CUtensorMap mWq, mWk, mWv, mWo, mX, mO, mWo2, mA, mOut;
    {
        cuuint64_t d[2] = {4096, 1024}, s[1] = {8192}; cuuint32_t b[2] = {64, 256};
        enc(fn, &mWq, d_in[8], 2, d, s, b, CU_TENSOR_MAP_SWIZZLE_128B);
        enc(fn, &mWk, d_in[9], 2, d, s, b, CU_TENSOR_MAP_SWIZZLE_128B);
        enc(fn, &mWv, d_in[10], 2, d, s, b, CU_TENSOR_MAP_SWIZZLE_128B);
    }
    {
        cuuint64_t d[2] = {1024, 4096}, s[1] = {2048}; cuuint32_t b[2] = {64, 128};
        enc(fn, &mWo, d_in[11], 2, d, s, b, CU_TENSOR_MAP_SWIZZLE_128B);
        cuuint64_t d2[3] = {64, 4096, 16}, s2[2] = {2048, 128}; cuuint32_t b2[3] = {64, 64, 4};
        enc(fn, &mWo2, d_in[11], 3, d2, s2, b2, CU_TENSOR_MAP_SWIZZLE_128B);
    }
    {
        cuuint64_t d[3] = {64, 2048, 16}, s[2] = {2048, 128}; cuuint32_t b[3] = {64, 32, 8};
        enc(fn, &mX, d_in[0], 3, d, s, b, CU_TENSOR_MAP_SWIZZLE_128B);
    }
    {
        cuuint64_t d[3] = {256, 128, 256}, s[2] = {512, 65536}; cuuint32_t b[3] = {256, 2, 16};
        enc(fn, &mO, pO, 3, d, s, b, CU_TENSOR_MAP_SWIZZLE_NONE);
    }
    {
        cuuint64_t d[5] = {1024, 2, 4, 4, 64}, s[4] = {2048, 16384, 4096, 65536}; cuuint32_t b[5] = {64, 2, 4, 4, 4};
        cuuint64_t da[3] = {2048, 8, 128}, sa[2] = {4096, 32768}; cuuint32_t ba[3] = {128, 8, 16};
        enc(fn, &mA, pA, 3, da, sa, ba, CU_TENSOR_MAP_SWIZZLE_NONE);
        enc(fn, &mOut, d_out, 5, d, s, b, CU_TENSOR_MAP_SWIZZLE_128B);
    }
    cudaStream_t st = cudaStreamPerThread;
    conv_kernel<<<128, 288, ck::TOTAL, st>>>(q, k, v, shift_k, ssm_k, ssm_D, gate_w, (const bf16*)d_in[8], (const bf16*)d_in[9],
                                             (const bf16*)d_in[10], (const bf16*)d_in[11], mWq, mWk, mWv, mWo, h_prm.rb);
    cudaLaunchAttribute at[1];
    at[0].id = cudaLaunchAttributeProgrammaticStreamSerialization;
    at[0].val.programmaticStreamSerializationAllowed = 1;
    cudaLaunchConfig_t cfg = {};
    cfg.stream = st; cfg.attrs = at; cfg.numAttrs = PDL;
    cfg.gridDim = dim3(NCTA); cfg.blockDim = dim3(256); cfg.dynamicSmemBytes = mk::TOTAL;
    cudaLaunchKernelEx(&cfg, main_kernel, mWq, mWk, mWv, mWo, mX, mem0, (const bf16*)d_in[11], h_prm);
    cfg.gridDim = dim3(128); cfg.blockDim = dim3(288); cfg.dynamicSmemBytes = ok::TOTAL;
    cudaLaunchKernelEx(&cfg, out_kernel, mO, mWo2, mA, mOut, h_prm);
}
```

```cpp
#include <cuda_runtime.h>
#include <cuda_bf16.h>
#include <cuda.h>
#include <stdint.h>

typedef __nv_bfloat16 bf16;

constexpr int SEQ = 2048, DM = 1024, NH = 32, DH = 128, NSEG = 64;
constexpr int SPIN_LIMIT = 1 << 13, NCTA = 132;
#define NPR 6
#define PDL 1
#define TPF 1

constexpr uint32_t HOME_BITS = 0xB3000;
constexpr uint32_t RB_R = 0;
constexpr uint32_t RB_B = 0x80000;
constexpr uint32_t RB_T = RB_B + 0x4000;
constexpr uint32_t RB_P = RB_B + 0x20000;
constexpr uint32_t RB_X = 2u << 20;
__device__ uint4 g_RB[(8 << 20) / 16];
__device__ uint32_t g_cls[160];
__device__ uint4 g_T[2 * NH * 3072];
__device__ uint4 g_O[NSEG * 4 * 4096];
__device__ uint4 g_A[SEQ * DM / 8];
__device__ float g_gate[SEQ];
__device__ uint32_t g_err;
#define TL(i)
#define TLX(i)

__device__ __forceinline__ uint32_t smem_u32(const void* p) { return (uint32_t)__cvta_generic_to_shared(p); }
__device__ __forceinline__ uint32_t clk() { uint32_t c; asm volatile("mov.u32 %0, %%clock;" : "=r"(c) :: "memory"); return c; }
__device__ __forceinline__ void ldsm4(uint32_t& r0, uint32_t& r1, uint32_t& r2, uint32_t& r3, uint32_t a) {
    asm volatile("ldmatrix.sync.aligned.m8n8.x4.shared.b16 {%0,%1,%2,%3}, [%4];" : "=r"(r0), "=r"(r1), "=r"(r2), "=r"(r3) : "r"(a) : "memory");
}
__device__ __forceinline__ void ldsm4t(uint32_t& r0, uint32_t& r1, uint32_t& r2, uint32_t& r3, uint32_t a) {
    asm volatile("ldmatrix.sync.aligned.m8n8.x4.trans.shared.b16 {%0,%1,%2,%3}, [%4];" : "=r"(r0), "=r"(r1), "=r"(r2), "=r"(r3) : "r"(a) : "memory");
}
__device__ __forceinline__ void ldsm2(uint32_t& r0, uint32_t& r1, uint32_t a) {
    asm volatile("ldmatrix.sync.aligned.m8n8.x2.shared.b16 {%0,%1}, [%2];" : "=r"(r0), "=r"(r1) : "r"(a) : "memory");
}
__device__ __forceinline__ void stsm4t(uint32_t a, uint32_t r0, uint32_t r1, uint32_t r2, uint32_t r3) {
    asm volatile("stmatrix.sync.aligned.m8n8.x4.trans.shared.b16 [%0], {%1,%2,%3,%4};" :: "r"(a), "r"(r0), "r"(r1), "r"(r2), "r"(r3) : "memory");
}
__device__ __forceinline__ void mma16(float* c, uint32_t a0, uint32_t a1, uint32_t a2, uint32_t a3, uint32_t b0, uint32_t b1) {
    asm volatile("mma.sync.aligned.m16n8k16.row.col.f32.bf16.bf16.f32 {%0,%1,%2,%3}, {%4,%5,%6,%7}, {%8,%9}, {%0,%1,%2,%3};"
        : "+f"(c[0]), "+f"(c[1]), "+f"(c[2]), "+f"(c[3]) : "r"(a0), "r"(a1), "r"(a2), "r"(a3), "r"(b0), "r"(b1));
}
__device__ __forceinline__ void mma8(float* c, uint32_t a0, uint32_t a1, uint32_t b0) {
    asm volatile("mma.sync.aligned.m16n8k8.row.col.f32.bf16.bf16.f32 {%0,%1,%2,%3}, {%4,%5}, {%6}, {%0,%1,%2,%3};"
        : "+f"(c[0]), "+f"(c[1]), "+f"(c[2]), "+f"(c[3]) : "r"(a0), "r"(a1), "r"(b0));
}
__device__ __forceinline__ uint32_t pack2(float lo, float hi) {
    uint32_t r; asm("cvt.rn.bf16x2.f32 %0, %1, %2;" : "=r"(r) : "f"(hi), "f"(lo)); return r;
}
__device__ __forceinline__ uint32_t hadd2(uint32_t a, uint32_t b) {
    uint32_t r; asm("add.rn.bf16x2 %0, %1, %2;" : "=r"(r) : "r"(a), "r"(b)); return r;
}
__device__ __forceinline__ float bflo(uint32_t w) { return __uint_as_float(w << 16); }
__device__ __forceinline__ float bfhi(uint32_t w) { return __uint_as_float(w & 0xFFFF0000u); }
__device__ __forceinline__ void st_g32(void* p, uint32_t v) { asm volatile("st.relaxed.gpu.global.u32 [%0], %1;" :: "l"(p), "r"(v) : "memory"); }
__device__ __forceinline__ void st_g128(void* p, uint32_t a, uint32_t b, uint32_t c, uint32_t d) {
    asm volatile("st.relaxed.gpu.global.v4.u32 [%0], {%1,%2,%3,%4};" :: "l"(p), "r"(a), "r"(b), "r"(c), "r"(d) : "memory");
}
__device__ __forceinline__ uint4 lds128(uint32_t a) { uint4 v; asm volatile("ld.shared.v4.u32 {%0,%1,%2,%3}, [%4];" : "=r"(v.x), "=r"(v.y), "=r"(v.z), "=r"(v.w) : "r"(a) : "memory"); return v; }
__device__ __forceinline__ void sts128(uint32_t a, uint4 v) { asm volatile("st.shared.v4.u32 [%0], {%1,%2,%3,%4};" :: "r"(a), "r"(v.x), "r"(v.y), "r"(v.z), "r"(v.w) : "memory"); }
__device__ __forceinline__ float2 lds64f(uint32_t a) { float2 v; asm volatile("ld.shared.v2.f32 {%0,%1}, [%2];" : "=f"(v.x), "=f"(v.y) : "r"(a) : "memory"); return v; }
__device__ __forceinline__ void sts64f(uint32_t a, float x, float y) { asm volatile("st.shared.v2.f32 [%0], {%1,%2};" :: "r"(a), "f"(x), "f"(y) : "memory"); }
__device__ __forceinline__ void sts32f(uint32_t a, float x) { asm volatile("st.shared.f32 [%0], %1;" :: "r"(a), "f"(x) : "memory"); }
__device__ __forceinline__ void sts32(uint32_t a, uint32_t x) { asm volatile("st.shared.u32 [%0], %1;" :: "r"(a), "r"(x) : "memory"); }
__device__ __forceinline__ uint32_t lds32(uint32_t a) { uint32_t v; asm volatile("ld.shared.u32 %0, [%1];" : "=r"(v) : "r"(a) : "memory"); return v; }
__device__ __forceinline__ void cpa16(uint32_t dst, const void* src) { asm volatile("cp.async.cg.shared.global [%0], [%1], 16;" :: "r"(dst), "l"(src) : "memory"); }
__device__ __forceinline__ void cpa_commit() { asm volatile("cp.async.commit_group;" ::: "memory"); }
__device__ __forceinline__ void cpa_wait() { asm volatile("cp.async.wait_all;" ::: "memory"); }
template <int ID, int N> __device__ __forceinline__ void bsync() { asm volatile("bar.sync %0, %1;" :: "n"(ID), "n"(N) : "memory"); }
template <int ID, int N> __device__ __forceinline__ void barrive() { asm volatile("bar.arrive %0, %1;" :: "n"(ID), "n"(N) : "memory"); }
template <int ID, int N> __device__ __forceinline__ void bsync_if(bool on) { asm volatile("{ .reg .pred p; setp.ne.b32 p, %2, 0; @p bar.sync %0, %1; }" :: "n"(ID), "n"(N), "r"((int)on) : "memory"); }
template <int ID, int N> __device__ __forceinline__ void barrive_if(bool on) { asm volatile("{ .reg .pred p; setp.ne.b32 p, %2, 0; @p bar.arrive %0, %1; }" :: "n"(ID), "n"(N), "r"((int)on) : "memory"); }
template <int ID> __device__ __forceinline__ uint32_t any128(uint32_t x) {
    uint32_t r; asm volatile("{ .reg .pred p; setp.ne.b32 p, %1, 0; bar.red.or.pred p, %2, 128, p; selp.u32 %0, 1, 0, p; }" : "=r"(r) : "r"(x), "n"(ID) : "memory"); return r;
}
__device__ __forceinline__ void mbar_init(uint32_t mb, uint32_t n) { asm volatile("mbarrier.init.shared::cta.b64 [%0], %1;" :: "r"(mb), "r"(n) : "memory"); }
__device__ __forceinline__ void mbar_expect(uint32_t mb, uint32_t bytes) { asm volatile("mbarrier.arrive.expect_tx.shared::cta.b64 _, [%0], %1;" :: "r"(mb), "r"(bytes) : "memory"); }
__device__ __forceinline__ void mbar_arrive(uint32_t mb) { asm volatile("mbarrier.arrive.shared::cta.b64 _, [%0];" :: "r"(mb) : "memory"); }
__device__ __forceinline__ void mbar_wait(uint32_t mb, uint32_t ph) {
    asm volatile("{ .reg .pred p; .reg .u32 n; mov.u32 n, 0;\n"
                 "MW_%=: mbarrier.try_wait.parity.shared::cta.b64 p, [%0], %1; add.u32 n, n, 1; setp.lt.and.u32 p, n, %2, !p; @p bra.uni MW_%=; }"
                 :: "r"(mb), "r"(ph), "n"(SPIN_LIMIT) : "memory");
}
__device__ __forceinline__ void tma2d(uint32_t dst, const CUtensorMap* m, int c0, int c1, uint32_t mb) {
    asm volatile("cp.async.bulk.tensor.2d.shared::cluster.global.mbarrier::complete_tx::bytes [%0], [%1, {%3, %4}], [%2];"
        :: "r"(dst), "l"(m), "r"(mb), "r"(c0), "r"(c1) : "memory");
}
__device__ __forceinline__ void tma3d(uint32_t dst, const CUtensorMap* m, int c0, int c1, int c2, uint32_t mb) {
    asm volatile("cp.async.bulk.tensor.3d.shared::cluster.global.mbarrier::complete_tx::bytes [%0], [%1, {%3, %4, %5}], [%2];"
        :: "r"(dst), "l"(m), "r"(mb), "r"(c0), "r"(c1), "r"(c2) : "memory");
}
__device__ __forceinline__ void bulk_ld(uint32_t dst, const void* src, uint32_t bytes, uint32_t mb) {
    asm volatile("cp.async.bulk.shared::cluster.global.mbarrier::complete_tx::bytes [%0], [%1], %2, [%3];" :: "r"(dst), "l"(src), "r"(bytes), "r"(mb) : "memory");
}
__device__ __forceinline__ uint64_t mkdesc(uint32_t addr, uint32_t lbo, uint32_t sbo, uint32_t swz) {
    return (uint64_t)((addr & 0x3FFFF) >> 4) | ((uint64_t)(lbo >> 4) << 16) | ((uint64_t)(sbo >> 4) << 32) | ((uint64_t)swz << 62);
}
__device__ __forceinline__ void wg_fence() { asm volatile("wgmma.fence.sync.aligned;" ::: "memory"); }
__device__ __forceinline__ void wg_commit() { asm volatile("wgmma.commit_group.sync.aligned;" ::: "memory"); }
template <int N> __device__ __forceinline__ void wg_wait() { asm volatile("wgmma.wait_group.sync.aligned %0;" :: "n"(N) : "memory"); }
#define F4(d, o) "+f"(d[o]), "+f"(d[o + 1]), "+f"(d[o + 2]), "+f"(d[o + 3])
__device__ __forceinline__ void wgmma_n32_rs(float* d, const uint32_t* a, uint64_t db, int accum) {
    asm volatile("{.reg .pred p; setp.ne.b32 p, %21, 0;\n"
        "wgmma.mma_async.sync.aligned.m64n32k16.f32.bf16.bf16 {%0,%1,%2,%3,%4,%5,%6,%7,%8,%9,%10,%11,%12,%13,%14,%15}, {%16,%17,%18,%19}, %20, p, 1, 1, 0;}"
        : F4(d, 0), F4(d, 4), F4(d, 8), F4(d, 12) : "r"(a[0]), "r"(a[1]), "r"(a[2]), "r"(a[3]), "l"(db), "r"(accum));
}
__device__ __forceinline__ void wait_until(uint32_t tgt, uint32_t any) {
    asm volatile("{ .reg .pred p, q; .reg .u32 t; .reg .s32 d; mov.u32 t, %0; setp.ne.u32 q, %1, 0xFFFFFFFF;\n"
                 "WU_%=: @q mov.u32 t, %%clock; sub.s32 d, t, %0; setp.lt.s32 p, d, 0; @p bra.uni WU_%=; }" :: "r"(tgt), "r"(any) : "memory");
}

namespace mk {
constexpr uint32_t SB = 1024;
constexpr uint32_t WV = SB, WO = SB + 65536, XT = SB + 131072, TK = SB + 163840  , TQ = TK + 32768, MEM = TQ + 4096,
                   SC = MEM + 8192  , PT = SC + 6144,
                   OB = SC + 8192, SUM = OB + 2048, BAR = SUM + 512, GRP = BAR + 128, PROFB = BAR + 192,
                   TOTAL = PROFB - SB;
static_assert(TOTAL <= 232448, "shared memory");
constexpr uint32_t MB_WQ = BAR, MB_WK = BAR + 8, MB_WV = BAR + 16, MB_WO = BAR + 24, MB_X = BAR + 32, MB_KV = BAR + 40, MB_R = BAR + 48, MB_B = BAR + 56;
constexpr uint32_t XT2 = WV, RS = WV + 32768, VE = RS + 4096;
enum { B_START = 1, B_H0, B_H2, B_H3, B_S1, B_SC, B_SC2, B_S0, B_O, B_O2, B_PT, B_GO, B_VX, B_RD, B_BT };
constexpr uint64_t XD0 = (uint64_t)(XT >> 4) | ((uint64_t)1 << 16) | ((uint64_t)64 << 32) | ((uint64_t)1 << 62);
constexpr uint32_t TSLOT = NH * 49152;
}
struct MainParams { int d[12]; uint32_t zero; char* rb; };
#define XD(i) (mk::XD0 - ((i) >> 5) * ((mk::XT - mk::XT2) >> 4) + (((i) & 31) >> 2) * 256 + ((i) & 3) * 2)
#define XD4(i) XD(i), XD(i + 1), XD(i + 2), XD(i + 3)
#define XD16(i) XD4(i), XD4(i + 4), XD4(i + 8), XD4(i + 12)
__constant__ __align__(256) uint64_t c_xd[64] = {XD16(0), XD16(16), XD16(32), XD16(48)};
#define CUT(r) asm volatile("{ .reg .pred q; setp.eq.u32 q, %1, 0xFFFFFFFF; @q mov.u32 %0, %%clock; }" : "+r"(r) : "r"(t16) : "memory")
__device__ __forceinline__ uint32_t opq(uint32_t x) { asm volatile("" : "+r"(x)); return x; }
__device__ __forceinline__ float opqf(float x) { asm volatile("" : "+f"(x)); return x; }
#define PROF(i)
#define PROFW(i, w)
#define TRC(i, v)
#define RETRY(i, on)
#define P(i) prm.d[i]
#define DELAY(n) do { if (n) { _Pragma("unroll") for (int i_ = 0; i_ < n; i_++) asm volatile("mad.lo.u32 %0, %0, %1, %0;" : "+r"(pb) : "r"(prm.zero)); CUT(pa); } } while (0)

__device__ __forceinline__ uint32_t tagw(uint32_t w, uint32_t tau) { return (w & ~1u) | tau; }
__device__ __forceinline__ uint32_t ld_g32(const void* p) { uint32_t v; asm volatile("ld.relaxed.gpu.global.u32 %0, [%1];" : "=r"(v) : "l"(p) : "memory"); return v; }
__device__ __forceinline__ void ld_g64(uint32_t* v, const void* p) { asm volatile("ld.relaxed.gpu.global.v2.u32 {%0,%1}, [%2];" : "=r"(v[0]), "=r"(v[1]) : "l"(p) : "memory"); }
__device__ __forceinline__ void ld_g128(uint32_t* v, const void* p) {
    asm volatile("ld.relaxed.gpu.global.v4.u32 {%0,%1,%2,%3}, [%4];" : "=r"(v[0]), "=r"(v[1]), "=r"(v[2]), "=r"(v[3]) : "l"(p) : "memory");
}
__device__ __forceinline__ void st_g64(void* p, uint32_t a, uint32_t b) { asm volatile("st.relaxed.gpu.global.v2.u32 [%0], {%1,%2};" :: "l"(p), "r"(a), "r"(b) : "memory"); }
__device__ __forceinline__ void lds128f(float* v, uint32_t a) { asm volatile("ld.shared.v4.f32 {%0,%1,%2,%3}, [%4];" : "=f"(v[0]), "=f"(v[1]), "=f"(v[2]), "=f"(v[3]) : "r"(a) : "memory"); }
__device__ __forceinline__ void sts128f(uint32_t a, float x, float y, float z, float w) { asm volatile("st.shared.v4.f32 [%0], {%1,%2,%3,%4};" :: "r"(a), "f"(x), "f"(y), "f"(z), "f"(w) : "memory"); }
__device__ __forceinline__ void stsm4(uint32_t a, uint32_t r0, uint32_t r1, uint32_t r2, uint32_t r3) {
    asm volatile("stmatrix.sync.aligned.m8n8.x4.shared.b16 [%0], {%1,%2,%3,%4};" :: "r"(a), "r"(r0), "r"(r1), "r"(r2), "r"(r3) : "memory");
}
__device__ __forceinline__ void mmaq(float* c, const uint32_t* a, uint32_t b0, uint32_t b1) { mma16(c, a[0], a[1], a[2], a[3], b0, b1); }
template <int LUT> __device__ __forceinline__ uint32_t lop3(uint32_t a, uint32_t b, uint32_t c) { uint32_t r; asm("lop3.b32 %0, %1, %2, %3, %4;" : "=r"(r) : "r"(a), "r"(b), "r"(c), "n"(LUT)); return r; }
template <int N, int S> __device__ __forceinline__ uint32_t stale(const uint32_t* x, uint32_t tau) {
    if constexpr (N == 2) return lop3<0x7E>(x[0], tau, x[S]);
    else if constexpr (N == 3) return lop3<0xF6>(stale<2, S>(x, tau), x[2 * S], tau);
    else if constexpr (N == 4 || N == 16) return lop3<0xFC>(stale<N / 2, S>(x, tau), stale<N / 2, S>(x + N / 2 * S, tau), 0);
    else return lop3<0xFE>(stale<3, S>(x, tau), stale<3, S>(x + 3 * S, tau), stale<2, S>(x + 6 * S, tau));
}
__device__ __forceinline__ uint32_t late(uint32_t a, uint32_t b, uint32_t mask) {
    uint32_t r;
    asm volatile("{ .reg .pred p; .reg .b32 t; lop3.b32 t, %1, %2, %3, 0xA8; setp.ne.b32 p, t, 0; vote.sync.any.pred p, p, 0xFFFFFFFF; selp.u32 %0, 1, 0, p; }" : "=r"(r) : "r"(a), "r"(b), "r"(mask));
    return r;
}
#define AGAIN(id, reload, ...) _Pragma("unroll 1") for (int n_ = 0; __builtin_expect(__VA_ARGS__, 0) && n_ < SPIN_LIMIT; n_++) { RETRY(id, 1); reload; }
__device__ __forceinline__ uint32_t tile_off(int lane, int chunk0) {
    return ((lane >> 4) * 8 + (lane & 7)) * 128 + (((chunk0 + ((lane >> 3) & 1)) ^ (lane & 7)) << 4);
}
template <int K0, int K1>
__device__ __forceinline__ void load_tile(uint32_t a, uint32_t* T) {
    #pragma unroll
    for (int ks = K0; ks < K1; ks++) ldsm4t(T[4 * ks], T[4 * ks + 1], T[4 * ks + 2], T[4 * ks + 3], a + ks * 2048);
}
__device__ __forceinline__ void lds128u(uint32_t* v, uint32_t a) { asm volatile("ld.shared.v4.u32 {%0,%1,%2,%3}, [%4];" : "=r"(v[0]), "=r"(v[1]), "=r"(v[2]), "=r"(v[3]) : "r"(a) : "memory"); }
template <int K0, int K1, int STRIDE = 4096>
__device__ __forceinline__ void load_frag(uint32_t a, uint32_t* T) {
    #pragma unroll
    for (int ks = K0; ks < K1; ks++) lds128u(&T[4 * ks], a + ks * STRIDE);
}
template <int L0, int L1, bool INIT = false>
__device__ __forceinline__ void wg_run(float* acc, const uint32_t* A, const uint64_t* d) {
    if (L1 > L0) {
        wg_fence();
        #pragma unroll
        for (int l = L0; l < L1; l++) wgmma_n32_rs(acc, &A[4 * l], d[l], INIT || l != 0);
        wg_commit();
    }
}
__device__ __forceinline__ void load_x(const CUtensorMap* tmX, int c, int seg, uint32_t dst, bool on) {
    asm volatile("{ .reg .pred p; elect.sync _|p, 0xFFFFFFFF; setp.ne.and.b32 p, %6, 0, p;\n"
        "@p mbarrier.arrive.expect_tx.shared::cta.b64 _, [%3], 32768;\n"
        "@p cp.async.bulk.tensor.3d.shared::cluster.global.mbarrier::complete_tx::bytes [%4], [%0, {%5, %1, %2}], [%3]; }"
        :: "l"(tmX), "r"(seg * 32), "r"((c & 1) * 8), "r"(mk::MB_X), "r"(dst), "r"(0), "r"((int)on) : "memory");
}
__device__ __forceinline__ void bulk_expect(uint32_t mb, uint32_t bytes) {
    asm volatile("{ .reg .pred p; elect.sync _|p, 0xFFFFFFFF; @p mbarrier.arrive.expect_tx.shared::cta.b64 _, [%0], %1; }" :: "r"(mb), "r"(bytes) : "memory");
}
__device__ __forceinline__ void bulk_copy(uint32_t dst, const void* src, uint32_t bytes, uint32_t mb) {
    asm volatile("{ .reg .pred p; elect.sync _|p, 0xFFFFFFFF; @p cp.async.bulk.shared::cluster.global.mbarrier::complete_tx::bytes [%0], [%1], %2, [%3]; }"
        :: "r"(dst), "l"(src), "r"(bytes), "r"(mb) : "memory");
    __syncwarp();
}
__device__ __forceinline__ void bulk_copy_if(bool on, uint32_t dst, const void* src, uint32_t bytes, uint32_t mb) {
    asm volatile("{ .reg .pred p; elect.sync _|p, 0xFFFFFFFF; setp.ne.and.b32 p, %4, 0, p; @p cp.async.bulk.shared::cluster.global.mbarrier::complete_tx::bytes [%0], [%1], %2, [%3]; }"
        :: "r"(dst), "l"(src), "r"(bytes), "r"(mb), "r"((int)on) : "memory");
    __syncwarp();
}
__device__ __forceinline__ void kv_expect(uint32_t bytes) { bulk_expect(mk::MB_KV, bytes); }
__device__ __forceinline__ void kv_copy(uint32_t dst, const void* src, uint32_t bytes) { bulk_copy(dst, src, bytes, mk::MB_KV); }
__device__ __forceinline__ uint32_t gtime() { uint32_t c; asm volatile("mov.u32 %0, %%globaltimer_lo;" : "=r"(c) :: "memory"); return c; }
__device__ __forceinline__ void wait_g(uint32_t tgt, uint32_t any) {
    asm volatile("{ .reg .pred p, q; .reg .u32 t; mov.u32 t, %0; setp.ne.u32 q, %1, 0xFFFFFFFF;\n"
                 "WG_%=: @q mov.u32 t, %%globaltimer_lo; sub.u32 t, t, %0; setp.gt.u32 p, t, 0xFFFF0000; @p bra.uni WG_%=; }" :: "r"(tgt), "r"(any) : "memory");
    __syncwarp();
}
__device__ __forceinline__ uint32_t clkv(uint32_t any) {
    uint32_t c; asm volatile("{ .reg .pred q; setp.ne.u32 q, %1, 0xFFFFFFFF; mov.u32 %0, 0; @q mov.u32 %0, %%clock; }" : "=r"(c) : "r"(any) : "memory"); return c;
}
__device__ __forceinline__ char* kv_src(int c, int seg) { return (char*)g_T + ((seg & 1) * mk::TSLOT + (c >> 2) * 49152); }
__device__ __forceinline__ void prefetch_l2(const void* p, uint32_t bytes) {
    asm volatile("{ .reg .pred p; elect.sync _|p, 0xFFFFFFFF; @p cp.async.bulk.prefetch.L2.global [%0], %1; }" :: "l"(p), "r"(bytes) : "memory");
}
__device__ __forceinline__ void refetch_kv(int c, int seg, uint32_t l16) {
    const char* src = kv_src(c, seg);
    #pragma unroll 1
    for (int i = 0; i < 72; i++) {
        uint32_t v[4];
        ld_g128(v, src + (i * 512 + (i >> 6) * (c & 3) * 4096) + l16);
        sts128(mk::TK + i * 512 + l16, make_uint4(v[0], v[1], v[2], v[3]));
    }
    __syncwarp();
}
__device__ __forceinline__ uint32_t phase(int i) { return (~i >> 1) & 1; }
__device__ __forceinline__ void qk_pack(const float* acc, uint32_t* p) {
    #pragma unroll
    for (int i = 0; i < 4; i++) { p[i] = pack2(acc[4 * i], acc[4 * i + 1]); p[4 + i] = pack2(acc[4 * i + 2], acc[4 * i + 3]); }
}
__device__ __forceinline__ void sts128_if(bool on, uint32_t a, const uint32_t* p) {
    asm volatile("{ .reg .pred p; setp.ne.b32 p, %5, 0; @p st.shared.v4.u32 [%0], {%1,%2,%3,%4}; }" :: "r"(a), "r"(p[0]), "r"(p[1]), "r"(p[2]), "r"(p[3]), "r"((int)on) : "memory");
}
__device__ __forceinline__ void st_if(bool on, char* a, const uint32_t* p) {
    asm volatile("{ .reg .pred p; setp.ne.b32 p, %5, 0; @p st.relaxed.gpu.global.v4.u32 [%0], {%1,%2,%3,%4}; }" :: "l"(a), "r"(p[0]), "r"(p[1]), "r"(p[2]), "r"(p[3]), "r"((int)on) : "memory");
}
__device__ __forceinline__ char* tok_dst(int c, int seg, int wg) { return kv_src(c, seg) + (wg ? (c & 1) * 8192 + (c & 2) * 2048 : 32768 + (c & 1) * 2048 + (c & 2) * 512); }
#define HI8 (wg ? 0x220 : 0xC0)
__device__ __forceinline__ void acc_init(float* acc, const uint32_t* p) {
    #pragma unroll
    for (int i = 0; i < 4; i++) { acc[4 * i] = bflo(p[i]); acc[4 * i + 1] = bfhi(p[i]); acc[4 * i + 2] = bflo(p[4 + i]); acc[4 * i + 3] = bfhi(p[4 + i]); }
}
__device__ __forceinline__ void acc_add(float* acc, const uint32_t* p) {
    #pragma unroll
    for (int i = 0; i < 4; i++) { acc[4 * i] += bflo(p[i]); acc[4 * i + 1] += bfhi(p[i]); acc[4 * i + 2] += bflo(p[4 + i]); acc[4 * i + 3] += bfhi(p[4 + i]); }
}
__device__ __forceinline__ void pack_tag(const float* acc, uint32_t* p, uint32_t tau) { qk_pack(acc, p); p[0] = tagw(p[0], tau); p[4] = tagw(p[4], tau); }
constexpr uint32_t ONES = 0x3F803F80u;
__device__ __forceinline__ float rcpf(float x) { float r; asm("rcp.approx.ftz.f32 %0, %1;" : "=f"(r) : "f"(x)); return r; }

#define ANN 2
#define POL 8
#define PRE0 4
#define PRE1 4
#define HC 2
#define HS 1
#define KM 1
#define NLDS 2
#define AL 2
#define RP 26
#define RQ 2
#define RL 29
#define R4 1
#define KVP 12
#define LD7 8
#define XP 3
#define G2 0
#define NB 26
#define BD 8
#define NP 22
#define TA 4
#define TA0 2
#define NT 19
#define VH 1
#define TRIES 200
#define NPW 3
#define EV0 5
#define EV1 8
#define WA1 6
#define WA2 9
#define H2 10
#define QV 1
#define QD 0
#define KD 0
#define VD 0
#define WA0 4
#define ONE 0
#define PP 12
#define OBA 3
#define WA3 1
#define WB1 0
#define WB2 12
#define WB3 13
#define H0 6
#define H3 10
__device__ __forceinline__ uint32_t tagm(uint32_t w, uint32_t mask, uint32_t tau) { return lop3<0xB8>(w, mask, tau); }
__device__ __forceinline__ char* at(uint32_t lo, uint32_t hi) { char* p; asm("mov.b64 %0, {%1,%2};" : "=l"(p) : "r"(lo), "r"(hi)); return p; }
__device__ __forceinline__ float ex2(float x) { float r; asm("ex2.approx.ftz.f32 %0, %1;" : "=f"(r) : "f"(x)); return r; }
__device__ __forceinline__ float max8(const float* x) { return fmaxf(fmaxf(fmaxf(x[0], x[1]), fmaxf(x[2], x[3])), fmaxf(fmaxf(x[4], x[5]), fmaxf(x[6], x[7]))); }
__device__ __forceinline__ float max4lanes(float m) { return fmaxf(fmaxf(m, __shfl_xor_sync(~0u, m, 1)), fmaxf(__shfl_xor_sync(~0u, m, 2), __shfl_xor_sync(~0u, m, 3))); }
constexpr float SCL = 0.08838834764831845f * 1.4426950408889634f;
__device__ __forceinline__ void tok_scores(float* x, uint32_t sa) {
    float y[8];
    lds128f(x, sa); lds128f(y, sa + 1024); lds128f(x + 4, sa + 512); lds128f(y + 4, sa + 1536);
    #pragma unroll
    for (int i = 0; i < 8; i++) x[i] += y[i];
}
__device__ __forceinline__ void mem_scores(float* x, uint32_t sa) {
    float z[8];
    lds128f(z, sa + 2048); lds128f(z + 4, sa + 2560);
    x[8] = (z[0] + z[2]) + (z[4] + z[6]); x[9] = (z[1] + z[3]) + (z[5] + z[7]);
}

struct Ctx { uint32_t u_rs, u_rl, u_bs, u_bl, rblo, rbhi; int w8, c; };
template <int wg>
__device__ __forceinline__ void steps(uint32_t* W, uint32_t* T, uint32_t t16, uint32_t pa, uint32_t pb, const Ctx& cx, const CUtensorMap* tmX, const MainParams& prm) {
    using namespace mk;
    const int c = cx.c, kap = c & 1, w8 = cx.w8;
    const uint32_t rbhi = cx.rbhi;
    uint32_t u_rs = cx.u_rs, u_rl = cx.u_rl, u_bs = cx.u_bs, u_bl = cx.u_bl ^ ((c & 2) << 14);
    uint32_t u_x = cx.rblo + RB_X + (c >> 2) * 16384, u_xs = u_x + kap * 2048 + (c & 2) * 512;
    uint32_t u_ta = ((cx.u_bl & ~0x10000u) ^ (kap << 12)) + (RB_T - RB_B) + 1024;
    uint32_t u_rp = cx.rblo + RB_T + 1024 + c * 4;
    uint32_t u_og = (c & 3) * 65536 + (c >> 2) * 2048 + (w8 & 3) * 256;
    const uint32_t u_sa = (w8 & 2) * 256 + (w8 & 1) * 8;
    #define TOK_DST() tok_dst(c, seg, wg)
    constexpr int EV = wg ? EV1 : EV0;
    constexpr uint32_t VEB = VE + (wg ? EV0 * 2048 - 2048 : 0) - (16 - EV) * 2048;
    static_assert((EV0 + EV1) * 2048 <= 28672, "");
    __syncthreads();
    #pragma unroll
    for (int i = 16 - EV; i < 16; i++) sts128(VEB + i * 2048 + t16, make_uint4(T[4 * i], T[4 * i + 1], T[4 * i + 2], T[4 * i + 3]));
    asm volatile("fence.proxy.async.shared::cta;" ::: "memory");
    #pragma unroll 1
    for (int s = 0, bc = 0, redo = 0;;) {
        bc = opq(bc + 1);
        t16 |= prm.zero & bc;
        const int seg = s + 2;
        const uint32_t tau = phase(s), tau2 = tau * 0x10001u;
        const uint32_t l16 = opq(t16 & 0x1F0);
        uint32_t F[64];
        float ot[3][2][4];
        uint32_t an[4];
        #define LDB(i) ldsm4t(b[i][0], b[i][1], b[i][2], b[i][3], MEM + l16 + (i) * 512)
        #define ST_X() do { char* xs = at(u_xs + (pb >> 16), rbhi) + wg * 4096; \
            st_g32(xs, tagm(pack2((a[0][0] + a[1][0]) + (a[2][0] + a[3][0]), (a[0][2] + a[1][2]) + (a[2][2] + a[3][2])), mG, tau * 0x10001u)); \
            st_g32(xs + 32, tagm(pack2((a[0][1] + a[1][1]) + (a[2][1] + a[3][1]), (a[0][3] + a[1][3]) + (a[2][3] + a[3][3])), mG, tau * 0x10001u)); } while (0)
        #define ST_V() st_g64(at(u_xs + (t16 >> 1), rbhi) + (8192 + wg * 3072), \
            tagm(pack2((v[0][0] + v[1][0]) + (v[2][0] + v[3][0]), (v[0][1] + v[1][1]) + (v[2][1] + v[3][1])), mT, tau), \
            pack2((v[0][2] + v[1][2]) + (v[2][2] + v[3][2]), (v[0][3] + v[1][3]) + (v[2][3] + v[3][3])))
        #define V_MMA(i, o) do { mmaq(v[2 * ((i) & 1)], &T[8 * (i)], b[(o) + (i)][0], b[(o) + (i)][1]); mmaq(v[2 * ((i) & 1) + 1], &T[8 * (i) + 4], b[(o) + (i)][2], b[(o) + (i)][3]); } while (0)
        #define ST_R(i) do { \
                const uint32_t r0 = pack2((r[i][0][0] + r[i][1][0]) * i0, (r[i][0][1] + r[i][1][1]) * i1); \
                const uint32_t r1 = pack2((r[i][0][2] + r[i][1][2]) * i0, (r[i][0][3] + r[i][1][3]) * i1); \
                st_g64(at(ra ^ (i * 0x3000), rbhi), tagm(r0, mT, tau), r1); } while (0)
        #define LD_OB(i) ldsm4t(ob[4 * (i)], ob[4 * (i) + 1], ob[4 * (i) + 2], ob[4 * (i) + 3], OB + l16 + (i) * 512)
        #define WO_MMA(have, more, mid, tail) uint32_t ob[16], ra; float r[2][2][4] = {}; \
            LD_OB(0); __syncwarp(); LD_OB(1); __syncwarp(); if (OBA > 2) { LD_OB(2); __syncwarp(); } \
            _Pragma("unroll") for (int i = have; i < have + more; i++) { lds128u(&F[4 * i], WO + t16 + i * 4096); __syncwarp(); } \
            _Pragma("unroll") for (int i = 0; i < 16; i++) { \
                if (!(i & 1) || (i > 4 && i < 8)) CUT(pb); \
                if (i == 4) LD_OB(OBA); \
                if (i == 5 && OBA == 2) LD_OB(3); \
                { const int n = have + more + i - 8 + OBA; if (i >= 8 - OBA && n < 16) lds128u(&F[4 * n], WO + t16 + n * 4096); } \
                if (wg == 0 && i == 4) { const float2 su = lds64f(SUM + (l16 >> 1)); i0 = su.x; i1 = su.y; } \
                mmaq(r[(i >> 1) & 1][i & 1], &F[4 * i], ob[(i >> 2) * 4 + 2 * (i & 1)], ob[(i >> 2) * 4 + 2 * (i & 1) + 1]); \
                if (wg && i == 2) { i0 = opqf(rcpf(i0)); i1 = opqf(rcpf(i1)); } \
                if (i == PP) { mid; } \
                if (wg && i == POL) POLL(); \
                if (!wg && i == KVP) bulk_copy(TK + 16384 + w8 * 4096, kv_src(c, s + 1) + (16384 + w8 * 4096), 4096, MB_KV); \
                if (i == 12) ra = opq(lop3<0x6A>((l16 >> 1) * 33, 0x1078, u_rs)); } \
            CUT(pb); tail; \
            if (!wg) { i0 = rcpf(i0); i1 = rcpf(i1); } \
            ST_R(0); ST_R(1)
        #define LD_X(r, o) do { ld_g64(r, xa + (o)); ld_g64(r + 2, xa + ((o) + 2048)); ld_g64(r + 4, xa + ((o) + 1024)); ld_g64(r + 6, xa + ((o) + 3072)); } while (0)
        #define REPORT(w, add) asm volatile("{ .reg .pred p; .reg .u32 t; setp.lt.u32 p, %1, 32; mov.u32 t, %1; @p mov.u32 t, %%globaltimer_lo; add.u32 t, t, %3; lop3.b32 t, t, 31, %2, 0xB8; @p st.relaxed.gpu.global.u32 [%0], t; }" \
            :: "l"(at(u_rp + (l16 << 8), rbhi)), "r"(t16 - (w) * 512), "r"(s), "r"(add) : "memory")
        #define POLL() asm volatile("{ .reg .pred p; setp.ge.u32 p, %5, 3584; mov.u32 %0, 0; mov.u32 %1, 0; mov.u32 %2, 0; mov.u32 %3, 0; @p ld.relaxed.gpu.global.v4.u32 {%0,%1,%2,%3}, [%4]; }" \
            : "=&r"(an[0]), "=&r"(an[1]), "=&r"(an[2]), "=&r"(an[3]) : "l"(at(u_ta + l16, rbhi)), "r"(t16) : "memory")
        #define GET_B(sl) do { const uint32_t a_ = u_bl ^ (sl); bulk_copy(MEM, at(a_, rbhi), 4096, MB_B); bulk_copy(MEM + 4096, at(a_ ^ 0x3000, rbhi), 4096, MB_B); } while (0)
        if constexpr (wg == 0) {
            float a[4][4], v[4][4] = {};
            uint32_t b[16][4];
            if (__builtin_expect(redo, 0)) {
                RETRY(6, 1);
                if (w8 == 3) { bulk_expect(MB_B, 8192); GET_B(1 << 20); }
                __syncwarp();
            }
            const uint32_t ck = opq(t16 * 2 + ((l16 >> 4) & 0x1C));
            CUT(pa);
            mbar_wait(MB_B, ~bc & 1);
            LDB(8); __syncwarp(); LDB(9); __syncwarp();
            const uint32_t c0 = lds32(MEM + ck), c1 = lds32(MEM + 4096 + ck);
            __syncwarp();
            #pragma unroll
            for (int n = 2; n < PRE0; n++) { LDB(n ^ 8); __syncwarp(); }
            PROF(0);
            #pragma unroll
            for (int n = 0; n < 16; n++) {
                const int i = n ^ 8;
                if (!(n & 1)) {
                    CUT(pa);
                    if (PRE0 < 8 && n + PRE0 < 16) { LDB((n + PRE0) ^ 8); __syncwarp(); LDB((n + PRE0 + 1) ^ 8); __syncwarp(); }
                    if (PRE0 == 8 && n >= 2 && n < 10) { LDB(n - 2); __syncwarp(); LDB(n - 1); __syncwarp(); }
                    if (n == HC) redo = any128<B_START>(lop3<0x7E>(c0, phase(s - 1), c1) & (s > 0 && bc < SPIN_LIMIT));
                    if (n == H0) { barrive_if<B_H0, 256>(!redo); CUT(pa); }
                    if (n == 12) redo = late(redo, 0, ~0u);
                }
                if (n < 2) { a[2 * n][0] = a[2 * n][1] = a[2 * n][2] = a[2 * n][3] = a[2 * n + 1][0] = a[2 * n + 1][1] = a[2 * n + 1][2] = a[2 * n + 1][3] = 0.f; }
                mmaq(a[2 * (i & 1)], &W[8 * i], b[i][0], b[i][1]); mmaq(a[2 * (i & 1) + 1], &W[8 * i + 4], b[i][2], b[i][3]);
            }
            CUT(pa);
            if (__builtin_expect(redo, 0)) { __syncwarp(); continue; }
            const uint32_t mG = (l16 & 0x1C0) ? 0 : 0x10001u, mT = (l16 & 0x30) ? 0 : 1;
            ST_X();
            CUT(pa);
            PROF(1);
            const char* const xa = at(u_x + (t16 >> 1), rbhi);
            float sc[4][4];
            uint32_t k[8], A[16], q[16], kf[16];
            #define LD_Q() do { LD_X(q, 0); { const char* const xa = at((u_x + (opq(t16) >> 1)) ^ 256, rbhi); LD_X(q + 8, 0); } } while (0)
            #define LD_A(i) ldsm4t(A[4 * i], A[4 * i + 1], A[4 * i + 2], A[4 * i + 3], TQ + (i & 1) * 1024 + ((i & 2) ? qb : qa))
            #define LD_K(mid) do { const uint32_t ka = opq(pa & 0xFFFF), kb = opq(ka ^ 0x400), qa = opq(pa >> 16), qb = opq(qa ^ 0x100); uint32_t k1[16]; \
                _Pragma("unroll") for (int i = 0; i < 4; i++) { const uint32_t a_ = opq(((i & 1) ? kb : ka) ^ ((i >> 1) << 4)); \
                    ldsm4t(kf[4 * i], kf[4 * i + 1], kf[4 * i + 2], kf[4 * i + 3], TK + a_); ldsm4t(k1[4 * i], k1[4 * i + 1], k1[4 * i + 2], k1[4 * i + 3], TK + 8192 + a_); __syncwarp(); } \
                LD_A(0); LD_A(1); if (KM) { LD_A(2); LD_A(3); CUT(pb); } if (KM == 2) { mid; } \
                badk = opq(stale<8, 1>(kf, tau2) | stale<8, 1>(k1, tau2)); \
                _Pragma("unroll") for (int i = 0; i < 8; i++) kf[i] = opq(hadd2(kf[i], k1[i])); \
                if (!KM) { CUT(pb); LD_A(2); LD_A(3); } \
                _Pragma("unroll") for (int i = 8; i < 16; i++) kf[i] = opq(hadd2(kf[i], k1[i])); \
                if (KM < 2) { mid; } \
                badk = opq(lop3<0xA8>(badk | stale<8, 1>(A, tau2), stale<8, 1>(A + 8, tau2), mG)); \
                _Pragma("unroll") for (int i = 0; i < 8; i++) A[2 * i + 1] = opq(hadd2(A[2 * i], A[2 * i + 1])); } while (0)
            uint32_t badk;
            #pragma unroll
            for (int i = 7; i >= 0; i--) V_MMA(i, 0);
            if (QV) ST_V();
            CUT(pb);
            DELAY(QD);
            LD_Q();
            CUT(pb);
            if (!QV) { ST_V(); CUT(pb); }
            bsync<B_H2, 256>();
            #define GET_K() CUT(pb); bsync<B_H3, 256>(); LD_X(k, 4096); CUT(pb); PROF(3)
            LD_K(GET_K());
            AGAIN(1, if (late(badk, 0, ~0u)) { RETRY(0, 1); refetch_kv(c, s, l16 | (opq(n_) >> 24)); LD_K(;); } LD_Q(); LD_X(k, 4096); sts32(SUM + 268, s + 1),
                  late(lop3<0xA8>(stale<4, 2>(q, tau), stale<4, 2>(q + 8, tau), mT), badk, ~0u))
            #pragma unroll
            for (int i = 0; i < 4; i++) {
                A[4 * i] = hadd2(q[4 * i], q[4 * i + 2]); A[4 * i + 2] = hadd2(q[4 * i + 1], q[4 * i + 3]);
                if (i < 2) { sc[i][0] = sc[i][1] = sc[i][2] = sc[i][3] = sc[2 + i][0] = sc[2 + i][1] = sc[2 + i][2] = sc[2 + i][3] = 0.f; }
                mmaq(sc[i & 1], A + 4 * i, kf[2 * i], kf[2 * i + 1]); mmaq(sc[2 + (i & 1)], A + 4 * i, kf[8 + 2 * i], kf[9 + 2 * i]);
            }
            sts128f(SC + t16, sc[0][0] + sc[1][0], sc[0][1] + sc[1][1], sc[2][0] + sc[3][0], sc[2][1] + sc[3][1]);
            barrive<B_S1, 256>();
            sts128f(SC + 3072 + t16, sc[0][2] + sc[1][2], sc[0][3] + sc[1][3], sc[2][2] + sc[3][2], sc[2][3] + sc[3][3]);
            load_frag<0, WB1>(WO + t16, F);
            const uint32_t sa = opq(l16 + u_sa);
            CUT(pb);
            PROF(4);
            float d[16];
            #pragma unroll 1
            for (int n_ = 0;; n_++) {
                #pragma unroll
                for (int i = 0; i < 4; i++) { d[4 * i] = d[4 * i + 1] = d[4 * i + 2] = d[4 * i + 3] = 0.f; mmaq(d + 4 * i, A + 4 * (i >> 1), k[2 * i], k[2 * i + 1]); }
                if (__builtin_expect(!late(stale<2, 2>(k, tau), stale<2, 2>(k + 4, tau), mT), 1) || n_ >= SPIN_LIMIT) break;
                RETRY(2, 1);
                LD_X(k, 4096);
            }
            sts64f(SC + 2048 + sa, (d[0] + d[4]) + (d[8] + d[12]), (d[1] + d[5]) + (d[9] + d[13]));
            barrive<B_SC, 256>();
            CUT(pb);
            sts64f(SC + 5120 + sa, (d[2] + d[6]) + (d[10] + d[14]), (d[3] + d[7]) + (d[11] + d[15]));
            PROF(5);
            if (w8 == 0) {
                float x[10];
                bsync<B_S0, 128>();
                tok_scores(x, SC + 3072 + l16); mem_scores(x, SC + 3072 + l16);
                __syncwarp();
                load_frag<WB1, WB2>(WO + t16, F);
                const int g = l16 >> 6, lim = 8 * (g >> 1) + 2 * (c & 3) + (g & 1) - ((l16 >> 1) & 0x18);
                #pragma unroll
                for (int i = 0; i < 8; i++) if (i > lim) x[i] = -INFINITY;
                const float ms = opqf(-SCL * max4lanes(fmaxf(max8(x), fmaxf(x[8], x[9]))));
                CUT(pb);
                #pragma unroll
                for (int i = 0; i < 10; i++) x[i] = ex2(fmaf(x[i], SCL, ms));
                load_frag<WB2, WB3>(WO + t16, F);
                sts128(PT + l16, make_uint4(pack2(x[0], x[1]), pack2(x[2], x[3]), pack2(x[4], x[5]), pack2(x[6], x[7])));
                sts32(PT + 512 + (l16 >> 2), pack2(x[8], x[9]));
                if (!ONE) barrive<B_PT, 160>();
            } else {
                if (ANN == 2) { bsync<B_S0, 128>(); const uint32_t f = lds32(SUM + 268 + opq(t16 >> 16)); REPORT(3, f == s + 1 ? P(2) : 0); } else barrive<B_S0, 128>();
                if (w8 == 1) { if (seg < NSEG) mbar_wait(MB_X, seg & 1); }
                else if (w8 == 2) {
                    bulk_expect(MB_KV, 36864);
                    bulk_copy(TK, kv_src(c, s + 1), 16384, MB_KV); bulk_copy(TQ, kv_src(c, s + 1) + (32768 + (c & 3) * 4096), 4096, MB_KV);
                    bulk_expect(MB_B, 8192); bulk_expect(MB_R, 4096);
                    __syncwarp();
                }
                bsync<B_SC2, 224>();
                load_frag<WB1, WB3>(WO + t16, F);
                __syncwarp();
                CUT(pb);
            }
            bsync<B_O2, 256>();
            PROF(6);
            float i0, i1;
            WO_MMA(WB3, 0, , );
        } else {
            float a[4][4], v[4][4] = {};
            uint32_t b[16][4];
            CUT(pa);
            bsync<B_H0, 256>();
            #pragma unroll
            for (int n = 0; n < PRE1; n++) { LDB(n); __syncwarp(); }
            PROF(0);
            #pragma unroll
            for (int i = 0; i < 16; i++) {
                if (!(i & 1)) {
                    CUT(pa);
                    if (PRE1 < 8 && i + PRE1 < 16) { LDB(i + PRE1); __syncwarp(); LDB(i + PRE1 + 1); __syncwarp(); }
                    if (PRE1 == 8 && i >= 2 && i < 10) { LDB(i + 6); __syncwarp(); LDB(i + 7); __syncwarp(); }
                    if (i == H2) { barrive<B_H2, 256>(); CUT(pa); }
                }
                if (i < 2) { a[2 * i][0] = a[2 * i][1] = a[2 * i][2] = a[2 * i][3] = a[2 * i + 1][0] = a[2 * i + 1][1] = a[2 * i + 1][2] = a[2 * i + 1][3] = 0.f; }
                mmaq(a[2 * (i & 1)], &W[8 * i], b[i][0], b[i][1]); mmaq(a[2 * (i & 1) + 1], &W[8 * i + 4], b[i][2], b[i][3]);
            }
            if (H3 == 0) { barrive<B_H3, 256>(); CUT(pb); }
            const uint32_t mG = (l16 & 0x1C0) ? 0 : 0x10001u, mT = (l16 & 0x30) ? 0 : 1;
            ST_X();
            if (H3 == 1) barrive<B_H3, 256>();
            CUT(pa);
            PROF(1);
            #pragma unroll
            for (int i = 7; i >= 0; i--) { V_MMA(i, 8); if (H3 == 9 - i) { CUT(pb); barrive<B_H3, 256>(); CUT(pb); } }
            ST_V();
            CUT(pb);
            if (H3 == 10) { DELAY(KD); if (HS) bsync<B_H3, 256>(); else barrive<B_H3, 256>(); CUT(pb); DELAY(6); }
            PROF(2);
            uint32_t vf[16], vm[16];
            const uint32_t va = opq(pa), vb = opq(va ^ 0x20);
            #define LD_V() do { _Pragma("unroll") for (int i = 0; i < 4; i++) { const uint32_t a_ = TK + 16384 + ((i & 1) ? vb : va) + (i >> 1) * 4096; \
                ldsm4(vf[4 * i], vf[4 * i + 1], vf[4 * i + 2], vf[4 * i + 3], a_); ldsm4(vm[4 * i], vm[4 * i + 1], vm[4 * i + 2], vm[4 * i + 3], a_ + 8192); } } while (0)
            LD_V();
            __syncwarp();
            load_frag<0, WA0>(WO + t16, F);
            AGAIN(0, refetch_kv(c, s, l16 | (opq(n_) >> 24)); LD_V(), late(stale<4, 4>(vf, tau2) | stale<4, 4>(vf + 1, tau2), stale<4, 4>(vm, tau2) | stale<4, 4>(vm + 1, tau2), mT))
            #pragma unroll
            for (int i = 0; i < 16; i++) vf[i] = opq(hadd2(vf[i], vm[i]));
            const char* const xa = at(u_x + (t16 >> 1), rbhi) + (8192 - 1024);
            DELAY(VD);
            LD_X(vm, 0); LD_X(vm + 8, 4096);
            __syncwarp();
            load_frag<WA0, WA1>(WO + t16, F);
            CUT(pb);
            float x[10];
            bsync<B_S1, 256>();
            const uint32_t qlate = lds32(SUM + 268 + opq(t16 >> 16));
            tok_scores(x, SC + l16);
            const float mt = opqf(max8(x));
            if (ANN == 3) REPORT(7, 0);
            CUT(pb);
            if (__builtin_expect(!late(qlate ^ (s + 1), 0, ~0u), 0)) {
                const char* const xa = at(u_x + (opq(t16) >> 1), rbhi) + (8192 - 1024);
                AGAIN(3, LD_X(vm, 0); LD_X(vm + 8, 4096), late(stale<4, 2>(vm, tau), stale<4, 2>(vm + 8, tau), mT))
            }
            PROF(3);
            bsync<B_SC, 256>();
            mem_scores(x, SC + l16);
            const float m1 = fmaxf(mt, fmaxf(x[8], x[9]));
            const float m2 = __shfl_xor_sync(~0u, m1, 1), m3 = __shfl_xor_sync(~0u, m1, 2), m4 = __shfl_xor_sync(~0u, m1, 3);
            CUT(pb);
            load_frag<WA1, WA2>(WO + t16, F);
            barrive<B_SC2, 224>();
            uint32_t p[5], vs[4];
            #define SUM_V() do { _Pragma("unroll") for (int i = 0; i < 4; i++) { const int e = (i >> 1) * 4 + (i & 1); vs[i] = hadd2(hadd2(vm[e], vm[e + 8]), hadd2(vm[e + 2], vm[e + 10])); } } while (0)
            CUT(pb);
            const float ms = -SCL * fmaxf(fmaxf(m1, m2), fmaxf(m3, m4));
            PROF(5);
            #pragma unroll
            for (int i = 0; i < 10; i++) x[i] = fmaf(x[i], SCL, ms);
            x[8] = opqf(ex2(x[8])); x[9] = opqf(ex2(x[9]));
            CUT(pb);
            uint32_t badv = late(stale<4, 2>(vm, tau), stale<4, 2>(vm + 8, tau), mT);
            SUM_V();
            #pragma unroll
            for (int i = 0; i < 4; i++) { x[i] = opqf(ex2(x[i])); vs[i] = opq(vs[i]); }
            const uint32_t z0 = t16 >> 16;
            uint32_t one[4] = {opq(ONES | z0), opq(ONES ^ z0), opq(ONES + z0), opq(ONES - z0)};
            CUT(pb);
            #pragma unroll
            for (int i = 4; i < 8; i++) x[i] = ex2(x[i]);
            #pragma unroll
            for (int i = 0; i < 5; i++) p[i] = pack2(x[2 * i], x[2 * i + 1]);
            float sm[4] = {};
            #define PV(also) do { float o[8] = {}; \
                mma8(o, vs[0], vs[1], p[4]); mma8(o + 4, vs[2], vs[3], p[4]); if (also) mma8(sm, one[0], one[1], p[4]); \
                mmaq(o, vf, p[0], p[1]); mmaq(o + 4, vf + 8, p[0], p[1]); if (also) mmaq(sm, one, p[0], p[1]); \
                mmaq(o, vf + 4, p[2], p[3]); mmaq(o + 4, vf + 12, p[2], p[3]); if (also) mmaq(sm, one, p[2], p[3]); \
                stsm4(OB - 2048 + opq(t16), pack2(o[0], o[1]), pack2(o[2], o[3]), pack2(o[4], o[5]), pack2(o[6], o[7])); } while (0)
            PV(true);
            if (w8 == 4) sts64f(SUM + (l16 >> 1), sm[0], sm[1]);
            if (__builtin_expect(badv, 0)) {
                int n_ = 0;
                uint32_t vm[16];
                const char* const xa = at(u_x + (8192 - 1024) + (opq(t16) >> 1), rbhi);
                do { RETRY(3, 1); LD_X(vm, 0); LD_X(vm + 8, 4096); } while (late(stale<4, 2>(vm, tau), stale<4, 2>(vm + 8, tau), mT) && ++n_ < SPIN_LIMIT);
                SUM_V();
                PV(false);
            }
            if (ONE) bsync<B_O2, 256>(); else { barrive<B_O2, 256>(); bsync<B_O, 128>(); }
            PROF(6);
            float i0 = sm[0], i1 = sm[1];
            #define GET_P() if (!ONE) bsync<B_PT, 160>(); lds128u(p, PT + l16); p[4] = lds32(PT + 512 + (l16 >> 2))
            #define TOK_PV() { const uint32_t z = t16 >> 17; one[0] = ONES | z; one[1] = ONES ^ z; one[2] = ONES + z; one[3] = ONES - z; } \
                _Pragma("unroll") for (int i = 0; i < 12; i++) ot[i >> 2][0][i & 3] = ot[i >> 2][1][i & 3] = 0.f; \
                mma8(ot[0][0], vs[0], vs[1], p[4]); mma8(ot[1][0], vs[2], vs[3], p[4]); mma8(ot[2][0], one[0], one[1], p[4]); \
                mmaq(ot[0][1], vf + 4, p[2], p[3]); mmaq(ot[1][1], vf + 12, p[2], p[3]); mmaq(ot[2][1], one, p[2], p[3]); CUT(pa)
            WO_MMA(WA2, WA3, GET_P(), TOK_PV());
            CUT(pa);
            mmaq(ot[0][0], vf, p[0], p[1]); mmaq(ot[1][0], vf + 8, p[0], p[1]); mmaq(ot[2][0], one, p[0], p[1]);
            CUT(pb);
            barrive<B_GO, 256>();
        }
        CUT(pb);
        PROF(7);
        #define PK_O() const float j0 = rcpf(ot[2][0][0] + ot[2][1][0]), j1 = rcpf(ot[2][0][1] + ot[2][1][1]); uint32_t ow[4]; \
            _Pragma("unroll") for (int i = 0; i < 4; i++) \
                ow[i] = opq(pack2((ot[i >> 1][0][2 * (i & 1)] + ot[i >> 1][1][2 * (i & 1)]) * j0, (ot[i >> 1][0][2 * (i & 1) + 1] + ot[i >> 1][1][2 * (i & 1) + 1]) * j1))
        #define ST_O() do { uint32_t* og = (uint32_t*)((char*)g_O + (u_og + (l16 >> 2))); \
            _Pragma("unroll") for (int i = 0; i < 4; i++) og[(i >> 1) * 256 + (i & 1) * 32] = ow[i]; } while (0)
        #define BSO() ((u_bs) ^ ((l16 & 0x10) + ((l16 >> 3) & 0xC) + (l16 & 0x80) * 0x20 + (l16 & 0x100) * 0x80))
        const uint32_t taus = phase(seg);
        const uint64_t* const dq = c_xd + (s & 1) * 32; const uint64_t* const dv = dq + (wg * 16 | (prm.zero & s));
        float acc[16], acv[16];
        uint32_t u[8];
        if constexpr (wg == 0) {
            if (s == NSEG - 1) { bsync<B_GO, 256>(); st_g32(at(BSO(), rbhi), 0); mbar_wait(MB_KV, 0); break; }
            load_frag<16 - EV, 16, 2048>(VEB + t16, T);
            bsync<B_GO, 256>();
            PROF(8);
            wg_run<0, 16 - EV>(acv, T, dv);
            wg_run<16 - EV, 16>(acv, T, dv);
            wg_run<0, 5>(acc, W, dq); wg_wait<1>();
            qk_pack(acv, u);
            #pragma unroll
            for (int i = 0; i < 8; i++) u[i] = opq(u[i]);
            CUT(pa);
            wg_run<5, 8>(acc, W, dq);
            __syncwarp();
            sts128(SC + opq(t16), make_uint4(u[0], u[1], u[2], u[3])); sts128(SC + 2048 + opq(t16), make_uint4(u[4], u[5], u[6], u[7]));
            barrive<B_VX, 256>();
            __syncwarp();
            PROF(9);
            wg_run<8, 12>(acc, W, dq);
            CUT(pa);
            char* const bs = at(opq(BSO()), opq(rbhi));
            CUT(pa);
            wg_run<12, 15>(acc, W, dq);
            CUT(pa);
            const uint32_t ro = opq(l16 * 8 + ((l16 & 0x70) ^ ((w8 & 3) << 5))), ro2 = opq(ro ^ 0x10);
            const uint32_t mG = opq((l16 & 0x1C0) ? 0 : 0x10001u), mB = opq((((l16 >> 2) & 4) + ((l16 >> 5) & 3)) == ((u_bs >> 7) & 7) ? 1 : 0), zz = t16 >> 18;
            CUT(pa);
            wg_run<15, 18>(acc, W, dq);
            CUT(pa);
            const uint32_t one[4] = {opq(ONES | zz), opq(ONES ^ zz), opq(ONES + zz), opq(ONES - zz)};
            const uint32_t par = s & 1, tt = tau * 0x10001u;
            CUT(pa);
            wg_run<18, RP>(acc, W, dq);
            CUT(pa);
            PROF(10);
            mbar_wait(MB_R, par);
            PROF(14);
            uint32_t x[8], bad;
            float d[4][4];
            #define SUM_R() do { ldsm4t(x[0], x[1], x[2], x[3], RS + ro); ldsm4t(x[4], x[5], x[6], x[7], RS + ro2); \
                _Pragma("unroll") for (int i = 0; i < 4; i++) { d[i][0] = d[i][1] = d[i][2] = d[i][3] = 0.f; mmaq(d[i], one, x[2 * i], x[2 * i + 1]); } } while (0)
            #define PUT_B() do { bad = late(stale<2, 1>(x, tt), stale<2, 1>(x + 2, tt), mG); \
                const uint32_t w0 = pack2(d[0][0] + d[1][0], d[0][1] + d[1][1]), w1 = pack2(d[2][0] + d[3][0], d[2][1] + d[3][1]); \
                asm volatile("{ .reg .pred p; setp.eq.b32 p, %2, 0; @p st.relaxed.gpu.global.u32 [%0], %1; }" :: "l"(bs), "r"(tagm((l16 & 0x40) ? w1 : w0, mB, tt)), "r"(bad) : "memory"); } while (0)
            SUM_R();
            CUT(pa);
            wg_run<RP, (RP + RQ < 32 ? RP + RQ : 32)>(acc, W, dq);
            if (RP + RQ >= RL) barrive<B_BT, 256>();
            CUT(pa);
            PUT_B();
            const uint32_t tb = lds32(SUM + 272 + 28 + zz);
            CUT(pa);
            PROF(11);
            if (RP + RQ < RL) { wg_run<RP + RQ, RL>(acc, W, dq); __syncwarp(); barrive<B_BT, 256>(); __syncwarp(); }
            wg_run<(RP + RQ < RL ? RL : RP + RQ), 32>(acc, W, dq);
            CUT(pa);
            AGAIN(5, ld_g128(x, at(u_rl + opq(ro), rbhi)); ld_g128(x + 4, at(u_rl + opq(ro2), rbhi)); sts128(RS + ro, make_uint4(x[0], x[1], x[2], x[3])); sts128(RS + ro2, make_uint4(x[4], x[5], x[6], x[7]));
                     CUT(pa); __syncwarp(); SUM_R(); PUT_B(), bad)
            if (w8 == 3) {
                TRC(13, gtime() - tb);
                wait_g(tb, t16);
                GET_B(0);
                PROFW(13, 3);
            } else mbar_wait(MB_KV, ~s & 1);
            const uint32_t ps = opq(pb & 0xFFFF), ps2 = opq(ps ^ HI8);
            char* const qd0 = TOK_DST() + ps; char* const qd1 = TOK_DST() + ps2;
            wg_wait<0>();
            pack_tag(acc, u, taus);
            #pragma unroll
            for (int i = 0; i < 8; i++) u[i] = opq(u[i]);
            CUT(pa);
            bsync<B_S0, 128>();
            st_if(seg < NSEG, qd0, u); st_if(seg < NSEG, qd1, u + 4);
            if (XP == 1) load_x(tmX, c, seg + 1, (s & 1) ? XT : XT2, w8 == 1 && seg + 1 < NSEG);
            PROF(12);
        } else {
            #define LAST() __reduce_max_sync(~0u, max(max(an[0], an[1]), max(an[2], an[3])))
            PK_O();
            CUT(pa);
            if (s == NSEG - 1) { ST_O(); break; }
            PROF(8);
            if (w8 != 7) load_frag<16 - EV, 16 - EV + TA0, 2048>(VEB + t16, T);
            else {
                uint32_t tr = LAST();
                AGAIN(8, ld_g128(an, at(u_ta + l16, rbhi)); tr = LAST(), late(stale<2, 1>(an, s), stale<2, 1>(an + 2, s), 31))
                tr = (tr & ~31u) + P(0);
                TRC(14, gtime() - tr);
                wait_g(tr, t16);
                if (R4) { for (int i = 0; i < 4; i++) bulk_copy(RS + i * 1024, at(u_rl + i * 1024, rbhi), 1024, MB_R); }
                else bulk_copy(RS, at(u_rl, rbhi), 4096, MB_R);
                PROFW(14, 3);
                if (XP == 3) load_x(tmX, c, seg + 1, (s & 1) ? XT : XT2, seg + 1 < NSEG);
                sts32(SUM + 272 + 28, tr + P(1));
                load_frag<16 - EV, 16 - EV + TA0, 2048>(VEB + t16, T);
            }
            CUT(pa);
            bsync<B_VX, 256>();
            lds128u(u, SC - 2048 + opq(t16)); lds128u(u + 4, SC + opq(t16));
            CUT(pa);
            ST_O();
            CUT(pa);
            load_frag<16 - EV + TA0, 16 - EV + TA, 2048>(VEB + t16, T);
            acc_init(acv, u);
            #pragma unroll
            for (int i = 0; i < 16; i++) acv[i] = opqf(acv[i]);
            const uint32_t ps = opq(pb & 0xFFFF), ps2 = opq(ps ^ HI8);
            CUT(pa);
            PROF(9);
            bsync<B_BT, 256>();
            CUT(pa);
            wg_run<0, 3>(acc, W, dq);
            PROF(11);
            wg_run<3, NT, true>(acc, W, dq);
            __syncwarp();
            load_frag<16 - EV + TA, 16, 2048>(VEB + t16, T);
            __syncwarp();
            wg_run<NT, NB>(acc, W, dq);
            char* const qd0 = TOK_DST() + ps; char* const qd1 = TOK_DST() + ps2;
            wg_run<NB, 32>(acc, W, dq);
            wg_run<0, 5, true>(acv, T, dv);
            wg_wait<1>();
            PROF(12);
            pack_tag(acc, u, taus);
            #pragma unroll
            for (int i = 0; i < 8; i++) u[i] = opq(u[i]);
            CUT(pa);
            wg_run<5, 16 - EV>(acv, T, dv);
            __syncwarp();
            st_if(seg < NSEG, qd0, u); st_if(seg < NSEG, qd1, u + 4);
            __syncwarp();
            wg_run<16 - EV, 16>(acv, T, dv);
            CUT(pa);
            PROF(10);
            wg_wait<0>();
            PROF(13);
            pack_tag(acv, u, taus);
            if (XP == 2) load_x(tmX, c, seg + 1, (s & 1) ? XT : XT2, w8 == 5 && seg + 1 < NSEG);
            st_if(seg < NSEG, qd0 + 16384, u); st_if(seg < NSEG, qd1 + 16384, u + 4);
        }
        s++;
        u_rs ^= 1 << 20; u_rl ^= 1 << 20; u_bs ^= 1 << 20; u_bl ^= 1 << 20; u_x ^= 1 << 20; u_xs ^= 1 << 20; u_ta ^= 1 << 20; u_rp ^= 1 << 20; u_og += 262144;
    }
}

__device__ __forceinline__ uint32_t round_trips(char* line, int n) {
    uint32_t best[2] = {0xFFFFu, 0xFFFFu};
    #pragma unroll 1
    for (int i = 0; i < n; i++) {
        uint32_t v; const uint32_t t0 = clk();
        asm volatile("atom.relaxed.gpu.global.exch.b32 %0, [%1], %2;" : "=r"(v) : "l"(line + (i & 1) * 4096), "r"(i) : "memory");
        if (v == 0x7FC1A5A5u) g_err = 2;
        const uint32_t dt = clk() - t0;
        if (i & 1) best[1] = min(best[1], dt); else best[0] = min(best[0], dt);
    }
    return (__popc((uint32_t)(uintptr_t)line & HOME_BITS) & 1) ? best[1] | best[0] << 16 : best[0] | best[1] << 16;
}
__device__ __forceinline__ int role(char* rb) {
    const int b = blockIdx.x, t = threadIdx.x;
    if (!(t & 31)) { const int i = b * 8 + (t >> 5); sts32(mk::SUM + (t >> 3), round_trips(rb + RB_P + (i & 31) * 128 + (i >> 5) * 8192, NPR)); }
    __syncthreads();
    if (t == 0) {
        const uint4 x = lds128(mk::SUM), y = lds128(mk::SUM + 16);
        const uint32_t m = __vminu2(__vminu2(__vminu2(x.x, x.y), __vminu2(x.z, x.w)), __vminu2(__vminu2(y.x, y.y), __vminu2(y.z, y.w)));
        uint32_t sm; asm volatile("mov.u32 %0, %%smid;" : "=r"(sm));
        const uint32_t g = sm < 64 ? (sm & 15) >> 1 : 1 + (sm - 64) % 14 / 2, i = sm < 64 ? sm >> 4 : 4 + (sm - 64) / 14;
        const uint32_t pos = sm < 120 ? g * 16 + i * 2 + (sm & 1) : sm + 8;
        st_g32(g_cls + b, 0x80000000u | (m >> 16 < (m & 0xFFFF)) << 24 | pos << 8 | b);
    }
    uint32_t e = ~0u, own;
    int n = 0;
    do { own = ld_g32(g_cls + b); if (t < NCTA) e = ld_g32(g_cls + t); } while (!((e & own) >> 31) && ++n < SPIN_LIMIT);
    const int below = __syncthreads_count(e < own), n0 = __syncthreads_count(!(e >> 24 & 1));
    const int c0 = 4 * min(max(16, 32 - (NCTA - n0) / 4), n0 / 4);
    return below < c0 ? below : below < n0 ? 128 + below - c0 : below - n0 + c0 < 128 ? below - n0 + c0 : below;
}

__global__ void __launch_bounds__(256, 1)
main_kernel(const __grid_constant__ CUtensorMap tmWq, const __grid_constant__ CUtensorMap tmWk, const __grid_constant__ CUtensorMap tmWv,
            const __grid_constant__ CUtensorMap tmWo, const __grid_constant__ CUtensorMap tmX, const bf16* __restrict__ mem0,
            const bf16* Wo, const __grid_constant__ MainParams prm) {
    using namespace mk;
    extern __shared__ __align__(1024) uint8_t smem_raw[];
    if (smem_u32(smem_raw) != SB) __trap();
    TL(2);
    const int tid0 = threadIdx.x, w8 = __shfl_sync(~0u, tid0 >> 5, 0), wg = w8 >> 2;
    asm volatile("griddepcontrol.wait;" ::: "memory");
    const int c = __shfl_sync(~0u, role(prm.rb), 0), kap = c & 1;
    if (c >= 128) return;
    if (tid0 == 0) {
        for (int i = 0; i < 8; i++) mbar_init(BAR + i * 8, 1);
        sts32(SUM + 268, 0); mbar_arrive(MB_B);
        asm volatile("fence.mbarrier_init.release.cluster;" ::: "memory");
        asm volatile("fence.proxy.async.shared::cta;" ::: "memory");
        const int col = (c >> 1) * 64, k0 = kap * 512;
        mbar_expect(MB_WQ, 65536); tma2d(WO, &tmWq, col, k0, MB_WQ); tma2d(WO + 32768, &tmWq, col, k0 + 256, MB_WQ);
        mbar_expect(MB_WK, 65536); tma2d(WV, &tmWk, col, k0, MB_WK); tma2d(WV + 32768, &tmWk, col, k0 + 256, MB_WK);
    }
    __syncwarp();
    load_x(&tmX, c, 0, XT, w8 == 0);
    for (int i = tid0; i < 4096; i += 256) {
        const int row = i >> 9, col = i & 511;
        const unsigned short v = __bfloat16_as_ushort(mem0[row * DM + kap * 512 + col]);
        asm volatile("st.shared.u16 [%0], %1;" :: "r"(MEM + col * 16 + row * 2), "h"(v) : "memory");
    }
    asm volatile("fence.proxy.async.shared::cta;" ::: "memory");
    __syncthreads();
    uint32_t W[128], T[64];
    mbar_wait(wg ? MB_WK : MB_WQ, 0);
    load_tile<0, 32>(tile_off(tid0 & 31, 2 * (w8 & 3)) + (wg ? WV : WO), W);
    __syncthreads();
    if (tid0 == 0) {
        mbar_expect(MB_WV, 65536); tma2d(WV, &tmWv, (c >> 1) * 64, kap * 512, MB_WV); tma2d(WV + 32768, &tmWv, (c >> 1) * 64, kap * 512 + 256, MB_WV);
        mbar_expect(MB_WO, 65536);
        for (int i = 0; i < 4; i++) tma2d(WO + i * 16384, &tmWo, (c & 3) * 256 + i * 64, (c >> 2) * DH, MB_WO);
    }
    asm volatile("griddepcontrol.launch_dependents;" ::: "memory");
    uint32_t t16 = tid0 * 16, pa, pb;
    {
        const int lane = tid0 & 31, w = w8 & 3, g = lane >> 2, t = lane & 3;
        auto vec = [](int hf, int gg, int ch) { return hf * 512 + (gg >> 1) * 128 + (gg & 1) * 64 + ((ch ^ (gg >> 1) ^ (hf << 1)) << 4); };
        const int kg = ((lane >> 3) & 1) * 4 + ((lane & 7) >> 1);
        pa = wg ? w * 1024 + vec((lane >> 3) & 1, lane & 7, lane >> 4)
                : ((lane >> 4) * 4096 + w * 1024 + vec(lane & 1, kg, 2 * (w & 1))) | ((lane & 8) * 256 + w * 256 + (lane & 1) * 128 + ((((lane >> 4) ^ (lane & 1)) * 4 + ((lane & 7) >> 1)) << 4)) << 16;
        pb = (wg ? w * 1024 + vec(0, g, t) : t * 4096 + w * 256 + g * 16) | (w * 256 + t * 64 + (g & 3) * 8 + (g >> 2) * 4) << 16;
    }
    mbar_wait(MB_WV, 0);
    load_tile<0, 16>(tile_off(tid0 & 31, 2 * (w8 & 3)) + wg * 32768 + WV, T);
    __syncthreads();
    #pragma unroll
    for (int i = 0; i < 16; i++) sts128(WV + i * 4096 + t16, make_uint4(T[4 * i], T[4 * i + 1], T[4 * i + 2], T[4 * i + 3]));
    int budget = SPIN_LIMIT;
    #pragma unroll 1
    for (int seg = 0; seg < 2; seg++) {
        const uint32_t tau = phase(seg), ps = pb & 0xFFFF;
        float acc[16], acv[16];
        uint32_t u[8];
        mbar_wait(MB_X, seg & 1);
        wg_run<0, 32>(acc, W, c_xd + (prm.zero & seg));
        wg_run<0, 16>(acv, T, c_xd + (wg * 16 | (prm.zero & (seg + 1))));
        wg_wait<0>();
        if (!wg) { qk_pack(acv, u); sts128(SC + t16, make_uint4(u[0], u[1], u[2], u[3])); sts128(SC + 2048 + t16, make_uint4(u[4], u[5], u[6], u[7])); }
        __syncthreads();
        load_x(&tmX, c, seg + 1, XT, w8 == 0);
        if (wg) { lds128u(u, SC - 2048 + t16); lds128u(u + 4, SC + t16); acc_add(acv, u); }
        #pragma unroll 1
        for (int m = 0; m <= wg; m++) {
            pack_tag(acc, u, tau);
            st_if(true, tok_dst(c, seg, wg) + (m * 16384 + ps), u); st_if(true, tok_dst(c, seg, wg) + (m * 16384 + (ps ^ HI8)), u + 4);
            #pragma unroll
            for (int i = 0; i < 16; i++) acc[i] = acv[i];
        }
        __syncthreads();
    }
    {
        mbar_wait(MB_WO, 0);
        const int lane = tid0 & 31;
        const uint32_t a = (tid0 >> 6) * 16384 + tile_off(lane, (w8 & 1) * 4) + WO;
        #pragma unroll
        for (int i = 0; i < 16; i++) ldsm4t(T[4 * i], T[4 * i + 1], T[4 * i + 2], T[4 * i + 3], ((i & 2) ? a ^ 32 : a) + ((i >> 2) + 4 * (i & 1)) * 2048);
        __syncthreads();
        const uint32_t d = WO + w8 * 512 + ((lane >> 3) * 4 + (lane & 3)) * 16 + ((lane >> 2) & 1) * 4;
        #pragma unroll
        for (int i = 0; i < 64; i++) sts32(d + (i >> 2) * 4096 + (i & 1) * 256 + (i & 2) * 4, T[i]);
        load_frag<0, 16>(WV + t16, T);
    }
    uint32_t u_rs, u_rl, u_bs, u_bl;
    const uint32_t rbhi = (uint32_t)((uintptr_t)prm.rb >> 32);
    {
        const int lane = tid0 & 31, h = c >> 2, j = c & 3;
        uint32_t cl;
        const int G = h >> 4, rk = h & 15;
        auto half = [&](uint32_t off) { return (uint32_t)(uintptr_t)prm.rb + off + ((__popc(off & HOME_BITS) ^ G) & 1) * 4096; };
        auto rpair = [&](int m) { return RB_R + (j << 16) + ((m & 1) << 13) + (((m >> 1) & 3) << 14) + ((m >> 3) << 18); };
        u_rs = (half(rpair(2 * w8)) ^ (G << 12)) + h * 128 + (h & 7) * 16;
        u_rl = half(rpair(rk));
        u_bs = (uint32_t)(uintptr_t)prm.rb + RB_B + ((j & 1) << 13) + ((j >> 1) << 16) + rk * 256 + G * 128 + (w8 & 3) * 32;
        u_bl = half(RB_B + (kap << 16));
        if (w8 == 0) {
            const char* v0 = kv_src(c, 0) + 16384 + lane * 128;
            do cl = ld_g32(v0) & ld_g32(v0 + 4096) & ld_g32(v0 + 8192) & ld_g32(v0 + 12288); while (__any_sync(~0u, !(cl & 1)) && --budget > 0);
            kv_expect(36864); kv_copy(TK, kv_src(c, 0), 32768); kv_copy(TQ, kv_src(c, 0) + 32768 + j * 4096, 4096);
        }
    }
    mbar_wait(MB_KV, 0);
    asm volatile("fence.proxy.async.shared::cta;" ::: "memory");
    TLX(7);
    __syncwarp();
    const Ctx cx = {u_rs, u_rl, u_bs, u_bl, (uint32_t)(uintptr_t)prm.rb, rbhi, w8, c};
    if (wg) steps<1>(W, T, t16, pa, pb, cx, &tmX, prm); else steps<0>(W, T, t16, pa, pb, cx, &tmX, prm);
    TLX(3);
}

namespace ck {
constexpr uint32_t U = 0;
constexpr uint32_t UPL = 136 * 16 + 64;
constexpr uint32_t UCH = 2 * UPL;
constexpr uint32_t F = 8 * UCH;
constexpr uint32_t FCP = 4160;
constexpr uint32_t FCH = 2 * FCP;
constexpr uint32_t SK = F + 8 * FCH;
constexpr uint32_t SKP = 257 * 16;
constexpr uint32_t SV = SK + 8 * SKP;
constexpr uint32_t SQ = SV + 32768;
constexpr uint32_t TOTAL = SQ + 32768;
}
__global__ void __launch_bounds__(288, 1)
conv_kernel(const bf16* __restrict__ q, const bf16* __restrict__ k, const bf16* __restrict__ v, const bf16* __restrict__ shift_k,
            const bf16* __restrict__ ssm_k, const bf16* __restrict__ ssm_D, const bf16* __restrict__ gate_w,
            const bf16* Wq, const bf16* Wk, const bf16* Wv, const bf16* Wo,
            const __grid_constant__ CUtensorMap tmWq, const __grid_constant__ CUtensorMap tmWk, const __grid_constant__ CUtensorMap tmWv,
            const __grid_constant__ CUtensorMap tmWo, char* rb) {
    using namespace ck;
    extern __shared__ uint8_t smem_raw[];
    const uint32_t sb = smem_u32(smem_raw);
    const int tid = threadIdx.x, w = tid >> 5, lane = tid & 31, c = blockIdx.x;
    TL(0);
    const int d0 = c * 8, t0 = tid * 8;
    if (w == 8) {
        bsync<1, 288>();
        if (lane < 10) {
            const CUtensorMap* m = lane < 2 ? &tmWq : lane < 4 ? &tmWk : lane < 6 ? &tmWv : &tmWo;
            const int c0 = lane < 6 ? (c >> 1) * 64 : (c & 3) * 256 + (lane - 6) * 64, c1 = lane < 6 ? (c & 1) * 512 + (lane & 1) * 256 : (c >> 2) * DH;
            asm volatile("cp.async.bulk.prefetch.tensor.2d.L2.global [%0, {%1, %2}];" :: "l"(m), "r"(c0), "r"(c1) : "memory");
        }
        return;
    }
    #pragma unroll
    for (int i = 0; i < 8; i++) {
        cpa16(sb + SK + i * SKP + (tid + 1) * 16, k + (size_t)(t0 + i) * DM + d0);
        cpa16(sb + SV + i * 4096 + tid * 16, v + (size_t)(t0 + i) * DM + d0);
    }
    cpa_commit();
    #pragma unroll
    for (int i = 0; i < 8; i++) cpa16(sb + SQ + i * 4096 + tid * 16, q + (size_t)(t0 + i) * DM + d0);
    cpa_commit();
    uint4 fx[8], gw[4], x0[4], x1[4], skr[4];
    const uint4* fp = (const uint4*)(ssm_k + (size_t)(d0 + w) * SEQ);
    #pragma unroll
    for (int i = 0; i < 8; i++) fx[i] = fp[lane + 32 * i];
    const int gr = c * 16 + w * 2;
    #pragma unroll
    for (int i = 0; i < 4; i++) {
        gw[i] = ((const uint4*)gate_w)[lane + 32 * i];
        x0[i] = ((const uint4*)(q + (size_t)gr * DM))[lane + 32 * i];
        x1[i] = ((const uint4*)(q + (size_t)(gr + 1) * DM))[lane + 32 * i];
        skr[i] = ((const uint4*)(shift_k + d0 * 4))[i];
    }
    if (c == 0 && tid < 160) g_cls[tid] = 0;
    if (tid < 128) sts128(sb + U + (tid >> 4) * UCH + ((tid >> 3) & 1) * UPL + (tid & 7) * 16, make_uint4(0, 0, 0, 0));
    else if (tid < 136) sts128(sb + SK + (tid & 7) * SKP, make_uint4(0, 0, 0, 0));
    {
        const uint32_t fb = sb + F + w * FCH;
        if (lane < 8) { sts32(fb + 4128 + lane * 4, 0); if (lane) sts32(fb + FCP + 4128 + lane * 4, 0); }
        #pragma unroll
        for (int i = 0; i < 8; i++) {
            const int vi = lane + 32 * i;
            const uint4 x = fx[i];
            const uint32_t a = __shfl_down_sync(~0u, x.x, 1), b = __shfl_sync(~0u, i < 7 ? fx[i < 7 ? i + 1 : 7].x : 0u, 0);
            const uint32_t nxt = lane == 31 ? b : a;
            const uint32_t ea = fb + (2056 - 8 * vi) * 2;
            sts128(ea, make_uint4(__byte_perm(x.w, 0, 0x1032), __byte_perm(x.z, 0, 0x1032), __byte_perm(x.y, 0, 0x1032), __byte_perm(x.x, 0, 0x1032)));
            sts128(ea + FCP, make_uint4(__byte_perm(nxt, x.w, 0x7610), __byte_perm(x.w, x.z, 0x7610), __byte_perm(x.z, x.y, 0x7610), __byte_perm(x.y, x.x, 0x7610)));
            if (vi == 0) sts32(fb + FCP + 4128, x.x & 0xFFFFu);
        }
    }
    {
        float a0 = 0.f, a1 = 0.f;
        #pragma unroll
        for (int i = 0; i < 16; i++) {
            const uint32_t gg = ((const uint32_t*)gw)[i], u0 = ((const uint32_t*)x0)[i], u1 = ((const uint32_t*)x1)[i];
            a0 = fmaf(bflo(u0), bflo(gg), fmaf(bfhi(u0), bfhi(gg), a0));
            a1 = fmaf(bflo(u1), bflo(gg), fmaf(bfhi(u1), bfhi(gg), a1));
        }
        #pragma unroll
        for (int o = 16; o; o >>= 1) { a0 += __shfl_xor_sync(~0u, a0, o); a1 += __shfl_xor_sync(~0u, a1, o); }
        if (lane < 2) g_gate[gr + lane] = 1.f / (1.f + __expf(lane ? -a1 : -a0));
    }
    cpa_wait();
    bsync<1, 288>();
    TLX(14);
    const uint4 dd = *(const uint4*)(ssm_D + d0);
    {
        uint4 kr[11], vr[8];
        #pragma unroll
        for (int i = 0; i < 11; i++) kr[i] = lds128(sb + SK + ((i + 5) & 7) * SKP + (tid + (i >= 3)) * 16);
        #pragma unroll
        for (int i = 0; i < 8; i++) vr[i] = lds128(sb + SV + i * 4096 + tid * 16);
        #pragma unroll
        for (int ch = 0; ch < 8; ch++) {
            const uint32_t s01 = ((const uint32_t*)skr)[2 * ch], s23 = ((const uint32_t*)skr)[2 * ch + 1];
            const float sk[4] = {bflo(s01), bfhi(s01), bflo(s23), bfhi(s23)};
            float kf[11], kv[8];
            #pragma unroll
            for (int i = 0; i < 11; i++) { const uint32_t wd = ((const uint32_t*)&kr[i])[ch >> 1]; kf[i] = (ch & 1) ? bfhi(wd) : bflo(wd); }
            #pragma unroll
            for (int i = 0; i < 8; i++) {
                const uint32_t wv = ((const uint32_t*)&vr[i])[ch >> 1];
                kv[i] = fmaf(kf[i + 3], sk[0], fmaf(kf[i + 2], sk[1], fmaf(kf[i + 1], sk[2], kf[i] * sk[3]))) * ((ch & 1) ? bfhi(wv) : bflo(wv));
            }
            sts128(sb + U + ch * UCH + (tid & 1) * UPL + (8 + (tid >> 1)) * 16,
                   make_uint4(pack2(kv[0], kv[1]), pack2(kv[2], kv[3]), pack2(kv[4], kv[5]), pack2(kv[6], kv[7])));
        }
    }
    bsync<2, 256>();
    TL(9);
    {
        const int g = lane >> 2, t = lane & 3;
        float acc[16][4];
        #pragma unroll
        for (int i = 0; i < 16; i++) acc[i][0] = acc[i][1] = acc[i][2] = acc[i][3] = 0.f;
        const uint32_t fa = sb + F + w * FCH + ((g & 1) ? (2063 - g + 2 * t) * 2 : FCP + (2064 - g + 2 * t) * 2);
        const uint32_t ua = sb + U + w * UCH + ((lane >> 3) & 1) * UPL + (8 + (lane >> 4) * 8 + (lane & 7)) * 16;
        #pragma unroll 1
        for (int r = 0; r < 8; r++) {
            uint32_t Fr[32];
            #pragma unroll
            for (int m = 0; m < 8; m++) ldsm4(Fr[4 * m], Fr[4 * m + 1], Fr[4 * m + 2], Fr[4 * m + 3], ua - r * 16 + m * 256);
            #pragma unroll
            for (int qq = 0; qq < 16; qq++) {
                const uint32_t o = fa - r * 32 - qq * 256;
                const uint32_t f0 = lds32(o), fp8 = lds32(o - 16), fm8 = lds32(o + 16);
                #pragma unroll
                for (int nt = qq; nt < 16; nt++) mma16(acc[nt], f0, fp8, fm8, f0, Fr[2 * (nt - qq)], Fr[2 * (nt - qq) + 1]);
            }
        }
        __syncwarp();
        const uint32_t ya = sb + F + w * FCH + ((lane >> 3) & 1) * 2048 + ((lane >> 4) * 8 + (lane & 7)) * 16;
        #pragma unroll
        for (int nt = 0; nt < 16; nt += 2)
            stsm4t(ya + nt * 128, pack2(acc[nt][0], acc[nt][1]), pack2(acc[nt][2], acc[nt][3]), pack2(acc[nt + 1][0], acc[nt + 1][1]), pack2(acc[nt + 1][2], acc[nt + 1][3]));
    }
    TL(11);
    bsync<2, 256>();
    {
        uint32_t outw[8][4];
        uint4 qr[8];
        #pragma unroll
        for (int i = 0; i < 8; i++) qr[i] = lds128(sb + SQ + i * 4096 + tid * 16);
        #pragma unroll
        for (int cp = 0; cp < 4; cp++) {
            const uint4 y0 = lds128(sb + F + (2 * cp) * FCH + (tid & 1) * 2048 + (tid >> 1) * 16), y1 = lds128(sb + F + (2 * cp + 1) * FCH + (tid & 1) * 2048 + (tid >> 1) * 16);
            const uint4 u0 = lds128(sb + U + (2 * cp) * UCH + (tid & 1) * UPL + (8 + (tid >> 1)) * 16), u1 = lds128(sb + U + (2 * cp + 1) * UCH + (tid & 1) * UPL + (8 + (tid >> 1)) * 16);
            const uint32_t dw = ((const uint32_t*)&dd)[cp];
            const float D0 = bflo(dw), D1 = bfhi(dw);
            #pragma unroll
            for (int i = 0; i < 8; i++) {
                const uint32_t a0 = ((const uint32_t*)&y0)[i >> 1], a1 = ((const uint32_t*)&y1)[i >> 1], b0 = ((const uint32_t*)&u0)[i >> 1], b1 = ((const uint32_t*)&u1)[i >> 1];
                const float yy0 = fmaf((i & 1) ? bfhi(b0) : bflo(b0), D0, (i & 1) ? bfhi(a0) : bflo(a0));
                const float yy1 = fmaf((i & 1) ? bfhi(b1) : bflo(b1), D1, (i & 1) ? bfhi(a1) : bflo(a1));
                const uint32_t qw = ((const uint32_t*)&qr[i])[cp];
                outw[i][cp] = pack2(bflo(qw) * yy0, bfhi(qw) * yy1);
            }
        }
        #pragma unroll
        for (int i = 0; i < 8; i++) g_A[c * 2048 + i * 256 + tid] = make_uint4(outw[i][0], outw[i][1], outw[i][2], outw[i][3]);
    }
    TL(1);
}

namespace ok {
constexpr int STAGES = 4;
constexpr uint32_t STG = 49152, TOTAL = STAGES * STG + 32768 + 256;
}
#define R8(o) F4(d, o), F4(d, o + 4)
__device__ __forceinline__ void wgmma_n256_ss_tt(float* d, uint64_t da, uint64_t db, int accum) {
    asm volatile("{.reg .pred p; setp.ne.b32 p, %130, 0;\n"
        "wgmma.mma_async.sync.aligned.m64n256k16.f32.bf16.bf16 {%0,%1,%2,%3,%4,%5,%6,%7,%8,%9,%10,%11,%12,%13,%14,%15,"
        "%16,%17,%18,%19,%20,%21,%22,%23,%24,%25,%26,%27,%28,%29,%30,%31,%32,%33,%34,%35,%36,%37,%38,%39,%40,%41,%42,%43,%44,%45,%46,%47,"
        "%48,%49,%50,%51,%52,%53,%54,%55,%56,%57,%58,%59,%60,%61,%62,%63,%64,%65,%66,%67,%68,%69,%70,%71,%72,%73,%74,%75,%76,%77,%78,%79,"
        "%80,%81,%82,%83,%84,%85,%86,%87,%88,%89,%90,%91,%92,%93,%94,%95,%96,%97,%98,%99,%100,%101,%102,%103,%104,%105,%106,%107,%108,%109,%110,%111,"
        "%112,%113,%114,%115,%116,%117,%118,%119,%120,%121,%122,%123,%124,%125,%126,%127}, %128, %129, p, 1, 1, 1, 1;}"
        : R8(0), R8(8), R8(16), R8(24), R8(32), R8(40), R8(48), R8(56), R8(64), R8(72), R8(80), R8(88), R8(96), R8(104), R8(112), R8(120)
        : "l"(da), "l"(db), "r"(accum));
}
#undef R8
__global__ void __cluster_dims__(2, 1, 1) __launch_bounds__(288, 1)
out_kernel(const __grid_constant__ CUtensorMap tmO, const __grid_constant__ CUtensorMap tmWo, const __grid_constant__ CUtensorMap tmA,
           const __grid_constant__ CUtensorMap tmOut, const __grid_constant__ MainParams prm) {
    using namespace ok;
    extern __shared__ __align__(1024) uint8_t smem_raw[];
    const uint32_t SB = smem_u32(smem_raw), AT = SB + STAGES * STG, BAR = AT + 32768;
    if (SB & 1023) __trap();
    const int tid = threadIdx.x, w = tid >> 5, lane = tid & 31;
    const int rank = blockIdx.x & 1, mt = blockIdx.x >> 3, nt = (blockIdx.x >> 1) & 3;
    const uint32_t full = BAR, empty = BAR + 64, afull = BAR + 128;
    if (tid == 0) {
        for (int i = 0; i < STAGES; i++) { mbar_init(full + i * 8, 1); mbar_init(empty + i * 8, 8); }
        mbar_init(afull, 1);
        asm volatile("fence.mbarrier_init.release.cluster;" ::: "memory");
    }
    __syncthreads();
    asm volatile("griddepcontrol.wait;" ::: "memory");
    TL(4);
    if (w == 8) {
        if (lane == 0) {
            int st = 0, ph = 1;
            for (int kb = 0; kb < 32; kb++) {
                if (kb >= STAGES) mbar_wait(empty + st * 8, ph);
                mbar_expect(full + st * 8, STG);
                tma3d(SB + st * STG, &tmO, 0, (rank * 32 + kb) * 2, mt * 16, full + st * 8);
                tma3d(SB + st * STG + 16384, &tmWo, 0, (rank * 32 + kb) * 64, nt * 4, full + st * 8);
                if (kb == STAGES - 1) { mbar_expect(afull, 32768); tma3d(AT, &tmA, mt * 128, 0, (nt * 2 + rank) * 16, afull); }
                if (++st == STAGES) { st = 0; ph ^= 1; }
            }
        }
        __syncwarp();
        asm volatile("barrier.cluster.arrive.aligned; barrier.cluster.wait.aligned;" ::: "memory");
        asm volatile("barrier.cluster.arrive.aligned; barrier.cluster.wait.aligned;" ::: "memory");
    } else {
        const int wg = w >> 2, g = lane >> 2;
        float acc[128];
        const int tok0 = 32 * (4 * mt + (w >> 1)) + 8 * (g >> 1) + 4 * (w & 1) + (g & 1);
        const float g0 = g_gate[tok0], g1 = g_gate[tok0 + 2];
        int st = 0, ph = 0, pst = 0;
        #pragma unroll 1
        for (int kb = 0; kb < 32; kb++) {
            mbar_wait(full + st * 8, ph);
            const uint64_t da = mkdesc(SB + st * STG + wg * 8192, 128, 1024, 0), db = mkdesc(SB + st * STG + 16384, 8192, 1024, 1);
            wg_fence();
            #pragma unroll
            for (int ks = 0; ks < 4; ks++) wgmma_n256_ss_tt(acc, da + ks * 16, db + ks * 128, (kb | ks) != 0);
            wg_commit();
            wg_wait<1>();
            if (kb > 0 && lane == 0) mbar_arrive(empty + pst * 8);
            pst = st;
            if (++st == STAGES) { st = 0; ph ^= 1; }
        }
        wg_wait<0>();
        TLX(12);
        asm volatile("barrier.cluster.arrive.aligned; barrier.cluster.wait.aligned;" ::: "memory");
        uint32_t peer;
        asm volatile("mapa.shared::cluster.u32 %0, %1, %2;" : "=r"(peer) : "r"(SB + 65536 + tid * 16), "r"(rank ^ 1));
        #define SND(e) pack2(rank ? acc[8 * i + (e)] : acc[64 + 8 * i + (e)], rank ? acc[8 * i + (e) + 1] : acc[65 + 8 * i + (e)])
        #pragma unroll
        for (int i = 0; i < 8; i++)
            asm volatile("st.shared::cluster.v4.b32 [%0], {%1,%2,%3,%4};" :: "r"(peer + i * 4096), "r"(SND(0)), "r"(SND(2)), "r"(SND(4)), "r"(SND(6)) : "memory");
        #undef SND
        asm volatile("barrier.cluster.arrive.aligned; barrier.cluster.wait.aligned;" ::: "memory");
        mbar_wait(afull, 0);
        const float h0 = 1.f - g0, h1 = 1.f - g1;
        const uint32_t la = AT + (lane >> 4) * 2048 + (4 * (w & 1) + 2 * ((lane >> 3) & 1) + (lane & 1)) * 256 + (4 * (w >> 1) + ((lane & 7) >> 1)) * 16;
        const uint32_t ra = SB + (w * 16 + (lane & 15)) * 128;
        #pragma unroll
        for (int i = 0; i < 8; i++) {
            const uint32_t a = ra + (i >> 2) * 16384 + ((((i & 3) * 2 + (lane >> 4)) ^ (lane & 7)) << 4);
            uint32_t r0, r1, r2, r3;
            ldsm4(r0, r1, r2, r3, la + i * 4096);
            const uint4 u = lds128(SB + 65536 + tid * 16 + i * 4096);
            float p[8];
            #pragma unroll
            for (int e = 0; e < 8; e++) { const uint32_t x = ((const uint32_t*)&u)[e >> 1]; p[e] = (rank ? acc[64 + 8 * i + e] : acc[8 * i + e]) + ((e & 1) ? bfhi(x) : bflo(x)); }
            stsm4(a, pack2(fmaf(g0, bflo(r0), h0 * p[0]), fmaf(g0, bfhi(r0), h0 * p[1])), pack2(fmaf(g1, bflo(r1), h1 * p[2]), fmaf(g1, bfhi(r1), h1 * p[3])),
                     pack2(fmaf(g0, bflo(r2), h0 * p[4]), fmaf(g0, bfhi(r2), h0 * p[5])), pack2(fmaf(g1, bflo(r3), h1 * p[6]), fmaf(g1, bfhi(r3), h1 * p[7])));
        }
        asm volatile("fence.proxy.async.shared::cta;" ::: "memory");
        bsync<1, 256>();
        if (tid == 0) {
            for (int hf = 0; hf < 2; hf++)
                asm volatile("cp.async.bulk.tensor.5d.global.shared::cta.bulk_group [%0, {%2, %3, %3, %3, %4}], [%1];"
                    :: "l"(&tmOut), "r"(SB + hf * 16384), "r"(nt * 256 + rank * 128 + hf * 64), "r"(0), "r"(mt * 4) : "memory");
            asm volatile("cp.async.bulk.commit_group;" ::: "memory");
            asm volatile("cp.async.bulk.wait_group 0;" ::: "memory");
        }
        TL(5);
    }
}

typedef CUresult (*EncodeFn)(CUtensorMap*, CUtensorMapDataType, cuuint32_t, void*, const cuuint64_t*, const cuuint64_t*, const cuuint32_t*,
                             const cuuint32_t*, CUtensorMapInterleave, CUtensorMapSwizzle, CUtensorMapL2promotion, CUtensorMapFloatOOBfill);
static void enc(EncodeFn fn, CUtensorMap* m, void* base, int rank, const cuuint64_t* dims, const cuuint64_t* strides, const cuuint32_t* box, CUtensorMapSwizzle sw) {
    cuuint32_t es[5] = {1, 1, 1, 1, 1};
    fn(m, CU_TENSOR_MAP_DATA_TYPE_BFLOAT16, rank, base, dims, strides, box, es, CU_TENSOR_MAP_INTERLEAVE_NONE, sw,
       CU_TENSOR_MAP_L2_PROMOTION_L2_128B, CU_TENSOR_MAP_FLOAT_OOB_FILL_NONE);
}
static MainParams h_prm = {{768, 512, 384, 0, 0, 0, 0, 0, 0, 0, 0, 0}, 0, nullptr};

extern "C" void kernel_launch(void* const* d_in, const int* in_sizes, int n_in, void* d_out, int out_size) {
    const bf16* q = (const bf16*)d_in[0];
    const bf16* k = (const bf16*)d_in[1];
    const bf16* v = (const bf16*)d_in[2];
    const bf16* shift_k = (const bf16*)d_in[3];
    const bf16* ssm_k = (const bf16*)d_in[4];
    const bf16* ssm_D = (const bf16*)d_in[5];
    const bf16* mem0 = (const bf16*)d_in[7];
    const bf16* gate_w = (const bf16*)d_in[13];

    static EncodeFn fn = nullptr;
    static void* pO = nullptr;
    static void* pA = nullptr;
    if (!fn) {
        cudaDriverEntryPointQueryResult qr;
        cudaGetDriverEntryPoint("cuTensorMapEncodeTiled", (void**)&fn, cudaEnableDefault, &qr);
        cudaGetSymbolAddress(&pO, g_O);
        cudaGetSymbolAddress(&pA, g_A);
        void* pRB; cudaGetSymbolAddress(&pRB, g_RB);
        h_prm.rb = (char*)(((uintptr_t)pRB + (4u << 20) - 1) & ~(uintptr_t)((4u << 20) - 1));
        cudaFuncSetAttribute(main_kernel, cudaFuncAttributeMaxDynamicSharedMemorySize, mk::TOTAL);
        cudaFuncSetAttribute(conv_kernel, cudaFuncAttributeMaxDynamicSharedMemorySize, ck::TOTAL);
        cudaFuncSetAttribute(out_kernel, cudaFuncAttributeMaxDynamicSharedMemorySize, ok::TOTAL);
    }
    CUtensorMap mWq, mWk, mWv, mWo, mX, mO, mWo2, mA, mOut;
    {
        cuuint64_t d[2] = {4096, 1024}, s[1] = {8192}; cuuint32_t b[2] = {64, 256};
        enc(fn, &mWq, d_in[8], 2, d, s, b, CU_TENSOR_MAP_SWIZZLE_128B);
        enc(fn, &mWk, d_in[9], 2, d, s, b, CU_TENSOR_MAP_SWIZZLE_128B);
        enc(fn, &mWv, d_in[10], 2, d, s, b, CU_TENSOR_MAP_SWIZZLE_128B);
    }
    {
        cuuint64_t d[2] = {1024, 4096}, s[1] = {2048}; cuuint32_t b[2] = {64, 128};
        enc(fn, &mWo, d_in[11], 2, d, s, b, CU_TENSOR_MAP_SWIZZLE_128B);
        cuuint64_t d2[3] = {64, 4096, 16}, s2[2] = {2048, 128}; cuuint32_t b2[3] = {64, 64, 4};
        enc(fn, &mWo2, d_in[11], 3, d2, s2, b2, CU_TENSOR_MAP_SWIZZLE_128B);
    }
    {
        cuuint64_t d[3] = {64, 2048, 16}, s[2] = {2048, 128}; cuuint32_t b[3] = {64, 32, 8};
        enc(fn, &mX, d_in[0], 3, d, s, b, CU_TENSOR_MAP_SWIZZLE_128B);
    }
    {
        cuuint64_t d[3] = {256, 128, 256}, s[2] = {512, 65536}; cuuint32_t b[3] = {256, 2, 16};
        enc(fn, &mO, pO, 3, d, s, b, CU_TENSOR_MAP_SWIZZLE_NONE);
    }
    {
        cuuint64_t d[5] = {1024, 2, 4, 4, 64}, s[4] = {2048, 16384, 4096, 65536}; cuuint32_t b[5] = {64, 2, 4, 4, 4};
        cuuint64_t da[3] = {2048, 8, 128}, sa[2] = {4096, 32768}; cuuint32_t ba[3] = {128, 8, 16};
        enc(fn, &mA, pA, 3, da, sa, ba, CU_TENSOR_MAP_SWIZZLE_NONE);
        enc(fn, &mOut, d_out, 5, d, s, b, CU_TENSOR_MAP_SWIZZLE_128B);
    }
    cudaStream_t st = cudaStreamPerThread;
    conv_kernel<<<128, 288, ck::TOTAL, st>>>(q, k, v, shift_k, ssm_k, ssm_D, gate_w, (const bf16*)d_in[8], (const bf16*)d_in[9],
                                             (const bf16*)d_in[10], (const bf16*)d_in[11], mWq, mWk, mWv, mWo, h_prm.rb);
    cudaLaunchAttribute at[1];
    at[0].id = cudaLaunchAttributeProgrammaticStreamSerialization;
    at[0].val.programmaticStreamSerializationAllowed = 1;
    cudaLaunchConfig_t cfg = {};
    cfg.stream = st; cfg.attrs = at; cfg.numAttrs = PDL;
    cfg.gridDim = dim3(NCTA); cfg.blockDim = dim3(256); cfg.dynamicSmemBytes = mk::TOTAL;
    cudaLaunchKernelEx(&cfg, main_kernel, mWq, mWk, mWv, mWo, mX, mem0, (const bf16*)d_in[11], h_prm);
    cfg.gridDim = dim3(128); cfg.blockDim = dim3(288); cfg.dynamicSmemBytes = ok::TOTAL;
    cudaLaunchKernelEx(&cfg, out_kernel, mO, mWo2, mA, mOut, h_prm);
}
```

```cpp
#include <cuda_runtime.h>
#include <cuda_bf16.h>
#include <cuda.h>
#include <stdint.h>

typedef __nv_bfloat16 bf16;

constexpr int SEQ = 2048, DM = 1024, NH = 32, DH = 128, NSEG = 64;
constexpr int SPIN_LIMIT = 1 << 13, NCTA = 132;
#define NPR 6
#define PDL 1
#define TPF 1

constexpr uint32_t HOME_BITS = 0xB3000;
constexpr uint32_t RB_R = 0;
constexpr uint32_t RB_B = 0x80000;
constexpr uint32_t RB_T = RB_B + 0x4000;
constexpr uint32_t RB_P = RB_B + 0x20000;
constexpr uint32_t RB_X = 2u << 20;
__device__ uint4 g_RB[(8 << 20) / 16];
__device__ uint32_t g_cls[160];
__device__ uint4 g_T[2 * NH * 3072];
__device__ uint4 g_O[NSEG * 4 * 4096];
__device__ uint4 g_A[SEQ * DM / 8];
__device__ float g_gate[SEQ];
__device__ uint32_t g_err;
#define TL(i)
#define TLX(i)

__device__ __forceinline__ uint32_t smem_u32(const void* p) { return (uint32_t)__cvta_generic_to_shared(p); }
__device__ __forceinline__ uint32_t clk() { uint32_t c; asm volatile("mov.u32 %0, %%clock;" : "=r"(c) :: "memory"); return c; }
__device__ __forceinline__ void ldsm4(uint32_t& r0, uint32_t& r1, uint32_t& r2, uint32_t& r3, uint32_t a) {
    asm volatile("ldmatrix.sync.aligned.m8n8.x4.shared.b16 {%0,%1,%2,%3}, [%4];" : "=r"(r0), "=r"(r1), "=r"(r2), "=r"(r3) : "r"(a) : "memory");
}
__device__ __forceinline__ void ldsm4t(uint32_t& r0, uint32_t& r1, uint32_t& r2, uint32_t& r3, uint32_t a) {
    asm volatile("ldmatrix.sync.aligned.m8n8.x4.trans.shared.b16 {%0,%1,%2,%3}, [%4];" : "=r"(r0), "=r"(r1), "=r"(r2), "=r"(r3) : "r"(a) : "memory");
}
__device__ __forceinline__ void ldsm2(uint32_t& r0, uint32_t& r1, uint32_t a) {
    asm volatile("ldmatrix.sync.aligned.m8n8.x2.shared.b16 {%0,%1}, [%2];" : "=r"(r0), "=r"(r1) : "r"(a) : "memory");
}
__device__ __forceinline__ void stsm4t(uint32_t a, uint32_t r0, uint32_t r1, uint32_t r2, uint32_t r3) {
    asm volatile("stmatrix.sync.aligned.m8n8.x4.trans.shared.b16 [%0], {%1,%2,%3,%4};" :: "r"(a), "r"(r0), "r"(r1), "r"(r2), "r"(r3) : "memory");
}
__device__ __forceinline__ void mma16(float* c, uint32_t a0, uint32_t a1, uint32_t a2, uint32_t a3, uint32_t b0, uint32_t b1) {
    asm volatile("mma.sync.aligned.m16n8k16.row.col.f32.bf16.bf16.f32 {%0,%1,%2,%3}, {%4,%5,%6,%7}, {%8,%9}, {%0,%1,%2,%3};"
        : "+f"(c[0]), "+f"(c[1]), "+f"(c[2]), "+f"(c[3]) : "r"(a0), "r"(a1), "r"(a2), "r"(a3), "r"(b0), "r"(b1));
}
__device__ __forceinline__ void mma8(float* c, uint32_t a0, uint32_t a1, uint32_t b0) {
    asm volatile("mma.sync.aligned.m16n8k8.row.col.f32.bf16.bf16.f32 {%0,%1,%2,%3}, {%4,%5}, {%6}, {%0,%1,%2,%3};"
        : "+f"(c[0]), "+f"(c[1]), "+f"(c[2]), "+f"(c[3]) : "r"(a0), "r"(a1), "r"(b0));
}
__device__ __forceinline__ uint32_t pack2(float lo, float hi) {
    uint32_t r; asm("cvt.rn.bf16x2.f32 %0, %1, %2;" : "=r"(r) : "f"(hi), "f"(lo)); return r;
}
__device__ __forceinline__ uint32_t hadd2(uint32_t a, uint32_t b) {
    uint32_t r; asm("add.rn.bf16x2 %0, %1, %2;" : "=r"(r) : "r"(a), "r"(b)); return r;
}
__device__ __forceinline__ float bflo(uint32_t w) { return __uint_as_float(w << 16); }
__device__ __forceinline__ float bfhi(uint32_t w) { return __uint_as_float(w & 0xFFFF0000u); }
__device__ __forceinline__ void st_g32(void* p, uint32_t v) { asm volatile("st.relaxed.gpu.global.u32 [%0], %1;" :: "l"(p), "r"(v) : "memory"); }
__device__ __forceinline__ void st_g128(void* p, uint32_t a, uint32_t b, uint32_t c, uint32_t d) {
    asm volatile("st.relaxed.gpu.global.v4.u32 [%0], {%1,%2,%3,%4};" :: "l"(p), "r"(a), "r"(b), "r"(c), "r"(d) : "memory");
}
__device__ __forceinline__ uint4 lds128(uint32_t a) { uint4 v; asm volatile("ld.shared.v4.u32 {%0,%1,%2,%3}, [%4];" : "=r"(v.x), "=r"(v.y), "=r"(v.z), "=r"(v.w) : "r"(a) : "memory"); return v; }
__device__ __forceinline__ void sts128(uint32_t a, uint4 v) { asm volatile("st.shared.v4.u32 [%0], {%1,%2,%3,%4};" :: "r"(a), "r"(v.x), "r"(v.y), "r"(v.z), "r"(v.w) : "memory"); }
__device__ __forceinline__ float2 lds64f(uint32_t a) { float2 v; asm volatile("ld.shared.v2.f32 {%0,%1}, [%2];" : "=f"(v.x), "=f"(v.y) : "r"(a) : "memory"); return v; }
__device__ __forceinline__ void sts64f(uint32_t a, float x, float y) { asm volatile("st.shared.v2.f32 [%0], {%1,%2};" :: "r"(a), "f"(x), "f"(y) : "memory"); }
__device__ __forceinline__ void sts32f(uint32_t a, float x) { asm volatile("st.shared.f32 [%0], %1;" :: "r"(a), "f"(x) : "memory"); }
__device__ __forceinline__ void sts32(uint32_t a, uint32_t x) { asm volatile("st.shared.u32 [%0], %1;" :: "r"(a), "r"(x) : "memory"); }
__device__ __forceinline__ uint32_t lds32(uint32_t a) { uint32_t v; asm volatile("ld.shared.u32 %0, [%1];" : "=r"(v) : "r"(a) : "memory"); return v; }
__device__ __forceinline__ void cpa16(uint32_t dst, const void* src) { asm volatile("cp.async.cg.shared.global [%0], [%1], 16;" :: "r"(dst), "l"(src) : "memory"); }
__device__ __forceinline__ void cpa_commit() { asm volatile("cp.async.commit_group;" ::: "memory"); }
__device__ __forceinline__ void cpa_wait() { asm volatile("cp.async.wait_all;" ::: "memory"); }
template <int ID, int N> __device__ __forceinline__ void bsync() { asm volatile("bar.sync %0, %1;" :: "n"(ID), "n"(N) : "memory"); }
template <int ID, int N> __device__ __forceinline__ void barrive() { asm volatile("bar.arrive %0, %1;" :: "n"(ID), "n"(N) : "memory"); }
template <int ID, int N> __device__ __forceinline__ void bsync_if(bool on) { asm volatile("{ .reg .pred p; setp.ne.b32 p, %2, 0; @p bar.sync %0, %1; }" :: "n"(ID), "n"(N), "r"((int)on) : "memory"); }
template <int ID, int N> __device__ __forceinline__ void barrive_if(bool on) { asm volatile("{ .reg .pred p; setp.ne.b32 p, %2, 0; @p bar.arrive %0, %1; }" :: "n"(ID), "n"(N), "r"((int)on) : "memory"); }
template <int ID> __device__ __forceinline__ uint32_t any128(uint32_t x) {
    uint32_t r; asm volatile("{ .reg .pred p; setp.ne.b32 p, %1, 0; bar.red.or.pred p, %2, 128, p; selp.u32 %0, 1, 0, p; }" : "=r"(r) : "r"(x), "n"(ID) : "memory"); return r;
}
__device__ __forceinline__ void mbar_init(uint32_t mb, uint32_t n) { asm volatile("mbarrier.init.shared::cta.b64 [%0], %1;" :: "r"(mb), "r"(n) : "memory"); }
__device__ __forceinline__ void mbar_expect(uint32_t mb, uint32_t bytes) { asm volatile("mbarrier.arrive.expect_tx.shared::cta.b64 _, [%0], %1;" :: "r"(mb), "r"(bytes) : "memory"); }
__device__ __forceinline__ void mbar_arrive(uint32_t mb) { asm volatile("mbarrier.arrive.shared::cta.b64 _, [%0];" :: "r"(mb) : "memory"); }
__device__ __forceinline__ void mbar_wait(uint32_t mb, uint32_t ph) {
    asm volatile("{ .reg .pred p; .reg .u32 n; mov.u32 n, 0;\n"
                 "MW_%=: mbarrier.try_wait.parity.shared::cta.b64 p, [%0], %1; add.u32 n, n, 1; setp.lt.and.u32 p, n, %2, !p; @p bra.uni MW_%=; }"
                 :: "r"(mb), "r"(ph), "n"(SPIN_LIMIT) : "memory");
}
__device__ __forceinline__ void tma2d(uint32_t dst, const CUtensorMap* m, int c0, int c1, uint32_t mb) {
    asm volatile("cp.async.bulk.tensor.2d.shared::cluster.global.mbarrier::complete_tx::bytes [%0], [%1, {%3, %4}], [%2];"
        :: "r"(dst), "l"(m), "r"(mb), "r"(c0), "r"(c1) : "memory");
}
__device__ __forceinline__ void tma3d(uint32_t dst, const CUtensorMap* m, int c0, int c1, int c2, uint32_t mb) {
    asm volatile("cp.async.bulk.tensor.3d.shared::cluster.global.mbarrier::complete_tx::bytes [%0], [%1, {%3, %4, %5}], [%2];"
        :: "r"(dst), "l"(m), "r"(mb), "r"(c0), "r"(c1), "r"(c2) : "memory");
}
__device__ __forceinline__ void bulk_ld(uint32_t dst, const void* src, uint32_t bytes, uint32_t mb) {
    asm volatile("cp.async.bulk.shared::cluster.global.mbarrier::complete_tx::bytes [%0], [%1], %2, [%3];" :: "r"(dst), "l"(src), "r"(bytes), "r"(mb) : "memory");
}
__device__ __forceinline__ uint64_t mkdesc(uint32_t addr, uint32_t lbo, uint32_t sbo, uint32_t swz) {
    return (uint64_t)((addr & 0x3FFFF) >> 4) | ((uint64_t)(lbo >> 4) << 16) | ((uint64_t)(sbo >> 4) << 32) | ((uint64_t)swz << 62);
}
__device__ __forceinline__ void wg_fence() { asm volatile("wgmma.fence.sync.aligned;" ::: "memory"); }
__device__ __forceinline__ void wg_commit() { asm volatile("wgmma.commit_group.sync.aligned;" ::: "memory"); }
template <int N> __device__ __forceinline__ void wg_wait() { asm volatile("wgmma.wait_group.sync.aligned %0;" :: "n"(N) : "memory"); }
#define F4(d, o) "+f"(d[o]), "+f"(d[o + 1]), "+f"(d[o + 2]), "+f"(d[o + 3])
__device__ __forceinline__ void wgmma_n32_rs(float* d, const uint32_t* a, uint64_t db, int accum) {
    asm volatile("{.reg .pred p; setp.ne.b32 p, %21, 0;\n"
        "wgmma.mma_async.sync.aligned.m64n32k16.f32.bf16.bf16 {%0,%1,%2,%3,%4,%5,%6,%7,%8,%9,%10,%11,%12,%13,%14,%15}, {%16,%17,%18,%19}, %20, p, 1, 1, 0;}"
        : F4(d, 0), F4(d, 4), F4(d, 8), F4(d, 12) : "r"(a[0]), "r"(a[1]), "r"(a[2]), "r"(a[3]), "l"(db), "r"(accum));
}
__device__ __forceinline__ void wait_until(uint32_t tgt, uint32_t any) {
    asm volatile("{ .reg .pred p, q; .reg .u32 t; .reg .s32 d; mov.u32 t, %0; setp.ne.u32 q, %1, 0xFFFFFFFF;\n"
                 "WU_%=: @q mov.u32 t, %%clock; sub.s32 d, t, %0; setp.lt.s32 p, d, 0; @p bra.uni WU_%=; }" :: "r"(tgt), "r"(any) : "memory");
}

namespace mk {
constexpr uint32_t SB = 1024;
constexpr uint32_t WV = SB, WO = SB + 65536, XT = SB + 131072, TK = SB + 163840  , TQ = TK + 32768, MEM = TQ + 4096,
                   SC = MEM + 8192  , PT = SC + 6144,
                   OB = SC + 8192, SUM = OB + 2048, BAR = SUM + 512, GRP = BAR + 128, PROFB = BAR + 192,
                   TOTAL = PROFB - SB;
static_assert(TOTAL <= 232448, "shared memory");
constexpr uint32_t MB_WQ = BAR, MB_WK = BAR + 8, MB_WV = BAR + 16, MB_WO = BAR + 24, MB_X = BAR + 32, MB_KV = BAR + 40, MB_R = BAR + 48, MB_B = BAR + 56;
constexpr uint32_t XT2 = WV, RS = WV + 32768, VE = RS + 4096;
enum { B_START = 1, B_H0, B_H2, B_H3, B_S1, B_SC, B_SC2, B_S0, B_O, B_O2, B_PT, B_GO, B_VX, B_RD, B_BT };
constexpr uint64_t XD0 = (uint64_t)(XT >> 4) | ((uint64_t)1 << 16) | ((uint64_t)64 << 32) | ((uint64_t)1 << 62);
constexpr uint32_t TSLOT = NH * 49152;
}
struct MainParams { int d[12]; uint32_t zero; char* rb; };
#define XD(i) (mk::XD0 - ((i) >> 5) * ((mk::XT - mk::XT2) >> 4) + (((i) & 31) >> 2) * 256 + ((i) & 3) * 2)
#define XD4(i) XD(i), XD(i + 1), XD(i + 2), XD(i + 3)
#define XD16(i) XD4(i), XD4(i + 4), XD4(i + 8), XD4(i + 12)
__constant__ __align__(256) uint64_t c_xd[64] = {XD16(0), XD16(16), XD16(32), XD16(48)};
#define CUT(r) asm volatile("{ .reg .pred q; setp.eq.u32 q, %1, 0xFFFFFFFF; @q mov.u32 %0, %%clock; }" : "+r"(r) : "r"(t16) : "memory")
__device__ __forceinline__ uint32_t opq(uint32_t x) { asm volatile("" : "+r"(x)); return x; }
__device__ __forceinline__ float opqf(float x) { asm volatile("" : "+f"(x)); return x; }
#define PROF(i)
#define PROFW(i, w)
#define TRC(i, v)
#define RETRY(i, on)
#define P(i) prm.d[i]
#define DELAY(n) do { if (n) { _Pragma("unroll") for (int i_ = 0; i_ < n; i_++) asm volatile("mad.lo.u32 %0, %0, %1, %0;" : "+r"(pb) : "r"(prm.zero)); CUT(pa); } } while (0)

__device__ __forceinline__ uint32_t tagw(uint32_t w, uint32_t tau) { return (w & ~1u) | tau; }
__device__ __forceinline__ uint32_t ld_g32(const void* p) { uint32_t v; asm volatile("ld.relaxed.gpu.global.u32 %0, [%1];" : "=r"(v) : "l"(p) : "memory"); return v; }
__device__ __forceinline__ void ld_g64(uint32_t* v, const void* p) { asm volatile("ld.relaxed.gpu.global.v2.u32 {%0,%1}, [%2];" : "=r"(v[0]), "=r"(v[1]) : "l"(p) : "memory"); }
__device__ __forceinline__ void ld_g128(uint32_t* v, const void* p) {
    asm volatile("ld.relaxed.gpu.global.v4.u32 {%0,%1,%2,%3}, [%4];" : "=r"(v[0]), "=r"(v[1]), "=r"(v[2]), "=r"(v[3]) : "l"(p) : "memory");
}
__device__ __forceinline__ void st_g64(void* p, uint32_t a, uint32_t b) { asm volatile("st.relaxed.gpu.global.v2.u32 [%0], {%1,%2};" :: "l"(p), "r"(a), "r"(b) : "memory"); }
__device__ __forceinline__ void lds128f(float* v, uint32_t a) { asm volatile("ld.shared.v4.f32 {%0,%1,%2,%3}, [%4];" : "=f"(v[0]), "=f"(v[1]), "=f"(v[2]), "=f"(v[3]) : "r"(a) : "memory"); }
__device__ __forceinline__ void sts128f(uint32_t a, float x, float y, float z, float w) { asm volatile("st.shared.v4.f32 [%0], {%1,%2,%3,%4};" :: "r"(a), "f"(x), "f"(y), "f"(z), "f"(w) : "memory"); }
__device__ __forceinline__ void stsm4(uint32_t a, uint32_t r0, uint32_t r1, uint32_t r2, uint32_t r3) {
    asm volatile("stmatrix.sync.aligned.m8n8.x4.shared.b16 [%0], {%1,%2,%3,%4};" :: "r"(a), "r"(r0), "r"(r1), "r"(r2), "r"(r3) : "memory");
}
__device__ __forceinline__ void mmaq(float* c, const uint32_t* a, uint32_t b0, uint32_t b1) { mma16(c, a[0], a[1], a[2], a[3], b0, b1); }
template <int LUT> __device__ __forceinline__ uint32_t lop3(uint32_t a, uint32_t b, uint32_t c) { uint32_t r; asm("lop3.b32 %0, %1, %2, %3, %4;" : "=r"(r) : "r"(a), "r"(b), "r"(c), "n"(LUT)); return r; }
template <int N, int S> __device__ __forceinline__ uint32_t stale(const uint32_t* x, uint32_t tau) {
    if constexpr (N == 2) return lop3<0x7E>(x[0], tau, x[S]);
    else if constexpr (N == 3) return lop3<0xF6>(stale<2, S>(x, tau), x[2 * S], tau);
    else if constexpr (N == 4 || N == 16) return lop3<0xFC>(stale<N / 2, S>(x, tau), stale<N / 2, S>(x + N / 2 * S, tau), 0);
    else return lop3<0xFE>(stale<3, S>(x, tau), stale<3, S>(x + 3 * S, tau), stale<2, S>(x + 6 * S, tau));
}
__device__ __forceinline__ uint32_t late(uint32_t a, uint32_t b, uint32_t mask) {
    uint32_t r;
    asm volatile("{ .reg .pred p; .reg .b32 t; lop3.b32 t, %1, %2, %3, 0xA8; setp.ne.b32 p, t, 0; vote.sync.any.pred p, p, 0xFFFFFFFF; selp.u32 %0, 1, 0, p; }" : "=r"(r) : "r"(a), "r"(b), "r"(mask));
    return r;
}
#define AGAIN(id, reload, ...) _Pragma("unroll 1") for (int n_ = 0; __builtin_expect(__VA_ARGS__, 0) && n_ < SPIN_LIMIT; n_++) { RETRY(id, 1); reload; }
__device__ __forceinline__ uint32_t tile_off(int lane, int chunk0) {
    return ((lane >> 4) * 8 + (lane & 7)) * 128 + (((chunk0 + ((lane >> 3) & 1)) ^ (lane & 7)) << 4);
}
template <int K0, int K1>
__device__ __forceinline__ void load_tile(uint32_t a, uint32_t* T) {
    #pragma unroll
    for (int ks = K0; ks < K1; ks++) ldsm4t(T[4 * ks], T[4 * ks + 1], T[4 * ks + 2], T[4 * ks + 3], a + ks * 2048);
}
__device__ __forceinline__ void lds128u(uint32_t* v, uint32_t a) { asm volatile("ld.shared.v4.u32 {%0,%1,%2,%3}, [%4];" : "=r"(v[0]), "=r"(v[1]), "=r"(v[2]), "=r"(v[3]) : "r"(a) : "memory"); }
template <int K0, int K1, int STRIDE = 4096>
__device__ __forceinline__ void load_frag(uint32_t a, uint32_t* T) {
    #pragma unroll
    for (int ks = K0; ks < K1; ks++) lds128u(&T[4 * ks], a + ks * STRIDE);
}
template <int L0, int L1, bool INIT = false>
__device__ __forceinline__ void wg_run(float* acc, const uint32_t* A, const uint64_t* d) {
    if (L1 > L0) {
        wg_fence();
        #pragma unroll
        for (int l = L0; l < L1; l++) wgmma_n32_rs(acc, &A[4 * l], d[l], INIT || l != 0);
        wg_commit();
    }
}
__device__ __forceinline__ void load_x(const CUtensorMap* tmX, int c, int seg, uint32_t dst, bool on) {
    asm volatile("{ .reg .pred p; elect.sync _|p, 0xFFFFFFFF; setp.ne.and.b32 p, %6, 0, p;\n"
        "@p mbarrier.arrive.expect_tx.shared::cta.b64 _, [%3], 32768;\n"
        "@p cp.async.bulk.tensor.3d.shared::cluster.global.mbarrier::complete_tx::bytes [%4], [%0, {%5, %1, %2}], [%3]; }"
        :: "l"(tmX), "r"(seg * 32), "r"((c & 1) * 8), "r"(mk::MB_X), "r"(dst), "r"(0), "r"((int)on) : "memory");
}
__device__ __forceinline__ void bulk_expect(uint32_t mb, uint32_t bytes) {
    asm volatile("{ .reg .pred p; elect.sync _|p, 0xFFFFFFFF; @p mbarrier.arrive.expect_tx.shared::cta.b64 _, [%0], %1; }" :: "r"(mb), "r"(bytes) : "memory");
}
__device__ __forceinline__ void bulk_copy(uint32_t dst, const void* src, uint32_t bytes, uint32_t mb) {
    asm volatile("{ .reg .pred p; elect.sync _|p, 0xFFFFFFFF; @p cp.async.bulk.shared::cluster.global.mbarrier::complete_tx::bytes [%0], [%1], %2, [%3]; }"
        :: "r"(dst), "l"(src), "r"(bytes), "r"(mb) : "memory");
    __syncwarp();
}
__device__ __forceinline__ void bulk_copy_if(bool on, uint32_t dst, const void* src, uint32_t bytes, uint32_t mb) {
    asm volatile("{ .reg .pred p; elect.sync _|p, 0xFFFFFFFF; setp.ne.and.b32 p, %4, 0, p; @p cp.async.bulk.shared::cluster.global.mbarrier::complete_tx::bytes [%0], [%1], %2, [%3]; }"
        :: "r"(dst), "l"(src), "r"(bytes), "r"(mb), "r"((int)on) : "memory");
    __syncwarp();
}
__device__ __forceinline__ void kv_expect(uint32_t bytes) { bulk_expect(mk::MB_KV, bytes); }
__device__ __forceinline__ void kv_copy(uint32_t dst, const void* src, uint32_t bytes) { bulk_copy(dst, src, bytes, mk::MB_KV); }
__device__ __forceinline__ uint32_t gtime() { uint32_t c; asm volatile("mov.u32 %0, %%globaltimer_lo;" : "=r"(c) :: "memory"); return c; }
__device__ __forceinline__ void wait_g(uint32_t tgt, uint32_t any) {
    asm volatile("{ .reg .pred p, q; .reg .u32 t; mov.u32 t, %0; setp.ne.u32 q, %1, 0xFFFFFFFF;\n"
                 "WG_%=: @q mov.u32 t, %%globaltimer_lo; sub.u32 t, t, %0; setp.gt.u32 p, t, 0xFFFF0000; @p bra.uni WG_%=; }" :: "r"(tgt), "r"(any) : "memory");
    __syncwarp();
}
__device__ __forceinline__ uint32_t clkv(uint32_t any) {
    uint32_t c; asm volatile("{ .reg .pred q; setp.ne.u32 q, %1, 0xFFFFFFFF; mov.u32 %0, 0; @q mov.u32 %0, %%clock; }" : "=r"(c) : "r"(any) : "memory"); return c;
}
__device__ __forceinline__ char* kv_src(int c, int seg) { return (char*)g_T + ((seg & 1) * mk::TSLOT + (c >> 2) * 49152); }
__device__ __forceinline__ void prefetch_l2(const void* p, uint32_t bytes) {
    asm volatile("{ .reg .pred p; elect.sync _|p, 0xFFFFFFFF; @p cp.async.bulk.prefetch.L2.global [%0], %1; }" :: "l"(p), "r"(bytes) : "memory");
}
__device__ __forceinline__ uint32_t phase(int i) { return (~i >> 1) & 1; }
__device__ __forceinline__ void qk_pack(const float* acc, uint32_t* p) {
    #pragma unroll
    for (int i = 0; i < 4; i++) { p[i] = pack2(acc[4 * i], acc[4 * i + 1]); p[4 + i] = pack2(acc[4 * i + 2], acc[4 * i + 3]); }
}
__device__ __forceinline__ void sts128_if(bool on, uint32_t a, const uint32_t* p) {
    asm volatile("{ .reg .pred p; setp.ne.b32 p, %5, 0; @p st.shared.v4.u32 [%0], {%1,%2,%3,%4}; }" :: "r"(a), "r"(p[0]), "r"(p[1]), "r"(p[2]), "r"(p[3]), "r"((int)on) : "memory");
}
__device__ __forceinline__ void st_if(bool on, char* a, const uint32_t* p) {
    asm volatile("{ .reg .pred p; setp.ne.b32 p, %5, 0; @p st.relaxed.gpu.global.v4.u32 [%0], {%1,%2,%3,%4}; }" :: "l"(a), "r"(p[0]), "r"(p[1]), "r"(p[2]), "r"(p[3]), "r"((int)on) : "memory");
}
__device__ __forceinline__ char* tok_dst(int c, int seg, int wg) { return kv_src(c, seg) + (wg ? (c & 1) * 8192 + (c & 2) * 2048 : 32768 + (c & 1) * 2048 + (c & 2) * 512); }
#define HI8 (wg ? 0x220 : 0xC0)
#define TAGW ((t16 >> (wg ? 7 : 9)) & 3)
__device__ __forceinline__ void acc_init(float* acc, const uint32_t* p) {
    #pragma unroll
    for (int i = 0; i < 4; i++) { acc[4 * i] = bflo(p[i]); acc[4 * i + 1] = bfhi(p[i]); acc[4 * i + 2] = bflo(p[4 + i]); acc[4 * i + 3] = bfhi(p[4 + i]); }
}
__device__ __forceinline__ void acc_add(float* acc, const uint32_t* p) {
    #pragma unroll
    for (int i = 0; i < 4; i++) { acc[4 * i] += bflo(p[i]); acc[4 * i + 1] += bfhi(p[i]); acc[4 * i + 2] += bflo(p[4 + i]); acc[4 * i + 3] += bfhi(p[4 + i]); }
}
__device__ __forceinline__ void pack_tag(const float* acc, uint32_t* p, uint32_t tau, uint32_t j) {
    qk_pack(acc, p);
    #pragma unroll
    for (int i = 0; i < 4; i++)
        asm("{ .reg .pred q; setp.eq.u32 q, %2, %4; @q lop3.b32 %0, %0, 1, %3, 0xB8; @q lop3.b32 %1, %1, 1, %3, 0xB8; }" : "+r"(p[i]), "+r"(p[4 + i]) : "r"(j), "r"(tau), "r"(i));
}
__device__ __forceinline__ uint32_t kv_stale(uint32_t w, uint32_t l16, uint32_t tau) {
    uint32_t x[12];
    const uint32_t a = opq(l16 * 2 + ((l16 >> 4) & 0x1C) + w * 12288), aq = w == 2 ? opq(l16 * 2 + ((l16 >> 2) & 0x10) + ((l16 >> 5) & 0xC) + 24576) : a;
    #pragma unroll
    for (int i = 0; i < 12; i++) x[i] = lds32(mk::TK + i * 1024 + (i < 8 ? a : aq));
    return (stale<8, 1>(x, tau) | stale<4, 1>(x + 8, tau)) & 1;
}
__device__ __forceinline__ void get_kv(int c, int seg) {
    kv_expect(36864); kv_copy(mk::TK, kv_src(c, seg), 32768); kv_copy(mk::TQ, kv_src(c, seg) + (32768 + (c & 3) * 4096), 4096);
}
constexpr uint32_t ONES = 0x3F803F80u;
__device__ __forceinline__ float rcpf(float x) { float r; asm("rcp.approx.ftz.f32 %0, %1;" : "=f"(r) : "f"(x)); return r; }

#define ANN 2
#define POL 8
#define PRE0 4
#define PRE1 4
#define HC 2
#define HR 10
#define CO 1
#define HS 2
#define VP 0
#define KM 2
#define NLDS 2
#define AL 2
#define RP 26
#define RQ 2
#define RL 29
#define R4 1
#define KVP 12
#define LD7 8
#define XP 3
#define G2 0
#define NB 26
#define BD 8
#define NP 22
#define TA 4
#define TA0 2
#define NT 19
#define VH 1
#define TRIES 200
#define NPW 3
#define EV0 6
#define EV1 8
#define WA1 6
#define WA2 9
#define H2 10
#define QV 1
#define QD 0
#define KD 0
#define VD 0
#define WA0 4
#define ONE 0
#define PP 12
#define OBA 3
#define WA3 1
#define WB1 0
#define WB2 12
#define WB3 14
#define H0 6
#define H3 10
__device__ __forceinline__ uint32_t tagm(uint32_t w, uint32_t mask, uint32_t tau) { return lop3<0xB8>(w, mask, tau); }
__device__ __forceinline__ char* at(uint32_t lo, uint32_t hi) { char* p; asm("mov.b64 %0, {%1,%2};" : "=l"(p) : "r"(lo), "r"(hi)); return p; }
__device__ __forceinline__ float ex2(float x) { float r; asm("ex2.approx.ftz.f32 %0, %1;" : "=f"(r) : "f"(x)); return r; }
__device__ __forceinline__ float max8(const float* x) { return fmaxf(fmaxf(fmaxf(x[0], x[1]), fmaxf(x[2], x[3])), fmaxf(fmaxf(x[4], x[5]), fmaxf(x[6], x[7]))); }
__device__ __forceinline__ float max4lanes(float m) { return fmaxf(fmaxf(m, __shfl_xor_sync(~0u, m, 1)), fmaxf(__shfl_xor_sync(~0u, m, 2), __shfl_xor_sync(~0u, m, 3))); }
constexpr float SCL = 0.08838834764831845f * 1.4426950408889634f;
__device__ __forceinline__ void tok_scores(float* x, uint32_t sa) {
    float y[8];
    lds128f(x, sa); lds128f(y, sa + 1024); lds128f(x + 4, sa + 512); lds128f(y + 4, sa + 1536);
    #pragma unroll
    for (int i = 0; i < 8; i++) x[i] += y[i];
}
__device__ __forceinline__ void mem_scores(float* x, uint32_t sa) {
    float z[8];
    lds128f(z, sa + 2048); lds128f(z + 4, sa + 2560);
    x[8] = (z[0] + z[2]) + (z[4] + z[6]); x[9] = (z[1] + z[3]) + (z[5] + z[7]);
}

struct Ctx { uint32_t u_rs, u_rl, u_bs, u_bl, rblo, rbhi; int w8, c, kc; };
template <int wg>
__device__ __forceinline__ void steps(uint32_t* W, uint32_t* T, uint32_t t16, uint32_t pa, uint32_t pb, const Ctx& cx, const CUtensorMap* tmX, const MainParams& prm) {
    using namespace mk;
    const int c = cx.c, kap = c & 1, w8 = cx.w8;
    const uint32_t rbhi = cx.rbhi;
    uint32_t u_rs = cx.u_rs, u_rl = cx.u_rl, u_bs = cx.u_bs, u_bl = cx.u_bl ^ ((c & 2) << 14);
    uint32_t u_x = cx.rblo + RB_X + (c >> 2) * 16384, u_xs = u_x + kap * 2048 + (c & 2) * 512;
    uint32_t u_ta = ((cx.u_bl & ~0x10000u) ^ (kap << 12)) + (RB_T - RB_B) + 1024;
    uint32_t u_rp = cx.rblo + RB_T + 1024 + c * 4;
    uint32_t u_og = (c & 3) * 65536 + (c >> 2) * 2048 + (w8 & 3) * 256;
    const uint32_t u_sa = (w8 & 2) * 256 + (w8 & 1) * 8;
    #define TOK_DST() tok_dst(c, seg, wg)
    constexpr int EV = wg ? EV1 : EV0;
    constexpr uint32_t VEB = VE + (wg ? EV0 * 2048 - 2048 : 0) - (16 - EV) * 2048;
    static_assert((EV0 + EV1) * 2048 <= 28672, "");
    __syncthreads();
    #pragma unroll
    for (int i = 16 - EV; i < 16; i++) sts128(VEB + i * 2048 + t16, make_uint4(T[4 * i], T[4 * i + 1], T[4 * i + 2], T[4 * i + 3]));
    asm volatile("fence.proxy.async.shared::cta;" ::: "memory");
    #pragma unroll 1
    for (int s = 0, bc = 0, redo = 0, kc = cx.kc;;) {
        bc = opq(bc + 1);
        t16 |= prm.zero & bc;
        const int seg = s + 2;
        const uint32_t tau = phase(s);
        const uint32_t l16 = opq(t16 & 0x1F0);
        uint32_t F[64];
        float ot[3][2][4];
        uint32_t an[4];
        #define LDB(i) ldsm4t(b[i][0], b[i][1], b[i][2], b[i][3], MEM + l16 + (i) * 512)
        #define ST_X() do { char* xs = at(u_xs + (pb >> 16), rbhi) + wg * 4096; \
            st_g32(xs, tagm(pack2((a[0][0] + a[1][0]) + (a[2][0] + a[3][0]), (a[0][2] + a[1][2]) + (a[2][2] + a[3][2])), mG, tau * 0x10001u)); \
            st_g32(xs + 32, tagm(pack2((a[0][1] + a[1][1]) + (a[2][1] + a[3][1]), (a[0][3] + a[1][3]) + (a[2][3] + a[3][3])), mG, tau * 0x10001u)); } while (0)
        #define ST_V() st_g64(at(u_xs + (t16 >> 1), rbhi) + (8192 + wg * 3072), \
            tagm(pack2((v[0][0] + v[1][0]) + (v[2][0] + v[3][0]), (v[0][1] + v[1][1]) + (v[2][1] + v[3][1])), mT, tau), \
            pack2((v[0][2] + v[1][2]) + (v[2][2] + v[3][2]), (v[0][3] + v[1][3]) + (v[2][3] + v[3][3])))
        #define V_MMA(i, o) do { mmaq(v[2 * ((i) & 1)], &T[8 * (i)], b[(o) + (i)][0], b[(o) + (i)][1]); mmaq(v[2 * ((i) & 1) + 1], &T[8 * (i) + 4], b[(o) + (i)][2], b[(o) + (i)][3]); } while (0)
        #define ST_R(i) do { \
                const uint32_t r0 = pack2((r[i][0][0] + r[i][1][0]) * i0, (r[i][0][1] + r[i][1][1]) * i1); \
                const uint32_t r1 = pack2((r[i][0][2] + r[i][1][2]) * i0, (r[i][0][3] + r[i][1][3]) * i1); \
                st_g64(at(ra ^ (i * 0x3000), rbhi), tagm(r0, mT, tau), r1); } while (0)
        #define LD_OB(i) ldsm4t(ob[4 * (i)], ob[4 * (i) + 1], ob[4 * (i) + 2], ob[4 * (i) + 3], OB + l16 + (i) * 512)
        #define WO_MMA(have, more, mid, tail) uint32_t ob[16], ra; float r[2][2][4] = {}; \
            LD_OB(0); __syncwarp(); LD_OB(1); __syncwarp(); if (OBA > 2) { LD_OB(2); __syncwarp(); } \
            _Pragma("unroll") for (int i = have; i < have + more; i++) { lds128u(&F[4 * i], WO + t16 + i * 4096); __syncwarp(); } \
            _Pragma("unroll") for (int i = 0; i < 16; i++) { \
                if (!(i & 1) || (i > 4 && i < 8)) CUT(pb); \
                if (i == 4) LD_OB(OBA); \
                if (i == 5 && OBA == 2) LD_OB(3); \
                { const int n = have + more + i - 8 + OBA; if (i >= 8 - OBA && n < 16) lds128u(&F[4 * n], WO + t16 + n * 4096); } \
                if (wg == 0 && i == 4) { const float2 su = lds64f(SUM + (l16 >> 1)); i0 = su.x; i1 = su.y; } \
                mmaq(r[(i >> 1) & 1][i & 1], &F[4 * i], ob[(i >> 2) * 4 + 2 * (i & 1)], ob[(i >> 2) * 4 + 2 * (i & 1) + 1]); \
                if (wg && i == 2) { i0 = opqf(rcpf(i0)); i1 = opqf(rcpf(i1)); } \
                if (i == PP) { mid; } \
                if (wg && i == POL) POLL(); \
                if (!wg && i == KVP) bulk_copy(TK + 16384 + w8 * 4096, kv_src(c, s + 1) + (16384 + w8 * 4096), 4096, MB_KV); \
                if (i == 12) ra = opq(lop3<0x6A>((l16 >> 1) * 33, 0x1078, u_rs)); } \
            CUT(pb); tail; \
            if (!wg) { i0 = rcpf(i0); i1 = rcpf(i1); } \
            ST_R(0); ST_R(1)
        #define LD_X(r, o) do { ld_g64(r, xa + (o)); ld_g64(r + 2, xa + ((o) + 2048)); ld_g64(r + 4, xa + ((o) + 1024)); ld_g64(r + 6, xa + ((o) + 3072)); } while (0)
        #define REPORT(w, add) asm volatile("{ .reg .pred p; .reg .u32 t; setp.lt.u32 p, %1, 32; mov.u32 t, %1; @p mov.u32 t, %%globaltimer_lo; add.u32 t, t, %3; lop3.b32 t, t, 31, %2, 0xB8; @p st.relaxed.gpu.global.u32 [%0], t; }" \
            :: "l"(at(u_rp + (l16 << 8), rbhi)), "r"(t16 - (w) * 512), "r"(s), "r"(add) : "memory")
        #define POLL() asm volatile("{ .reg .pred p; setp.ge.u32 p, %5, 3584; mov.u32 %0, 0; mov.u32 %1, 0; mov.u32 %2, 0; mov.u32 %3, 0; @p ld.relaxed.gpu.global.v4.u32 {%0,%1,%2,%3}, [%4]; }" \
            : "=&r"(an[0]), "=&r"(an[1]), "=&r"(an[2]), "=&r"(an[3]) : "l"(at(u_ta + l16, rbhi)), "r"(t16) : "memory")
        #define GET_B(sl) do { const uint32_t a_ = u_bl ^ (sl); bulk_copy(MEM, at(a_, rbhi), 4096, MB_B); bulk_copy(MEM + 4096, at(a_ ^ 0x3000, rbhi), 4096, MB_B); } while (0)
        if constexpr (wg == 0) {
            float a[4][4], v[4][4] = {};
            uint32_t b[16][4];
            if (__builtin_expect(redo, 0)) {
                RETRY(6, 1);
                bsync<B_RD, 256>();
                if (w8 == 3) { bulk_expect(MB_B, 8192); GET_B(1 << 20); }
                __syncwarp();
            }
            const uint32_t ck = opq(t16 * 2 + ((l16 >> 4) & 0x1C)), tp = opq(phase(s - 1)), cm = opq((2 * bc + (s > 0 && bc < SPIN_LIMIT)) | (t16 >> 19));
            CUT(pa);
            mbar_wait(MB_B, ~bc & 1);
            LDB(8); __syncwarp(); LDB(9); __syncwarp();
            const uint32_t c0 = lds32(MEM + ck), c1 = lds32(MEM + 4096 + ck);
            __syncwarp();
            #pragma unroll
            for (int n = 2; n < PRE0; n++) { LDB(n ^ 8); __syncwarp(); }
            PROF(0);
            #pragma unroll
            for (int n = 0; n < 16; n++) {
                const int i = n ^ 8;
                if (!(n & 1)) {
                    CUT(pa);
                    if (PRE0 < 8 && n + PRE0 < 16) { LDB((n + PRE0) ^ 8); __syncwarp(); LDB((n + PRE0 + 1) ^ 8); __syncwarp(); }
                    if (PRE0 == 8 && n >= 2 && n < 10) { LDB(n - 2); __syncwarp(); LDB(n - 1); __syncwarp(); }
                    if (n == HC) redo = opq(lop3<0x7E>(c0, tp, c1) & cm);
                    if (n == HC + 2) asm volatile("{ .reg .pred p; setp.ne.u32 p, %2, 0; @p st.shared.u32 [%0], %1; }" :: "r"(SUM + 256), "r"(cm), "r"(redo & 1) : "memory");
                    if (n == H0) { barrive<B_H0, 256>(); CUT(pa); }
                    if (n == HR) bsync<B_START, 128>();
                    if (n == HR + 2) { redo = lds32(SUM + 256 + opq(t16 >> 20)); __syncwarp(); }
                }
                else if (CO) CUT(pa);
                if (n < 2) { a[2 * n][0] = a[2 * n][1] = a[2 * n][2] = a[2 * n][3] = a[2 * n + 1][0] = a[2 * n + 1][1] = a[2 * n + 1][2] = a[2 * n + 1][3] = 0.f; }
                mmaq(a[2 * (i & 1)], &W[8 * i], b[i][0], b[i][1]); mmaq(a[2 * (i & 1) + 1], &W[8 * i + 4], b[i][2], b[i][3]);
            }
            redo = !late(redo ^ (2 * bc + 1), 0, ~0u);
            CUT(pa);
            if (__builtin_expect(redo, 0)) { __syncwarp(); continue; }
            CUT(pa); CUT(pb);
            const uint32_t mG = (l16 & 0x1C0) ? 0 : 0x10001u, mT = (l16 & 0x30) ? 0 : 1;
            ST_X();
            CUT(pa);
            PROF(1);
            const char* const xa = at(u_x + (t16 >> 1), rbhi);
            float sc[4][4];
            uint32_t k[8], A[16], q[16], kf[16];
            #define LD_Q(xb) do { LD_X(q, 0); { const char* const xa = xb; LD_X(q + 8, 0); } } while (0)
            #define XB() at((u_x + (opq(t16) >> 1)) ^ 256, rbhi)
            #define LD_A(i) ldsm4t(A[4 * i], A[4 * i + 1], A[4 * i + 2], A[4 * i + 3], TQ + (i & 1) * 1024 + ((i & 2) ? qb : qa))
            #define LD_K(mid) do { uint32_t k1[16]; \
                _Pragma("unroll") for (int i = 0; i < 4; i++) { const uint32_t a_ = ka[i]; \
                    ldsm4t(kf[4 * i], kf[4 * i + 1], kf[4 * i + 2], kf[4 * i + 3], TK + a_); ldsm4t(k1[4 * i], k1[4 * i + 1], k1[4 * i + 2], k1[4 * i + 3], TK + 8192 + a_); __syncwarp(); } \
                LD_A(0); LD_A(1); if (KM) { LD_A(2); LD_A(3); CUT(pb); } if (KM == 2) { mid; } \
                _Pragma("unroll") for (int i = 0; i < 8; i++) kf[i] = opq(hadd2(kf[i], k1[i])); \
                if (!KM) { CUT(pb); LD_A(2); LD_A(3); } \
                _Pragma("unroll") for (int i = 8; i < 16; i++) kf[i] = opq(hadd2(kf[i], k1[i])); \
                if (KM < 2) { mid; } \
                _Pragma("unroll") for (int i = 0; i < 8; i++) A[2 * i + 1] = opq(hadd2(A[2 * i], A[2 * i + 1])); } while (0)
            #pragma unroll
            for (int i = 7; i >= 0; i--) V_MMA(i, 0);
            const char* const xb = XB();
            const uint32_t ka[4] = {opq(pa & 0xFFFF), opq((pa & 0xFFFF) ^ 0x400), opq((pa & 0xFFFF) ^ 0x10), opq((pa & 0xFFFF) ^ 0x410)}, qa = opq(pa >> 16), qb = opq(qa ^ 0x100);
            ST_V();
            CUT(pb);
            DELAY(QD);
            LD_Q(xb);
            CUT(pb);
            bsync<B_H2, 256>();
            #define GET_K() CUT(pb); bsync<B_H3, 256>(); LD_X(k, 4096); if (HS == 2) barrive<B_VX, 256>(); CUT(pb); PROF(3)
            LD_K(GET_K());
            CUT(pb);
            AGAIN(1, LD_Q(XB()); LD_X(k, 4096); sts32(SUM + 268, s + 1), late(stale<4, 2>(q, tau), stale<4, 2>(q + 8, tau), mT))
            #pragma unroll
            for (int i = 0; i < 4; i++) {
                A[4 * i] = hadd2(q[4 * i], q[4 * i + 2]); A[4 * i + 2] = hadd2(q[4 * i + 1], q[4 * i + 3]);
                if (i < 2) { sc[i][0] = sc[i][1] = sc[i][2] = sc[i][3] = sc[2 + i][0] = sc[2 + i][1] = sc[2 + i][2] = sc[2 + i][3] = 0.f; }
                mmaq(sc[i & 1], A + 4 * i, kf[2 * i], kf[2 * i + 1]); mmaq(sc[2 + (i & 1)], A + 4 * i, kf[8 + 2 * i], kf[9 + 2 * i]);
            }
            sts128f(SC + t16, sc[0][0] + sc[1][0], sc[0][1] + sc[1][1], sc[2][0] + sc[3][0], sc[2][1] + sc[3][1]);
            barrive<B_S1, 256>();
            sts128f(SC + 3072 + t16, sc[0][2] + sc[1][2], sc[0][3] + sc[1][3], sc[2][2] + sc[3][2], sc[2][3] + sc[3][3]);
            load_frag<0, WB1>(WO + t16, F);
            const uint32_t sa = opq(l16 + u_sa);
            CUT(pb);
            PROF(4);
            float d[16];
            #pragma unroll 1
            for (int n_ = 0;; n_++) {
                #pragma unroll
                for (int i = 0; i < 4; i++) { d[4 * i] = d[4 * i + 1] = d[4 * i + 2] = d[4 * i + 3] = 0.f; mmaq(d + 4 * i, A + 4 * (i >> 1), k[2 * i], k[2 * i + 1]); }
                if (__builtin_expect(!late(stale<2, 2>(k, tau), stale<2, 2>(k + 4, tau), mT), 1) || n_ >= SPIN_LIMIT) break;
                RETRY(2, 1);
                LD_X(k, 4096);
            }
            sts64f(SC + 2048 + sa, (d[0] + d[4]) + (d[8] + d[12]), (d[1] + d[5]) + (d[9] + d[13]));
            barrive<B_SC, 256>();
            CUT(pb);
            sts64f(SC + 5120 + sa, (d[2] + d[6]) + (d[10] + d[14]), (d[3] + d[7]) + (d[11] + d[15]));
            PROF(5);
            if (w8 == 0) {
                float x[10];
                bsync<B_S0, 128>();
                tok_scores(x, SC + 3072 + l16); mem_scores(x, SC + 3072 + l16);
                __syncwarp();
                load_frag<WB1, WB2>(WO + t16, F);
                const int g = l16 >> 6, lim = 8 * (g >> 1) + 2 * (c & 3) + (g & 1) - ((l16 >> 1) & 0x18);
                #pragma unroll
                for (int i = 0; i < 8; i++) if (i > lim) x[i] = -INFINITY;
                const float ms = opqf(-SCL * max4lanes(fmaxf(max8(x), fmaxf(x[8], x[9]))));
                CUT(pb);
                #pragma unroll
                for (int i = 0; i < 10; i++) x[i] = ex2(fmaf(x[i], SCL, ms));
                load_frag<WB2, WB3>(WO + t16, F);
                sts128(PT + l16, make_uint4(pack2(x[0], x[1]), pack2(x[2], x[3]), pack2(x[4], x[5]), pack2(x[6], x[7])));
                sts32(PT + 512 + (l16 >> 2), pack2(x[8], x[9]));
                if (!ONE) barrive<B_PT, 160>();
            } else {
                if (ANN == 2) { bsync<B_S0, 128>(); const uint32_t f = lds32(SUM + 268 + opq(t16 >> 16)); REPORT(3, f == s + 1 ? P(2) : 0); } else barrive<B_S0, 128>();
                if (w8 == 1) { if (seg < NSEG) mbar_wait(MB_X, seg & 1); }
                else if (w8 == 2) {
                    bulk_expect(MB_KV, 36864);
                    bulk_copy(TK, kv_src(c, s + 1), 16384, MB_KV); bulk_copy(TQ, kv_src(c, s + 1) + (32768 + (c & 3) * 4096), 4096, MB_KV);
                    bulk_expect(MB_B, 8192); bulk_expect(MB_R, 4096);
                    __syncwarp();
                }
                bsync<B_SC2, 224>();
                load_frag<WB1, WB3>(WO + t16, F);
                __syncwarp();
                CUT(pb);
            }
            bsync<B_O2, 256>();
            PROF(6);
            float i0, i1;
            WO_MMA(WB3, 0, , );
        } else {
            float a[4][4], v[4][4] = {};
            uint32_t b[16][4];
            barrive_if<B_RD, 256>(redo);
            CUT(pa);
            bsync<B_H0, 256>();
            #pragma unroll
            for (int n = 0; n < PRE1; n++) { LDB(n); __syncwarp(); }
            redo = lds32(SUM + 256 + opq(t16 >> 20));
            PROF(0);
            #pragma unroll
            for (int i = 0; i < 16; i++) {
                if (!(i & 1)) {
                    CUT(pa);
                    if (PRE1 < 8 && i + PRE1 < 16) { LDB(i + PRE1); __syncwarp(); LDB(i + PRE1 + 1); __syncwarp(); }
                    if (PRE1 == 8 && i >= 2 && i < 10) { LDB(i + 6); __syncwarp(); LDB(i + 7); __syncwarp(); }
                    if (i == 6) redo = !late(redo ^ (2 * bc + 1), 0, ~0u);
                    if (i == H2) { barrive_if<B_H2, 256>(!redo); CUT(pa); }
                }
                else if (CO) CUT(pa);
                if (i < 2) { a[2 * i][0] = a[2 * i][1] = a[2 * i][2] = a[2 * i][3] = a[2 * i + 1][0] = a[2 * i + 1][1] = a[2 * i + 1][2] = a[2 * i + 1][3] = 0.f; }
                mmaq(a[2 * (i & 1)], &W[8 * i], b[i][0], b[i][1]); mmaq(a[2 * (i & 1) + 1], &W[8 * i + 4], b[i][2], b[i][3]);
            }
            if (__builtin_expect(redo, 0)) { __syncwarp(); continue; }
            CUT(pa); CUT(pb);
            if (H3 == 0) { barrive<B_H3, 256>(); CUT(pb); }
            const uint32_t mG = (l16 & 0x1C0) ? 0 : 0x10001u, mT = (l16 & 0x30) ? 0 : 1;
            ST_X();
            if (H3 == 1) barrive<B_H3, 256>();
            CUT(pa);
            PROF(1);
            #pragma unroll
            for (int i = 7; i >= 0; i--) { V_MMA(i, 8); if (H3 == 9 - i) { CUT(pb); barrive<B_H3, 256>(); CUT(pb); } }
            ST_V();
            CUT(pb);
            if (H3 == 10) { DELAY(KD); if (HS == 1) bsync<B_H3, 256>(); else barrive<B_H3, 256>(); CUT(pb); if (HS < 2) DELAY(6); }
            if (HS == 2) bsync<B_VX, 256>();
            PROF(2);
            uint32_t vf[16], vm[16];
            const uint32_t va = opq(pa), vb = opq(va ^ 0x20);
            #define LD_V() do { _Pragma("unroll") for (int i = 0; i < 4; i++) { const uint32_t a_ = TK + 16384 + ((i & 1) ? vb : va) + (i >> 1) * 4096; \
                ldsm4(vf[4 * i], vf[4 * i + 1], vf[4 * i + 2], vf[4 * i + 3], a_); ldsm4(vm[4 * i], vm[4 * i + 1], vm[4 * i + 2], vm[4 * i + 3], a_ + 8192); } } while (0)
            LD_V();
            __syncwarp();
            load_frag<0, WA0>(WO + t16, F);
            #pragma unroll
            for (int i = 0; i < 16; i++) vf[i] = opq(hadd2(vf[i], vm[i]));
            const char* const xa = at(u_x + (t16 >> 1), rbhi) + (8192 - 1024);
            if (VP) CUT(pb);
            DELAY(VD);
            LD_X(vm, 0); LD_X(vm + 8, 4096);
            __syncwarp();
            load_frag<WA0, WA1>(WO + t16, F);
            CUT(pb);
            float x[10];
            bsync<B_S1, 256>();
            tok_scores(x, SC + l16);
            const float mt = opqf(max8(x));
            if (ANN == 3) REPORT(7, 0);
            CUT(pb);
            PROF(3);
            bsync<B_SC, 256>();
            mem_scores(x, SC + l16);
            const float m1 = fmaxf(mt, fmaxf(x[8], x[9]));
            const float m2 = __shfl_xor_sync(~0u, m1, 1), m3 = __shfl_xor_sync(~0u, m1, 2), m4 = __shfl_xor_sync(~0u, m1, 3);
            CUT(pb);
            load_frag<WA1, WA2>(WO + t16, F);
            barrive<B_SC2, 224>();
            uint32_t p[5], vs[4];
            #define SUM_V() do { _Pragma("unroll") for (int i = 0; i < 4; i++) { const int e = (i >> 1) * 4 + (i & 1); vs[i] = hadd2(hadd2(vm[e], vm[e + 8]), hadd2(vm[e + 2], vm[e + 10])); } } while (0)
            CUT(pb);
            const float ms = -SCL * fmaxf(fmaxf(m1, m2), fmaxf(m3, m4));
            PROF(5);
            #pragma unroll
            for (int i = 0; i < 10; i++) x[i] = fmaf(x[i], SCL, ms);
            x[8] = opqf(ex2(x[8])); x[9] = opqf(ex2(x[9]));
            CUT(pb);
            uint32_t badv = late(stale<4, 2>(vm, tau), stale<4, 2>(vm + 8, tau), mT);
            SUM_V();
            #pragma unroll
            for (int i = 0; i < 4; i++) { x[i] = opqf(ex2(x[i])); vs[i] = opq(vs[i]); }
            const uint32_t z0 = t16 >> 16;
            uint32_t one[4] = {opq(ONES | z0), opq(ONES ^ z0), opq(ONES + z0), opq(ONES - z0)};
            CUT(pb);
            #pragma unroll
            for (int i = 4; i < 8; i++) x[i] = ex2(x[i]);
            #pragma unroll
            for (int i = 0; i < 5; i++) p[i] = pack2(x[2 * i], x[2 * i + 1]);
            float sm[4] = {};
            #define PV(also) do { float o[8] = {}; \
                mma8(o, vs[0], vs[1], p[4]); mma8(o + 4, vs[2], vs[3], p[4]); if (also) mma8(sm, one[0], one[1], p[4]); \
                mmaq(o, vf, p[0], p[1]); mmaq(o + 4, vf + 8, p[0], p[1]); if (also) mmaq(sm, one, p[0], p[1]); \
                mmaq(o, vf + 4, p[2], p[3]); mmaq(o + 4, vf + 12, p[2], p[3]); if (also) mmaq(sm, one, p[2], p[3]); \
                stsm4(OB - 2048 + opq(t16), pack2(o[0], o[1]), pack2(o[2], o[3]), pack2(o[4], o[5]), pack2(o[6], o[7])); } while (0)
            PV(true);
            if (w8 == 4) sts64f(SUM + (l16 >> 1), sm[0], sm[1]);
            if (__builtin_expect(badv, 0)) {
                int n_ = 0;
                uint32_t vm[16];
                const char* const xa = at(u_x + (8192 - 1024) + (opq(t16) >> 1), rbhi);
                do { RETRY(3, 1); LD_X(vm, 0); LD_X(vm + 8, 4096); } while (late(stale<4, 2>(vm, tau), stale<4, 2>(vm + 8, tau), mT) && ++n_ < SPIN_LIMIT);
                SUM_V();
                PV(false);
            }
            if (ONE) bsync<B_O2, 256>(); else { barrive<B_O2, 256>(); bsync<B_O, 128>(); }
            PROF(6);
            float i0 = sm[0], i1 = sm[1];
            #define GET_P() if (!ONE) bsync<B_PT, 160>(); lds128u(p, PT + l16); p[4] = lds32(PT + 512 + (l16 >> 2))
            #define TOK_PV() { const uint32_t z = t16 >> 17; one[0] = ONES | z; one[1] = ONES ^ z; one[2] = ONES + z; one[3] = ONES - z; } \
                _Pragma("unroll") for (int i = 0; i < 12; i++) ot[i >> 2][0][i & 3] = ot[i >> 2][1][i & 3] = 0.f; \
                mma8(ot[0][0], vs[0], vs[1], p[4]); mma8(ot[1][0], vs[2], vs[3], p[4]); mma8(ot[2][0], one[0], one[1], p[4]); \
                mmaq(ot[0][1], vf + 4, p[2], p[3]); mmaq(ot[1][1], vf + 12, p[2], p[3]); mmaq(ot[2][1], one, p[2], p[3]); CUT(pa)
            WO_MMA(WA2, WA3, GET_P(), TOK_PV());
            CUT(pa);
            mmaq(ot[0][0], vf, p[0], p[1]); mmaq(ot[1][0], vf + 8, p[0], p[1]); mmaq(ot[2][0], one, p[0], p[1]);
            CUT(pb);
            barrive<B_GO, 256>();
        }
        CUT(pb);
        PROF(7);
        #define PK_O() const float j0 = rcpf(ot[2][0][0] + ot[2][1][0]), j1 = rcpf(ot[2][0][1] + ot[2][1][1]); uint32_t ow[4]; \
            _Pragma("unroll") for (int i = 0; i < 4; i++) \
                ow[i] = opq(pack2((ot[i >> 1][0][2 * (i & 1)] + ot[i >> 1][1][2 * (i & 1)]) * j0, (ot[i >> 1][0][2 * (i & 1) + 1] + ot[i >> 1][1][2 * (i & 1) + 1]) * j1))
        #define ST_O() do { uint32_t* og = (uint32_t*)((char*)g_O + (u_og + (l16 >> 2))); \
            _Pragma("unroll") for (int i = 0; i < 4; i++) og[(i >> 1) * 256 + (i & 1) * 32] = ow[i]; } while (0)
        #define BSO() ((u_bs) ^ ((l16 & 0x10) + ((l16 >> 3) & 0xC) + (l16 & 0x80) * 0x20 + (l16 & 0x100) * 0x80))
        const uint32_t taus = phase(seg);
        const uint64_t* const dq = c_xd + (s & 1) * 32; const uint64_t* const dv = dq + (wg * 16 | (prm.zero & s));
        float acc[16], acv[16];
        uint32_t u[8];
        if constexpr (wg == 0) {
            if (s == NSEG - 1) { bsync<B_GO, 256>(); st_g32(at(BSO(), rbhi), 0); mbar_wait(MB_KV, kc & 1); break; }
            load_frag<16 - EV, 16, 2048>(VEB + t16, T);
            bsync<B_GO, 256>();
            PROF(8);
            wg_run<0, 16 - EV>(acv, T, dv);
            wg_run<16 - EV, 16>(acv, T, dv);
            wg_run<0, 5>(acc, W, dq); wg_wait<1>();
            qk_pack(acv, u);
            #pragma unroll
            for (int i = 0; i < 8; i++) u[i] = opq(u[i]);
            CUT(pa);
            wg_run<5, 8>(acc, W, dq);
            __syncwarp();
            sts128(SC + opq(t16), make_uint4(u[0], u[1], u[2], u[3])); sts128(SC + 2048 + opq(t16), make_uint4(u[4], u[5], u[6], u[7]));
            barrive<B_VX, 256>();
            __syncwarp();
            PROF(9);
            wg_run<8, 12>(acc, W, dq);
            CUT(pa);
            char* const bs = at(opq(BSO()), opq(rbhi));
            CUT(pa);
            wg_run<12, 15>(acc, W, dq);
            CUT(pa);
            const uint32_t ro = opq(l16 * 8 + ((l16 & 0x70) ^ ((w8 & 3) << 5))), ro2 = opq(ro ^ 0x10);
            const uint32_t mG = opq((l16 & 0x1C0) ? 0 : 0x10001u), mB = opq((((l16 >> 2) & 4) + ((l16 >> 5) & 3)) == ((u_bs >> 7) & 7) ? 1 : 0), zz = t16 >> 18;
            CUT(pa);
            wg_run<15, 18>(acc, W, dq);
            CUT(pa);
            const uint32_t one[4] = {opq(ONES | zz), opq(ONES ^ zz), opq(ONES + zz), opq(ONES - zz)};
            const uint32_t par = s & 1, tt = tau * 0x10001u;
            CUT(pa);
            wg_run<18, RP>(acc, W, dq);
            CUT(pa);
            PROF(10);
            mbar_wait(MB_R, par);
            PROF(14);
            uint32_t x[8], bad;
            float d[4][4];
            #define SUM_R() do { ldsm4t(x[0], x[1], x[2], x[3], RS + ro); ldsm4t(x[4], x[5], x[6], x[7], RS + ro2); \
                _Pragma("unroll") for (int i = 0; i < 4; i++) { d[i][0] = d[i][1] = d[i][2] = d[i][3] = 0.f; mmaq(d[i], one, x[2 * i], x[2 * i + 1]); } } while (0)
            #define PUT_B() do { bad = late(stale<2, 1>(x, tt), stale<2, 1>(x + 2, tt), mG); \
                const uint32_t w0 = pack2(d[0][0] + d[1][0], d[0][1] + d[1][1]), w1 = pack2(d[2][0] + d[3][0], d[2][1] + d[3][1]); \
                asm volatile("{ .reg .pred p; setp.eq.b32 p, %2, 0; @p st.relaxed.gpu.global.u32 [%0], %1; }" :: "l"(bs), "r"(tagm((l16 & 0x40) ? w1 : w0, mB, tt)), "r"(bad) : "memory"); } while (0)
            SUM_R();
            CUT(pa);
            wg_run<RP, (RP + RQ < 32 ? RP + RQ : 32)>(acc, W, dq);
            if (RP + RQ >= RL) barrive<B_BT, 256>();
            CUT(pa);
            PUT_B();
            const uint32_t tb = lds32(SUM + 272 + 28 + zz);
            CUT(pa);
            PROF(11);
            if (RP + RQ < RL) { wg_run<RP + RQ, RL>(acc, W, dq); __syncwarp(); barrive<B_BT, 256>(); __syncwarp(); }
            wg_run<(RP + RQ < RL ? RL : RP + RQ), 32>(acc, W, dq);
            CUT(pa);
            AGAIN(5, ld_g128(x, at(u_rl + opq(ro), rbhi)); ld_g128(x + 4, at(u_rl + opq(ro2), rbhi)); sts128(RS + ro, make_uint4(x[0], x[1], x[2], x[3])); sts128(RS + ro2, make_uint4(x[4], x[5], x[6], x[7]));
                     CUT(pa); __syncwarp(); SUM_R(); PUT_B(), bad)
            uint32_t badkv = 0;
            if (w8 == 3) {
                TRC(13, gtime() - tb);
                wait_g(tb, t16);
                GET_B(0);
                PROFW(13, 3);
            } else { mbar_wait(MB_KV, kc & 1); badkv = kv_stale(w8, l16, phase(s + 1)); }
            const uint32_t ps = opq(pb & 0xFFFF), ps2 = opq(ps ^ HI8);
            char* const qd0 = TOK_DST() + ps; char* const qd1 = TOK_DST() + ps2;
            wg_wait<0>();
            pack_tag(acc, u, taus, TAGW);
            #pragma unroll
            for (int i = 0; i < 8; i++) u[i] = opq(u[i]);
            CUT(pa);
            badkv = any128<B_S0>(badkv);
            st_if(seg < NSEG, qd0, u); st_if(seg < NSEG, qd1, u + 4);
            AGAIN(0, kc++; if (w8 == 0) get_kv(c, s + 1); mbar_wait(MB_KV, kc & 1); badkv = any128<B_S0>(w8 < 3 ? kv_stale(w8, l16, phase(s + 1)) : 0), late(badkv, 0, 1))
            kc++;
            if (XP == 1) load_x(tmX, c, seg + 1, (s & 1) ? XT : XT2, w8 == 1 && seg + 1 < NSEG);
            PROF(12);
        } else {
            #define LAST() __reduce_max_sync(~0u, max(max(an[0], an[1]), max(an[2], an[3])))
            PK_O();
            CUT(pa);
            if (s == NSEG - 1) { ST_O(); break; }
            PROF(8);
            if (w8 != 7) load_frag<16 - EV, 16 - EV + TA0, 2048>(VEB + t16, T);
            else {
                uint32_t tr = LAST();
                AGAIN(8, ld_g128(an, at(u_ta + l16, rbhi)); tr = LAST(), late(stale<2, 1>(an, s), stale<2, 1>(an + 2, s), 31))
                tr = (tr & ~31u) + P(0);
                TRC(14, gtime() - tr);
                wait_g(tr, t16);
                if (R4) { for (int i = 0; i < 4; i++) bulk_copy(RS + i * 1024, at(u_rl + i * 1024, rbhi), 1024, MB_R); }
                else bulk_copy(RS, at(u_rl, rbhi), 4096, MB_R);
                PROFW(14, 3);
                if (XP == 3) load_x(tmX, c, seg + 1, (s & 1) ? XT : XT2, seg + 1 < NSEG);
                sts32(SUM + 272 + 28, tr + P(1));
                load_frag<16 - EV, 16 - EV + TA0, 2048>(VEB + t16, T);
            }
            CUT(pa);
            bsync<B_VX, 256>();
            lds128u(u, SC - 2048 + opq(t16)); lds128u(u + 4, SC + opq(t16));
            CUT(pa);
            ST_O();
            CUT(pa);
            load_frag<16 - EV + TA0, 16 - EV + TA, 2048>(VEB + t16, T);
            acc_init(acv, u);
            #pragma unroll
            for (int i = 0; i < 16; i++) acv[i] = opqf(acv[i]);
            const uint32_t ps = opq(pb & 0xFFFF), ps2 = opq(ps ^ HI8);
            CUT(pa);
            PROF(9);
            bsync<B_BT, 256>();
            CUT(pa);
            wg_run<0, 3>(acc, W, dq);
            PROF(11);
            wg_run<3, NT, true>(acc, W, dq);
            __syncwarp();
            load_frag<16 - EV + TA, 16, 2048>(VEB + t16, T);
            __syncwarp();
            wg_run<NT, NB>(acc, W, dq);
            char* const qd0 = TOK_DST() + ps; char* const qd1 = TOK_DST() + ps2;
            wg_run<NB, 32>(acc, W, dq);
            wg_run<0, 5, true>(acv, T, dv);
            wg_wait<1>();
            PROF(12);
            pack_tag(acc, u, taus, TAGW);
            #pragma unroll
            for (int i = 0; i < 8; i++) u[i] = opq(u[i]);
            CUT(pa);
            wg_run<5, 16 - EV>(acv, T, dv);
            __syncwarp();
            st_if(seg < NSEG, qd0, u); st_if(seg < NSEG, qd1, u + 4);
            __syncwarp();
            wg_run<16 - EV, 16>(acv, T, dv);
            CUT(pa);
            PROF(10);
            wg_wait<0>();
            PROF(13);
            pack_tag(acv, u, taus, TAGW);
            if (XP == 2) load_x(tmX, c, seg + 1, (s & 1) ? XT : XT2, w8 == 5 && seg + 1 < NSEG);
            st_if(seg < NSEG, qd0 + 16384, u); st_if(seg < NSEG, qd1 + 16384, u + 4);
        }
        s++;
        u_rs ^= 1 << 20; u_rl ^= 1 << 20; u_bs ^= 1 << 20; u_bl ^= 1 << 20; u_x ^= 1 << 20; u_xs ^= 1 << 20; u_ta ^= 1 << 20; u_rp ^= 1 << 20; u_og += 262144;
    }
}

__device__ __forceinline__ uint32_t round_trips(char* line, int n) {
    uint32_t best[2] = {0xFFFFu, 0xFFFFu};
    #pragma unroll 1
    for (int i = 0; i < n; i++) {
        uint32_t v; const uint32_t t0 = clk();
        asm volatile("atom.relaxed.gpu.global.exch.b32 %0, [%1], %2;" : "=r"(v) : "l"(line + (i & 1) * 4096), "r"(i) : "memory");
        if (v == 0x7FC1A5A5u) g_err = 2;
        const uint32_t dt = clk() - t0;
        if (i & 1) best[1] = min(best[1], dt); else best[0] = min(best[0], dt);
    }
    return (__popc((uint32_t)(uintptr_t)line & HOME_BITS) & 1) ? best[1] | best[0] << 16 : best[0] | best[1] << 16;
}
__device__ __forceinline__ int role(char* rb) {
    const int b = blockIdx.x, t = threadIdx.x;
    if (!(t & 31)) { const int i = b * 8 + (t >> 5); sts32(mk::SUM + (t >> 3), round_trips(rb + RB_P + (i & 31) * 128 + (i >> 5) * 8192, NPR)); }
    __syncthreads();
    if (t == 0) {
        const uint4 x = lds128(mk::SUM), y = lds128(mk::SUM + 16);
        const uint32_t m = __vminu2(__vminu2(__vminu2(x.x, x.y), __vminu2(x.z, x.w)), __vminu2(__vminu2(y.x, y.y), __vminu2(y.z, y.w)));
        uint32_t sm; asm volatile("mov.u32 %0, %%smid;" : "=r"(sm));
        const uint32_t g = sm < 64 ? (sm & 15) >> 1 : 1 + (sm - 64) % 14 / 2, i = sm < 64 ? sm >> 4 : 4 + (sm - 64) / 14;
        const uint32_t pos = sm < 120 ? g * 16 + i * 2 + (sm & 1) : sm + 8;
        st_g32(g_cls + b, 0x80000000u | (m >> 16 < (m & 0xFFFF)) << 24 | pos << 8 | b);
    }
    uint32_t e = ~0u, own;
    int n = 0;
    do { own = ld_g32(g_cls + b); if (t < NCTA) e = ld_g32(g_cls + t); } while (!((e & own) >> 31) && ++n < SPIN_LIMIT);
    const int below = __syncthreads_count(e < own), n0 = __syncthreads_count(!(e >> 24 & 1));
    const int c0 = 4 * min(max(16, 32 - (NCTA - n0) / 4), n0 / 4);
    return below < c0 ? below : below < n0 ? 128 + below - c0 : below - n0 + c0 < 128 ? below - n0 + c0 : below;
}

__global__ void __launch_bounds__(256, 1)
main_kernel(const __grid_constant__ CUtensorMap tmWq, const __grid_constant__ CUtensorMap tmWk, const __grid_constant__ CUtensorMap tmWv,
            const __grid_constant__ CUtensorMap tmWo, const __grid_constant__ CUtensorMap tmX, const bf16* __restrict__ mem0,
            const bf16* Wo, const __grid_constant__ MainParams prm) {
    using namespace mk;
    extern __shared__ __align__(1024) uint8_t smem_raw[];
    if (smem_u32(smem_raw) != SB) __trap();
    TL(2);
    const int tid0 = threadIdx.x, w8 = __shfl_sync(~0u, tid0 >> 5, 0), wg = w8 >> 2;
    asm volatile("griddepcontrol.wait;" ::: "memory");
    const int c = __shfl_sync(~0u, role(prm.rb), 0), kap = c & 1;
    if (c >= 128) return;
    if (tid0 == 0) {
        for (int i = 0; i < 8; i++) mbar_init(BAR + i * 8, 1);
        sts32(SUM + 256, 0); sts32(SUM + 268, 0); mbar_arrive(MB_B);
        asm volatile("fence.mbarrier_init.release.cluster;" ::: "memory");
        asm volatile("fence.proxy.async.shared::cta;" ::: "memory");
        const int col = (c >> 1) * 64, k0 = kap * 512;
        mbar_expect(MB_WQ, 65536); tma2d(WO, &tmWq, col, k0, MB_WQ); tma2d(WO + 32768, &tmWq, col, k0 + 256, MB_WQ);
        mbar_expect(MB_WK, 65536); tma2d(WV, &tmWk, col, k0, MB_WK); tma2d(WV + 32768, &tmWk, col, k0 + 256, MB_WK);
    }
    __syncwarp();
    load_x(&tmX, c, 0, XT, w8 == 0);
    for (int i = tid0; i < 4096; i += 256) {
        const int row = i >> 9, col = i & 511;
        const unsigned short v = __bfloat16_as_ushort(mem0[row * DM + kap * 512 + col]);
        asm volatile("st.shared.u16 [%0], %1;" :: "r"(MEM + col * 16 + row * 2), "h"(v) : "memory");
    }
    asm volatile("fence.proxy.async.shared::cta;" ::: "memory");
    __syncthreads();
    uint32_t W[128], T[64];
    mbar_wait(wg ? MB_WK : MB_WQ, 0);
    load_tile<0, 32>(tile_off(tid0 & 31, 2 * (w8 & 3)) + (wg ? WV : WO), W);
    __syncthreads();
    if (tid0 == 0) {
        mbar_expect(MB_WV, 65536); tma2d(WV, &tmWv, (c >> 1) * 64, kap * 512, MB_WV); tma2d(WV + 32768, &tmWv, (c >> 1) * 64, kap * 512 + 256, MB_WV);
        mbar_expect(MB_WO, 65536);
        for (int i = 0; i < 4; i++) tma2d(WO + i * 16384, &tmWo, (c & 3) * 256 + i * 64, (c >> 2) * DH, MB_WO);
    }
    asm volatile("griddepcontrol.launch_dependents;" ::: "memory");
    uint32_t t16 = tid0 * 16, pa, pb;
    {
        const int lane = tid0 & 31, w = w8 & 3, g = lane >> 2, t = lane & 3;
        auto vec = [](int hf, int gg, int ch) { return hf * 512 + (gg >> 1) * 128 + (gg & 1) * 64 + ((ch ^ (gg >> 1) ^ (hf << 1)) << 4); };
        const int kg = ((lane >> 3) & 1) * 4 + ((lane & 7) >> 1);
        pa = wg ? w * 1024 + vec((lane >> 3) & 1, lane & 7, lane >> 4)
                : ((lane >> 4) * 4096 + w * 1024 + vec(lane & 1, kg, 2 * (w & 1))) | ((lane & 8) * 256 + w * 256 + (lane & 1) * 128 + ((((lane >> 4) ^ (lane & 1)) * 4 + ((lane & 7) >> 1)) << 4)) << 16;
        pb = (wg ? w * 1024 + vec(0, g, t) : t * 4096 + w * 256 + g * 16) | (w * 256 + t * 64 + (g & 3) * 8 + (g >> 2) * 4) << 16;
    }
    mbar_wait(MB_WV, 0);
    load_tile<0, 16>(tile_off(tid0 & 31, 2 * (w8 & 3)) + wg * 32768 + WV, T);
    __syncthreads();
    #pragma unroll
    for (int i = 0; i < 16; i++) sts128(WV + i * 4096 + t16, make_uint4(T[4 * i], T[4 * i + 1], T[4 * i + 2], T[4 * i + 3]));
    int budget = SPIN_LIMIT;
    #pragma unroll 1
    for (int seg = 0; seg < 2; seg++) {
        const uint32_t tau = phase(seg), ps = pb & 0xFFFF;
        float acc[16], acv[16];
        uint32_t u[8];
        mbar_wait(MB_X, seg & 1);
        wg_run<0, 32>(acc, W, c_xd + (prm.zero & seg));
        wg_run<0, 16>(acv, T, c_xd + (wg * 16 | (prm.zero & (seg + 1))));
        wg_wait<0>();
        if (!wg) { qk_pack(acv, u); sts128(SC + t16, make_uint4(u[0], u[1], u[2], u[3])); sts128(SC + 2048 + t16, make_uint4(u[4], u[5], u[6], u[7])); }
        __syncthreads();
        load_x(&tmX, c, seg + 1, XT, w8 == 0);
        if (wg) { lds128u(u, SC - 2048 + t16); lds128u(u + 4, SC + t16); acc_add(acv, u); }
        #pragma unroll 1
        for (int m = 0; m <= wg; m++) {
            pack_tag(acc, u, tau, TAGW);
            st_if(true, tok_dst(c, seg, wg) + (m * 16384 + ps), u); st_if(true, tok_dst(c, seg, wg) + (m * 16384 + (ps ^ HI8)), u + 4);
            #pragma unroll
            for (int i = 0; i < 16; i++) acc[i] = acv[i];
        }
        __syncthreads();
    }
    {
        mbar_wait(MB_WO, 0);
        const int lane = tid0 & 31;
        const uint32_t a = (tid0 >> 6) * 16384 + tile_off(lane, (w8 & 1) * 4) + WO;
        #pragma unroll
        for (int i = 0; i < 16; i++) ldsm4t(T[4 * i], T[4 * i + 1], T[4 * i + 2], T[4 * i + 3], ((i & 2) ? a ^ 32 : a) + ((i >> 2) + 4 * (i & 1)) * 2048);
        __syncthreads();
        const uint32_t d = WO + w8 * 512 + ((lane >> 3) * 4 + (lane & 3)) * 16 + ((lane >> 2) & 1) * 4;
        #pragma unroll
        for (int i = 0; i < 64; i++) sts32(d + (i >> 2) * 4096 + (i & 1) * 256 + (i & 2) * 4, T[i]);
        load_frag<0, 16>(WV + t16, T);
    }
    uint32_t u_rs, u_rl, u_bs, u_bl;
    const uint32_t rbhi = (uint32_t)((uintptr_t)prm.rb >> 32);
    {
        const int lane = tid0 & 31, h = c >> 2, j = c & 3;
        uint32_t cl;
        const int G = h >> 4, rk = h & 15;
        auto half = [&](uint32_t off) { return (uint32_t)(uintptr_t)prm.rb + off + ((__popc(off & HOME_BITS) ^ G) & 1) * 4096; };
        auto rpair = [&](int m) { return RB_R + (j << 16) + ((m & 1) << 13) + (((m >> 1) & 3) << 14) + ((m >> 3) << 18); };
        u_rs = (half(rpair(2 * w8)) ^ (G << 12)) + h * 128 + (h & 7) * 16;
        u_rl = half(rpair(rk));
        u_bs = (uint32_t)(uintptr_t)prm.rb + RB_B + ((j & 1) << 13) + ((j >> 1) << 16) + rk * 256 + G * 128 + (w8 & 3) * 32;
        u_bl = half(RB_B + (kap << 16));
        if (w8 == 0) {
            const char* v0 = kv_src(c, 0) + 16384 + lane * 128 + (lane & 3) * 4;
            do cl = ld_g32(v0) & ld_g32(v0 + 4096) & ld_g32(v0 + 8192) & ld_g32(v0 + 12288); while (__any_sync(~0u, !(cl & 1)) && --budget > 0);
        }
    }
    int kc = 0;
    do {
        if (w8 == 0) get_kv(c, 0);
        mbar_wait(MB_KV, kc++ & 1);
    } while (__syncthreads_or(w8 < 3 && kv_stale(w8, t16 & 0x1F0, 1)) && kc < SPIN_LIMIT);
    kc = __shfl_sync(~0u, kc, 0);
    asm volatile("fence.proxy.async.shared::cta;" ::: "memory");
    TLX(7);
    __syncwarp();
    const Ctx cx = {u_rs, u_rl, u_bs, u_bl, (uint32_t)(uintptr_t)prm.rb, rbhi, w8, c, kc};
    if (wg) steps<1>(W, T, t16, pa, pb, cx, &tmX, prm); else steps<0>(W, T, t16, pa, pb, cx, &tmX, prm);
    TLX(3);
}

namespace ck {
constexpr uint32_t U = 0;
constexpr uint32_t UPL = 136 * 16 + 64;
constexpr uint32_t UCH = 2 * UPL;
constexpr uint32_t F = 8 * UCH;
constexpr uint32_t FCP = 4160;
constexpr uint32_t FCH = 2 * FCP;
constexpr uint32_t SK = F + 8 * FCH;
constexpr uint32_t SKP = 257 * 16;
constexpr uint32_t SV = SK + 8 * SKP;
constexpr uint32_t SQ = SV + 32768;
constexpr uint32_t TOTAL = SQ + 32768;
}
__global__ void __launch_bounds__(288, 1)
conv_kernel(const bf16* __restrict__ q, const bf16* __restrict__ k, const bf16* __restrict__ v, const bf16* __restrict__ shift_k,
            const bf16* __restrict__ ssm_k, const bf16* __restrict__ ssm_D, const bf16* __restrict__ gate_w,
            const bf16* Wq, const bf16* Wk, const bf16* Wv, const bf16* Wo,
            const __grid_constant__ CUtensorMap tmWq, const __grid_constant__ CUtensorMap tmWk, const __grid_constant__ CUtensorMap tmWv,
            const __grid_constant__ CUtensorMap tmWo, char* rb) {
    using namespace ck;
    extern __shared__ uint8_t smem_raw[];
    const uint32_t sb = smem_u32(smem_raw);
    const int tid = threadIdx.x, w = tid >> 5, lane = tid & 31, c = blockIdx.x;
    TL(0);
    const int d0 = c * 8, t0 = tid * 8;
    if (w == 8) {
        bsync<1, 288>();
        if (lane < 10) {
            const CUtensorMap* m = lane < 2 ? &tmWq : lane < 4 ? &tmWk : lane < 6 ? &tmWv : &tmWo;
            const int c0 = lane < 6 ? (c >> 1) * 64 : (c & 3) * 256 + (lane - 6) * 64, c1 = lane < 6 ? (c & 1) * 512 + (lane & 1) * 256 : (c >> 2) * DH;
            asm volatile("cp.async.bulk.prefetch.tensor.2d.L2.global [%0, {%1, %2}];" :: "l"(m), "r"(c0), "r"(c1) : "memory");
        }
        return;
    }
    #pragma unroll
    for (int i = 0; i < 8; i++) {
        cpa16(sb + SK + i * SKP + (tid + 1) * 16, k + (size_t)(t0 + i) * DM + d0);
        cpa16(sb + SV + i * 4096 + tid * 16, v + (size_t)(t0 + i) * DM + d0);
    }
    cpa_commit();
    #pragma unroll
    for (int i = 0; i < 8; i++) cpa16(sb + SQ + i * 4096 + tid * 16, q + (size_t)(t0 + i) * DM + d0);
    cpa_commit();
    uint4 fx[8], gw[4], x0[4], x1[4], skr[4];
    const uint4* fp = (const uint4*)(ssm_k + (size_t)(d0 + w) * SEQ);
    #pragma unroll
    for (int i = 0; i < 8; i++) fx[i] = fp[lane + 32 * i];
    const int gr = c * 16 + w * 2;
    #pragma unroll
    for (int i = 0; i < 4; i++) {
        gw[i] = ((const uint4*)gate_w)[lane + 32 * i];
        x0[i] = ((const uint4*)(q + (size_t)gr * DM))[lane + 32 * i];
        x1[i] = ((const uint4*)(q + (size_t)(gr + 1) * DM))[lane + 32 * i];
        skr[i] = ((const uint4*)(shift_k + d0 * 4))[i];
    }
    if (c == 0 && tid < 160) g_cls[tid] = 0;
    if (tid < 128) sts128(sb + U + (tid >> 4) * UCH + ((tid >> 3) & 1) * UPL + (tid & 7) * 16, make_uint4(0, 0, 0, 0));
    else if (tid < 136) sts128(sb + SK + (tid & 7) * SKP, make_uint4(0, 0, 0, 0));
    {
        const uint32_t fb = sb + F + w * FCH;
        if (lane < 8) { sts32(fb + 4128 + lane * 4, 0); if (lane) sts32(fb + FCP + 4128 + lane * 4, 0); }
        #pragma unroll
        for (int i = 0; i < 8; i++) {
            const int vi = lane + 32 * i;
            const uint4 x = fx[i];
            const uint32_t a = __shfl_down_sync(~0u, x.x, 1), b = __shfl_sync(~0u, i < 7 ? fx[i < 7 ? i + 1 : 7].x : 0u, 0);
            const uint32_t nxt = lane == 31 ? b : a;
            const uint32_t ea = fb + (2056 - 8 * vi) * 2;
            sts128(ea, make_uint4(__byte_perm(x.w, 0, 0x1032), __byte_perm(x.z, 0, 0x1032), __byte_perm(x.y, 0, 0x1032), __byte_perm(x.x, 0, 0x1032)));
            sts128(ea + FCP, make_uint4(__byte_perm(nxt, x.w, 0x7610), __byte_perm(x.w, x.z, 0x7610), __byte_perm(x.z, x.y, 0x7610), __byte_perm(x.y, x.x, 0x7610)));
            if (vi == 0) sts32(fb + FCP + 4128, x.x & 0xFFFFu);
        }
    }
    {
        float a0 = 0.f, a1 = 0.f;
        #pragma unroll
        for (int i = 0; i < 16; i++) {
            const uint32_t gg = ((const uint32_t*)gw)[i], u0 = ((const uint32_t*)x0)[i], u1 = ((const uint32_t*)x1)[i];
            a0 = fmaf(bflo(u0), bflo(gg), fmaf(bfhi(u0), bfhi(gg), a0));
            a1 = fmaf(bflo(u1), bflo(gg), fmaf(bfhi(u1), bfhi(gg), a1));
        }
        #pragma unroll
        for (int o = 16; o; o >>= 1) { a0 += __shfl_xor_sync(~0u, a0, o); a1 += __shfl_xor_sync(~0u, a1, o); }
        if (lane < 2) g_gate[gr + lane] = 1.f / (1.f + __expf(lane ? -a1 : -a0));
    }
    cpa_wait();
    bsync<1, 288>();
    TLX(14);
    const uint4 dd = *(const uint4*)(ssm_D + d0);
    {
        uint4 kr[11], vr[8];
        #pragma unroll
        for (int i = 0; i < 11; i++) kr[i] = lds128(sb + SK + ((i + 5) & 7) * SKP + (tid + (i >= 3)) * 16);
        #pragma unroll
        for (int i = 0; i < 8; i++) vr[i] = lds128(sb + SV + i * 4096 + tid * 16);
        #pragma unroll
        for (int ch = 0; ch < 8; ch++) {
            const uint32_t s01 = ((const uint32_t*)skr)[2 * ch], s23 = ((const uint32_t*)skr)[2 * ch + 1];
            const float sk[4] = {bflo(s01), bfhi(s01), bflo(s23), bfhi(s23)};
            float kf[11], kv[8];
            #pragma unroll
            for (int i = 0; i < 11; i++) { const uint32_t wd = ((const uint32_t*)&kr[i])[ch >> 1]; kf[i] = (ch & 1) ? bfhi(wd) : bflo(wd); }
            #pragma unroll
            for (int i = 0; i < 8; i++) {
                const uint32_t wv = ((const uint32_t*)&vr[i])[ch >> 1];
                kv[i] = fmaf(kf[i + 3], sk[0], fmaf(kf[i + 2], sk[1], fmaf(kf[i + 1], sk[2], kf[i] * sk[3]))) * ((ch & 1) ? bfhi(wv) : bflo(wv));
            }
            sts128(sb + U + ch * UCH + (tid & 1) * UPL + (8 + (tid >> 1)) * 16,
                   make_uint4(pack2(kv[0], kv[1]), pack2(kv[2], kv[3]), pack2(kv[4], kv[5]), pack2(kv[6], kv[7])));
        }
    }
    bsync<2, 256>();
    TL(9);
    {
        const int g = lane >> 2, t = lane & 3;
        float acc[16][4];
        #pragma unroll
        for (int i = 0; i < 16; i++) acc[i][0] = acc[i][1] = acc[i][2] = acc[i][3] = 0.f;
        const uint32_t fa = sb + F + w * FCH + ((g & 1) ? (2063 - g + 2 * t) * 2 : FCP + (2064 - g + 2 * t) * 2);
        const uint32_t ua = sb + U + w * UCH + ((lane >> 3) & 1) * UPL + (8 + (lane >> 4) * 8 + (lane & 7)) * 16;
        #pragma unroll 1
        for (int r = 0; r < 8; r++) {
            uint32_t Fr[32];
            #pragma unroll
            for (int m = 0; m < 8; m++) ldsm4(Fr[4 * m], Fr[4 * m + 1], Fr[4 * m + 2], Fr[4 * m + 3], ua - r * 16 + m * 256);
            #pragma unroll
            for (int qq = 0; qq < 16; qq++) {
                const uint32_t o = fa - r * 32 - qq * 256;
                const uint32_t f0 = lds32(o), fp8 = lds32(o - 16), fm8 = lds32(o + 16);
                #pragma unroll
                for (int nt = qq; nt < 16; nt++) mma16(acc[nt], f0, fp8, fm8, f0, Fr[2 * (nt - qq)], Fr[2 * (nt - qq) + 1]);
            }
        }
        __syncwarp();
        const uint32_t ya = sb + F + w * FCH + ((lane >> 3) & 1) * 2048 + ((lane >> 4) * 8 + (lane & 7)) * 16;
        #pragma unroll
        for (int nt = 0; nt < 16; nt += 2)
            stsm4t(ya + nt * 128, pack2(acc[nt][0], acc[nt][1]), pack2(acc[nt][2], acc[nt][3]), pack2(acc[nt + 1][0], acc[nt + 1][1]), pack2(acc[nt + 1][2], acc[nt + 1][3]));
    }
    TL(11);
    bsync<2, 256>();
    {
        uint32_t outw[8][4];
        uint4 qr[8];
        #pragma unroll
        for (int i = 0; i < 8; i++) qr[i] = lds128(sb + SQ + i * 4096 + tid * 16);
        #pragma unroll
        for (int cp = 0; cp < 4; cp++) {
            const uint4 y0 = lds128(sb + F + (2 * cp) * FCH + (tid & 1) * 2048 + (tid >> 1) * 16), y1 = lds128(sb + F + (2 * cp + 1) * FCH + (tid & 1) * 2048 + (tid >> 1) * 16);
            const uint4 u0 = lds128(sb + U + (2 * cp) * UCH + (tid & 1) * UPL + (8 + (tid >> 1)) * 16), u1 = lds128(sb + U + (2 * cp + 1) * UCH + (tid & 1) * UPL + (8 + (tid >> 1)) * 16);
            const uint32_t dw = ((const uint32_t*)&dd)[cp];
            const float D0 = bflo(dw), D1 = bfhi(dw);
            #pragma unroll
            for (int i = 0; i < 8; i++) {
                const uint32_t a0 = ((const uint32_t*)&y0)[i >> 1], a1 = ((const uint32_t*)&y1)[i >> 1], b0 = ((const uint32_t*)&u0)[i >> 1], b1 = ((const uint32_t*)&u1)[i >> 1];
                const float yy0 = fmaf((i & 1) ? bfhi(b0) : bflo(b0), D0, (i & 1) ? bfhi(a0) : bflo(a0));
                const float yy1 = fmaf((i & 1) ? bfhi(b1) : bflo(b1), D1, (i & 1) ? bfhi(a1) : bflo(a1));
                const uint32_t qw = ((const uint32_t*)&qr[i])[cp];
                outw[i][cp] = pack2(bflo(qw) * yy0, bfhi(qw) * yy1);
            }
        }
        #pragma unroll
        for (int i = 0; i < 8; i++) g_A[c * 2048 + i * 256 + tid] = make_uint4(outw[i][0], outw[i][1], outw[i][2], outw[i][3]);
    }
    TL(1);
}

namespace ok {
constexpr int STAGES = 4;
constexpr uint32_t STG = 49152, TOTAL = STAGES * STG + 32768 + 256;
}
#define R8(o) F4(d, o), F4(d, o + 4)
__device__ __forceinline__ void wgmma_n256_ss_tt(float* d, uint64_t da, uint64_t db, int accum) {
    asm volatile("{.reg .pred p; setp.ne.b32 p, %130, 0;\n"
        "wgmma.mma_async.sync.aligned.m64n256k16.f32.bf16.bf16 {%0,%1,%2,%3,%4,%5,%6,%7,%8,%9,%10,%11,%12,%13,%14,%15,"
        "%16,%17,%18,%19,%20,%21,%22,%23,%24,%25,%26,%27,%28,%29,%30,%31,%32,%33,%34,%35,%36,%37,%38,%39,%40,%41,%42,%43,%44,%45,%46,%47,"
        "%48,%49,%50,%51,%52,%53,%54,%55,%56,%57,%58,%59,%60,%61,%62,%63,%64,%65,%66,%67,%68,%69,%70,%71,%72,%73,%74,%75,%76,%77,%78,%79,"
        "%80,%81,%82,%83,%84,%85,%86,%87,%88,%89,%90,%91,%92,%93,%94,%95,%96,%97,%98,%99,%100,%101,%102,%103,%104,%105,%106,%107,%108,%109,%110,%111,"
        "%112,%113,%114,%115,%116,%117,%118,%119,%120,%121,%122,%123,%124,%125,%126,%127}, %128, %129, p, 1, 1, 1, 1;}"
        : R8(0), R8(8), R8(16), R8(24), R8(32), R8(40), R8(48), R8(56), R8(64), R8(72), R8(80), R8(88), R8(96), R8(104), R8(112), R8(120)
        : "l"(da), "l"(db), "r"(accum));
}
#undef R8
__global__ void __cluster_dims__(2, 1, 1) __launch_bounds__(288, 1)
out_kernel(const __grid_constant__ CUtensorMap tmO, const __grid_constant__ CUtensorMap tmWo, const __grid_constant__ CUtensorMap tmA,
           const __grid_constant__ CUtensorMap tmOut, const __grid_constant__ MainParams prm) {
    using namespace ok;
    extern __shared__ __align__(1024) uint8_t smem_raw[];
    const uint32_t SB = smem_u32(smem_raw), AT = SB + STAGES * STG, BAR = AT + 32768;
    if (SB & 1023) __trap();
    const int tid = threadIdx.x, w = tid >> 5, lane = tid & 31;
    const int rank = blockIdx.x & 1, mt = blockIdx.x >> 3, nt = (blockIdx.x >> 1) & 3;
    const uint32_t full = BAR, empty = BAR + 64, afull = BAR + 128;
    if (tid == 0) {
        for (int i = 0; i < STAGES; i++) { mbar_init(full + i * 8, 1); mbar_init(empty + i * 8, 8); }
        mbar_init(afull, 1);
        asm volatile("fence.mbarrier_init.release.cluster;" ::: "memory");
    }
    __syncthreads();
    asm volatile("griddepcontrol.wait;" ::: "memory");
    TL(4);
    if (w == 8) {
        if (lane == 0) {
            int st = 0, ph = 1;
            for (int kb = 0; kb < 32; kb++) {
                if (kb >= STAGES) mbar_wait(empty + st * 8, ph);
                mbar_expect(full + st * 8, STG);
                tma3d(SB + st * STG, &tmO, 0, (rank * 32 + kb) * 2, mt * 16, full + st * 8);
                tma3d(SB + st * STG + 16384, &tmWo, 0, (rank * 32 + kb) * 64, nt * 4, full + st * 8);
                if (kb == STAGES - 1) { mbar_expect(afull, 32768); tma3d(AT, &tmA, mt * 128, 0, (nt * 2 + rank) * 16, afull); }
                if (++st == STAGES) { st = 0; ph ^= 1; }
            }
        }
        __syncwarp();
        asm volatile("barrier.cluster.arrive.aligned; barrier.cluster.wait.aligned;" ::: "memory");
        asm volatile("barrier.cluster.arrive.aligned; barrier.cluster.wait.aligned;" ::: "memory");
    } else {
        const int wg = w >> 2, g = lane >> 2;
        float acc[128];
        const int tok0 = 32 * (4 * mt + (w >> 1)) + 8 * (g >> 1) + 4 * (w & 1) + (g & 1);
        const float g0 = g_gate[tok0], g1 = g_gate[tok0 + 2];
        int st = 0, ph = 0, pst = 0;
        #pragma unroll 1
        for (int kb = 0; kb < 32; kb++) {
            mbar_wait(full + st * 8, ph);
            const uint64_t da = mkdesc(SB + st * STG + wg * 8192, 128, 1024, 0), db = mkdesc(SB + st * STG + 16384, 8192, 1024, 1);
            wg_fence();
            #pragma unroll
            for (int ks = 0; ks < 4; ks++) wgmma_n256_ss_tt(acc, da + ks * 16, db + ks * 128, (kb | ks) != 0);
            wg_commit();
            wg_wait<1>();
            if (kb > 0 && lane == 0) mbar_arrive(empty + pst * 8);
            pst = st;
            if (++st == STAGES) { st = 0; ph ^= 1; }
        }
        wg_wait<0>();
        TLX(12);
        asm volatile("barrier.cluster.arrive.aligned; barrier.cluster.wait.aligned;" ::: "memory");
        uint32_t peer;
        asm volatile("mapa.shared::cluster.u32 %0, %1, %2;" : "=r"(peer) : "r"(SB + 65536 + tid * 16), "r"(rank ^ 1));
        #define SND(e) pack2(rank ? acc[8 * i + (e)] : acc[64 + 8 * i + (e)], rank ? acc[8 * i + (e) + 1] : acc[65 + 8 * i + (e)])
        #pragma unroll
        for (int i = 0; i < 8; i++)
            asm volatile("st.shared::cluster.v4.b32 [%0], {%1,%2,%3,%4};" :: "r"(peer + i * 4096), "r"(SND(0)), "r"(SND(2)), "r"(SND(4)), "r"(SND(6)) : "memory");
        #undef SND
        asm volatile("barrier.cluster.arrive.aligned; barrier.cluster.wait.aligned;" ::: "memory");
        mbar_wait(afull, 0);
        const float h0 = 1.f - g0, h1 = 1.f - g1;
        const uint32_t la = AT + (lane >> 4) * 2048 + (4 * (w & 1) + 2 * ((lane >> 3) & 1) + (lane & 1)) * 256 + (4 * (w >> 1) + ((lane & 7) >> 1)) * 16;
        const uint32_t ra = SB + (w * 16 + (lane & 15)) * 128;
        #pragma unroll
        for (int i = 0; i < 8; i++) {
            const uint32_t a = ra + (i >> 2) * 16384 + ((((i & 3) * 2 + (lane >> 4)) ^ (lane & 7)) << 4);
            uint32_t r0, r1, r2, r3;
            ldsm4(r0, r1, r2, r3, la + i * 4096);
            const uint4 u = lds128(SB + 65536 + tid * 16 + i * 4096);
            float p[8];
            #pragma unroll
            for (int e = 0; e < 8; e++) { const uint32_t x = ((const uint32_t*)&u)[e >> 1]; p[e] = (rank ? acc[64 + 8 * i + e] : acc[8 * i + e]) + ((e & 1) ? bfhi(x) : bflo(x)); }
            stsm4(a, pack2(fmaf(g0, bflo(r0), h0 * p[0]), fmaf(g0, bfhi(r0), h0 * p[1])), pack2(fmaf(g1, bflo(r1), h1 * p[2]), fmaf(g1, bfhi(r1), h1 * p[3])),
                     pack2(fmaf(g0, bflo(r2), h0 * p[4]), fmaf(g0, bfhi(r2), h0 * p[5])), pack2(fmaf(g1, bflo(r3), h1 * p[6]), fmaf(g1, bfhi(r3), h1 * p[7])));
        }
        asm volatile("fence.proxy.async.shared::cta;" ::: "memory");
        bsync<1, 256>();
        if (tid == 0) {
            for (int hf = 0; hf < 2; hf++)
                asm volatile("cp.async.bulk.tensor.5d.global.shared::cta.bulk_group [%0, {%2, %3, %3, %3, %4}], [%1];"
                    :: "l"(&tmOut), "r"(SB + hf * 16384), "r"(nt * 256 + rank * 128 + hf * 64), "r"(0), "r"(mt * 4) : "memory");
            asm volatile("cp.async.bulk.commit_group;" ::: "memory");
            asm volatile("cp.async.bulk.wait_group 0;" ::: "memory");
        }
        TL(5);
    }
}

typedef CUresult (*EncodeFn)(CUtensorMap*, CUtensorMapDataType, cuuint32_t, void*, const cuuint64_t*, const cuuint64_t*, const cuuint32_t*,
                             const cuuint32_t*, CUtensorMapInterleave, CUtensorMapSwizzle, CUtensorMapL2promotion, CUtensorMapFloatOOBfill);
static void enc(EncodeFn fn, CUtensorMap* m, void* base, int rank, const cuuint64_t* dims, const cuuint64_t* strides, const cuuint32_t* box, CUtensorMapSwizzle sw) {
    cuuint32_t es[5] = {1, 1, 1, 1, 1};
    fn(m, CU_TENSOR_MAP_DATA_TYPE_BFLOAT16, rank, base, dims, strides, box, es, CU_TENSOR_MAP_INTERLEAVE_NONE, sw,
       CU_TENSOR_MAP_L2_PROMOTION_L2_128B, CU_TENSOR_MAP_FLOAT_OOB_FILL_NONE);
}
static MainParams h_prm = {{768, 512, 384, 0, 0, 0, 0, 0, 0, 0, 0, 0}, 0, nullptr};

extern "C" void kernel_launch(void* const* d_in, const int* in_sizes, int n_in, void* d_out, int out_size) {
    const bf16* q = (const bf16*)d_in[0];
    const bf16* k = (const bf16*)d_in[1];
    const bf16* v = (const bf16*)d_in[2];
    const bf16* shift_k = (const bf16*)d_in[3];
    const bf16* ssm_k = (const bf16*)d_in[4];
    const bf16* ssm_D = (const bf16*)d_in[5];
    const bf16* mem0 = (const bf16*)d_in[7];
    const bf16* gate_w = (const bf16*)d_in[13];

    static EncodeFn fn = nullptr;
    static void* pO = nullptr;
    static void* pA = nullptr;
    if (!fn) {
        cudaDriverEntryPointQueryResult qr;
        cudaGetDriverEntryPoint("cuTensorMapEncodeTiled", (void**)&fn, cudaEnableDefault, &qr);
        cudaGetSymbolAddress(&pO, g_O);
        cudaGetSymbolAddress(&pA, g_A);
        void* pRB; cudaGetSymbolAddress(&pRB, g_RB);
        h_prm.rb = (char*)(((uintptr_t)pRB + (4u << 20) - 1) & ~(uintptr_t)((4u << 20) - 1));
        cudaFuncSetAttribute(main_kernel, cudaFuncAttributeMaxDynamicSharedMemorySize, mk::TOTAL);
        cudaFuncSetAttribute(conv_kernel, cudaFuncAttributeMaxDynamicSharedMemorySize, ck::TOTAL);
        cudaFuncSetAttribute(out_kernel, cudaFuncAttributeMaxDynamicSharedMemorySize, ok::TOTAL);
    }
    CUtensorMap mWq, mWk, mWv, mWo, mX, mO, mWo2, mA, mOut;
    {
        cuuint64_t d[2] = {4096, 1024}, s[1] = {8192}; cuuint32_t b[2] = {64, 256};
        enc(fn, &mWq, d_in[8], 2, d, s, b, CU_TENSOR_MAP_SWIZZLE_128B);
        enc(fn, &mWk, d_in[9], 2, d, s, b, CU_TENSOR_MAP_SWIZZLE_128B);
        enc(fn, &mWv, d_in[10], 2, d, s, b, CU_TENSOR_MAP_SWIZZLE_128B);
    }
    {
        cuuint64_t d[2] = {1024, 4096}, s[1] = {2048}; cuuint32_t b[2] = {64, 128};
        enc(fn, &mWo, d_in[11], 2, d, s, b, CU_TENSOR_MAP_SWIZZLE_128B);
        cuuint64_t d2[3] = {64, 4096, 16}, s2[2] = {2048, 128}; cuuint32_t b2[3] = {64, 64, 4};
        enc(fn, &mWo2, d_in[11], 3, d2, s2, b2, CU_TENSOR_MAP_SWIZZLE_128B);
    }
    {
        cuuint64_t d[3] = {64, 2048, 16}, s[2] = {2048, 128}; cuuint32_t b[3] = {64, 32, 8};
        enc(fn, &mX, d_in[0], 3, d, s, b, CU_TENSOR_MAP_SWIZZLE_128B);
    }
    {
        cuuint64_t d[3] = {256, 128, 256}, s[2] = {512, 65536}; cuuint32_t b[3] = {256, 2, 16};
        enc(fn, &mO, pO, 3, d, s, b, CU_TENSOR_MAP_SWIZZLE_NONE);
    }
    {
        cuuint64_t d[5] = {1024, 2, 4, 4, 64}, s[4] = {2048, 16384, 4096, 65536}; cuuint32_t b[5] = {64, 2, 4, 4, 4};
        cuuint64_t da[3] = {2048, 8, 128}, sa[2] = {4096, 32768}; cuuint32_t ba[3] = {128, 8, 16};
        enc(fn, &mA, pA, 3, da, sa, ba, CU_TENSOR_MAP_SWIZZLE_NONE);
        enc(fn, &mOut, d_out, 5, d, s, b, CU_TENSOR_MAP_SWIZZLE_128B);
    }
    cudaStream_t st = cudaStreamPerThread;
    conv_kernel<<<128, 288, ck::TOTAL, st>>>(q, k, v, shift_k, ssm_k, ssm_D, gate_w, (const bf16*)d_in[8], (const bf16*)d_in[9],
                                             (const bf16*)d_in[10], (const bf16*)d_in[11], mWq, mWk, mWv, mWo, h_prm.rb);
    cudaLaunchAttribute at[1];
    at[0].id = cudaLaunchAttributeProgrammaticStreamSerialization;
    at[0].val.programmaticStreamSerializationAllowed = 1;
    cudaLaunchConfig_t cfg = {};
    cfg.stream = st; cfg.attrs = at; cfg.numAttrs = PDL;
    cfg.gridDim = dim3(NCTA); cfg.blockDim = dim3(256); cfg.dynamicSmemBytes = mk::TOTAL;
    cudaLaunchKernelEx(&cfg, main_kernel, mWq, mWk, mWv, mWo, mX, mem0, (const bf16*)d_in[11], h_prm);
    cfg.gridDim = dim3(128); cfg.blockDim = dim3(288); cfg.dynamicSmemBytes = ok::TOTAL;
    cudaLaunchKernelEx(&cfg, out_kernel, mO, mWo2, mA, mOut, h_prm);
}
```

```cpp
#include <cuda_runtime.h>
#include <cuda_bf16.h>
#include <cuda.h>
#include <stdint.h>

typedef __nv_bfloat16 bf16;

constexpr int SEQ = 2048, DM = 1024, NH = 32, DH = 128, NSEG = 64;
constexpr int SPIN_LIMIT = 1 << 13, NCTA = 132;
#define NPR 6
#define PDL 1
#define TPF 1

constexpr uint32_t HOME_BITS = 0xB3000;
constexpr uint32_t RB_R = 0;
constexpr uint32_t RB_B = 0x80000;
constexpr uint32_t RB_T = RB_B + 0x4000;
constexpr uint32_t RB_P = RB_B + 0x20000;
constexpr uint32_t RB_X = 2u << 20;
__device__ uint4 g_RB[(8 << 20) / 16];
__device__ uint32_t g_cls[160];
__device__ uint4 g_T[2 * NH * 3072];
__device__ uint4 g_O[NSEG * 4 * 4096];
__device__ uint4 g_A[SEQ * DM / 8];
__device__ float g_gate[SEQ];
__device__ uint32_t g_err;
#define TL(i)
#define TLX(i)

__device__ __forceinline__ uint32_t smem_u32(const void* p) { return (uint32_t)__cvta_generic_to_shared(p); }
__device__ __forceinline__ uint32_t clk() { uint32_t c; asm volatile("mov.u32 %0, %%clock;" : "=r"(c) :: "memory"); return c; }
__device__ __forceinline__ void ldsm4(uint32_t& r0, uint32_t& r1, uint32_t& r2, uint32_t& r3, uint32_t a) {
    asm volatile("ldmatrix.sync.aligned.m8n8.x4.shared.b16 {%0,%1,%2,%3}, [%4];" : "=r"(r0), "=r"(r1), "=r"(r2), "=r"(r3) : "r"(a) : "memory");
}
__device__ __forceinline__ void ldsm4t(uint32_t& r0, uint32_t& r1, uint32_t& r2, uint32_t& r3, uint32_t a) {
    asm volatile("ldmatrix.sync.aligned.m8n8.x4.trans.shared.b16 {%0,%1,%2,%3}, [%4];" : "=r"(r0), "=r"(r1), "=r"(r2), "=r"(r3) : "r"(a) : "memory");
}
__device__ __forceinline__ void ldsm2(uint32_t& r0, uint32_t& r1, uint32_t a) {
    asm volatile("ldmatrix.sync.aligned.m8n8.x2.shared.b16 {%0,%1}, [%2];" : "=r"(r0), "=r"(r1) : "r"(a) : "memory");
}
__device__ __forceinline__ void stsm4t(uint32_t a, uint32_t r0, uint32_t r1, uint32_t r2, uint32_t r3) {
    asm volatile("stmatrix.sync.aligned.m8n8.x4.trans.shared.b16 [%0], {%1,%2,%3,%4};" :: "r"(a), "r"(r0), "r"(r1), "r"(r2), "r"(r3) : "memory");
}
__device__ __forceinline__ void mma16(float* c, uint32_t a0, uint32_t a1, uint32_t a2, uint32_t a3, uint32_t b0, uint32_t b1) {
    asm volatile("mma.sync.aligned.m16n8k16.row.col.f32.bf16.bf16.f32 {%0,%1,%2,%3}, {%4,%5,%6,%7}, {%8,%9}, {%0,%1,%2,%3};"
        : "+f"(c[0]), "+f"(c[1]), "+f"(c[2]), "+f"(c[3]) : "r"(a0), "r"(a1), "r"(a2), "r"(a3), "r"(b0), "r"(b1));
}
__device__ __forceinline__ void mma8(float* c, uint32_t a0, uint32_t a1, uint32_t b0) {
    asm volatile("mma.sync.aligned.m16n8k8.row.col.f32.bf16.bf16.f32 {%0,%1,%2,%3}, {%4,%5}, {%6}, {%0,%1,%2,%3};"
        : "+f"(c[0]), "+f"(c[1]), "+f"(c[2]), "+f"(c[3]) : "r"(a0), "r"(a1), "r"(b0));
}
__device__ __forceinline__ uint32_t pack2(float lo, float hi) {
    uint32_t r; asm("cvt.rn.bf16x2.f32 %0, %1, %2;" : "=r"(r) : "f"(hi), "f"(lo)); return r;
}
__device__ __forceinline__ uint32_t hadd2(uint32_t a, uint32_t b) {
    uint32_t r; asm("add.rn.bf16x2 %0, %1, %2;" : "=r"(r) : "r"(a), "r"(b)); return r;
}
__device__ __forceinline__ float bflo(uint32_t w) { return __uint_as_float(w << 16); }
__device__ __forceinline__ float bfhi(uint32_t w) { return __uint_as_float(w & 0xFFFF0000u); }
__device__ __forceinline__ void st_g32(void* p, uint32_t v) { asm volatile("st.relaxed.gpu.global.u32 [%0], %1;" :: "l"(p), "r"(v) : "memory"); }
__device__ __forceinline__ void st_g128(void* p, uint32_t a, uint32_t b, uint32_t c, uint32_t d) {
    asm volatile("st.relaxed.gpu.global.v4.u32 [%0], {%1,%2,%3,%4};" :: "l"(p), "r"(a), "r"(b), "r"(c), "r"(d) : "memory");
}
__device__ __forceinline__ uint4 lds128(uint32_t a) { uint4 v; asm volatile("ld.shared.v4.u32 {%0,%1,%2,%3}, [%4];" : "=r"(v.x), "=r"(v.y), "=r"(v.z), "=r"(v.w) : "r"(a) : "memory"); return v; }
__device__ __forceinline__ void sts128(uint32_t a, uint4 v) { asm volatile("st.shared.v4.u32 [%0], {%1,%2,%3,%4};" :: "r"(a), "r"(v.x), "r"(v.y), "r"(v.z), "r"(v.w) : "memory"); }
__device__ __forceinline__ float2 lds64f(uint32_t a) { float2 v; asm volatile("ld.shared.v2.f32 {%0,%1}, [%2];" : "=f"(v.x), "=f"(v.y) : "r"(a) : "memory"); return v; }
__device__ __forceinline__ void sts64f(uint32_t a, float x, float y) { asm volatile("st.shared.v2.f32 [%0], {%1,%2};" :: "r"(a), "f"(x), "f"(y) : "memory"); }
__device__ __forceinline__ void sts32f(uint32_t a, float x) { asm volatile("st.shared.f32 [%0], %1;" :: "r"(a), "f"(x) : "memory"); }
__device__ __forceinline__ void sts32(uint32_t a, uint32_t x) { asm volatile("st.shared.u32 [%0], %1;" :: "r"(a), "r"(x) : "memory"); }
__device__ __forceinline__ uint32_t lds32(uint32_t a) { uint32_t v; asm volatile("ld.shared.u32 %0, [%1];" : "=r"(v) : "r"(a) : "memory"); return v; }
__device__ __forceinline__ void cpa16(uint32_t dst, const void* src) { asm volatile("cp.async.cg.shared.global [%0], [%1], 16;" :: "r"(dst), "l"(src) : "memory"); }
__device__ __forceinline__ void cpa_commit() { asm volatile("cp.async.commit_group;" ::: "memory"); }
__device__ __forceinline__ void cpa_wait() { asm volatile("cp.async.wait_all;" ::: "memory"); }
template <int ID, int N> __device__ __forceinline__ void bsync() { asm volatile("bar.sync %0, %1;" :: "n"(ID), "n"(N) : "memory"); }
template <int ID, int N> __device__ __forceinline__ void barrive() { asm volatile("bar.arrive %0, %1;" :: "n"(ID), "n"(N) : "memory"); }
template <int ID, int N> __device__ __forceinline__ void bsync_if(bool on) { asm volatile("{ .reg .pred p; setp.ne.b32 p, %2, 0; @p bar.sync %0, %1; }" :: "n"(ID), "n"(N), "r"((int)on) : "memory"); }
template <int ID, int N> __device__ __forceinline__ void barrive_if(bool on) { asm volatile("{ .reg .pred p; setp.ne.b32 p, %2, 0; @p bar.arrive %0, %1; }" :: "n"(ID), "n"(N), "r"((int)on) : "memory"); }
template <int ID> __device__ __forceinline__ uint32_t any128(uint32_t x) {
    uint32_t r; asm volatile("{ .reg .pred p; setp.ne.b32 p, %1, 0; bar.red.or.pred p, %2, 128, p; selp.u32 %0, 1, 0, p; }" : "=r"(r) : "r"(x), "n"(ID) : "memory"); return r;
}
__device__ __forceinline__ void mbar_init(uint32_t mb, uint32_t n) { asm volatile("mbarrier.init.shared::cta.b64 [%0], %1;" :: "r"(mb), "r"(n) : "memory"); }
__device__ __forceinline__ void mbar_expect(uint32_t mb, uint32_t bytes) { asm volatile("mbarrier.arrive.expect_tx.shared::cta.b64 _, [%0], %1;" :: "r"(mb), "r"(bytes) : "memory"); }
__device__ __forceinline__ void mbar_arrive(uint32_t mb) { asm volatile("mbarrier.arrive.shared::cta.b64 _, [%0];" :: "r"(mb) : "memory"); }
__device__ __forceinline__ void mbar_wait(uint32_t mb, uint32_t ph) {
    asm volatile("{ .reg .pred p; .reg .u32 n; mov.u32 n, 0;\n"
                 "MW_%=: mbarrier.try_wait.parity.shared::cta.b64 p, [%0], %1; add.u32 n, n, 1; setp.lt.and.u32 p, n, %2, !p; @p bra.uni MW_%=; }"
                 :: "r"(mb), "r"(ph), "n"(SPIN_LIMIT) : "memory");
}
__device__ __forceinline__ void tma2d(uint32_t dst, const CUtensorMap* m, int c0, int c1, uint32_t mb) {
    asm volatile("cp.async.bulk.tensor.2d.shared::cluster.global.mbarrier::complete_tx::bytes [%0], [%1, {%3, %4}], [%2];"
        :: "r"(dst), "l"(m), "r"(mb), "r"(c0), "r"(c1) : "memory");
}
__device__ __forceinline__ void tma3d(uint32_t dst, const CUtensorMap* m, int c0, int c1, int c2, uint32_t mb) {
    asm volatile("cp.async.bulk.tensor.3d.shared::cluster.global.mbarrier::complete_tx::bytes [%0], [%1, {%3, %4, %5}], [%2];"
        :: "r"(dst), "l"(m), "r"(mb), "r"(c0), "r"(c1), "r"(c2) : "memory");
}
__device__ __forceinline__ void bulk_ld(uint32_t dst, const void* src, uint32_t bytes, uint32_t mb) {
    asm volatile("cp.async.bulk.shared::cluster.global.mbarrier::complete_tx::bytes [%0], [%1], %2, [%3];" :: "r"(dst), "l"(src), "r"(bytes), "r"(mb) : "memory");
}
__device__ __forceinline__ uint64_t mkdesc(uint32_t addr, uint32_t lbo, uint32_t sbo, uint32_t swz) {
    return (uint64_t)((addr & 0x3FFFF) >> 4) | ((uint64_t)(lbo >> 4) << 16) | ((uint64_t)(sbo >> 4) << 32) | ((uint64_t)swz << 62);
}
__device__ __forceinline__ void wg_fence() { asm volatile("wgmma.fence.sync.aligned;" ::: "memory"); }
__device__ __forceinline__ void wg_commit() { asm volatile("wgmma.commit_group.sync.aligned;" ::: "memory"); }
template <int N> __device__ __forceinline__ void wg_wait() { asm volatile("wgmma.wait_group.sync.aligned %0;" :: "n"(N) : "memory"); }
#define F4(d, o) "+f"(d[o]), "+f"(d[o + 1]), "+f"(d[o + 2]), "+f"(d[o + 3])
__device__ __forceinline__ void wgmma_n32_rs(float* d, const uint32_t* a, uint64_t db, int accum) {
    asm volatile("{.reg .pred p; setp.ne.b32 p, %21, 0;\n"
        "wgmma.mma_async.sync.aligned.m64n32k16.f32.bf16.bf16 {%0,%1,%2,%3,%4,%5,%6,%7,%8,%9,%10,%11,%12,%13,%14,%15}, {%16,%17,%18,%19}, %20, p, 1, 1, 0;}"
        : F4(d, 0), F4(d, 4), F4(d, 8), F4(d, 12) : "r"(a[0]), "r"(a[1]), "r"(a[2]), "r"(a[3]), "l"(db), "r"(accum));
}
__device__ __forceinline__ void wait_until(uint32_t tgt, uint32_t any) {
    asm volatile("{ .reg .pred p, q; .reg .u32 t; .reg .s32 d; mov.u32 t, %0; setp.ne.u32 q, %1, 0xFFFFFFFF;\n"
                 "WU_%=: @q mov.u32 t, %%clock; sub.s32 d, t, %0; setp.lt.s32 p, d, 0; @p bra.uni WU_%=; }" :: "r"(tgt), "r"(any) : "memory");
}

namespace mk {
constexpr uint32_t SB = 1024;
constexpr uint32_t WV = SB, WO = SB + 65536, XT = SB + 131072, TK = SB + 163840  , TQ = TK + 32768, MEM = TQ + 4096,
                   SC = MEM + 8192  , PT = SC + 6144,
                   OB = SC + 8192, SUM = OB + 2048, BAR = SUM + 512, GRP = BAR + 128, PROFB = BAR + 192,
                   TOTAL = PROFB - SB;
static_assert(TOTAL <= 232448, "shared memory");
constexpr uint32_t MB_WQ = BAR, MB_WK = BAR + 8, MB_WV = BAR + 16, MB_WO = BAR + 24, MB_X = BAR + 32, MB_KV = BAR + 40, MB_R = BAR + 48, MB_B = BAR + 56;
constexpr uint32_t XT2 = WV, RS = WV + 32768, VE = RS + 4096;
enum { B_START = 1, B_H0, B_H2, B_H3, B_S1, B_SC, B_SC2, B_S0, B_O, B_O2, B_PT, B_GO, B_VX, B_RD, B_BT };
constexpr uint64_t XD0 = (uint64_t)(XT >> 4) | ((uint64_t)1 << 16) | ((uint64_t)64 << 32) | ((uint64_t)1 << 62);
constexpr uint32_t TSLOT = NH * 49152;
}
struct MainParams { int d[12]; uint32_t zero; char* rb; };
#define XD(i) (mk::XD0 - ((i) >> 5) * ((mk::XT - mk::XT2) >> 4) + (((i) & 31) >> 2) * 256 + ((i) & 3) * 2)
#define XD4(i) XD(i), XD(i + 1), XD(i + 2), XD(i + 3)
#define XD16(i) XD4(i), XD4(i + 4), XD4(i + 8), XD4(i + 12)
__constant__ __align__(256) uint64_t c_xd[64] = {XD16(0), XD16(16), XD16(32), XD16(48)};
#define CUT(r) asm volatile("{ .reg .pred q; setp.eq.u32 q, %1, 0xFFFFFFFF; @q mov.u32 %0, %%clock; }" : "+r"(r) : "r"(t16) : "memory")
__device__ __forceinline__ uint32_t opq(uint32_t x) { asm volatile("" : "+r"(x)); return x; }
__device__ __forceinline__ float opqf(float x) { asm volatile("" : "+f"(x)); return x; }
#define PROF(i)
#define PROFW(i, w)
#define TRC(i, v)
#define RETRY(i, on)
#define P(i) prm.d[i]
#define DELAY(n) do { if (n) { _Pragma("unroll") for (int i_ = 0; i_ < n; i_++) asm volatile("mad.lo.u32 %0, %0, %1, %0;" : "+r"(pb) : "r"(prm.zero)); CUT(pa); } } while (0)

__device__ __forceinline__ uint32_t tagw(uint32_t w, uint32_t tau) { return (w & ~1u) | tau; }
__device__ __forceinline__ uint32_t ld_g32(const void* p) { uint32_t v; asm volatile("ld.relaxed.gpu.global.u32 %0, [%1];" : "=r"(v) : "l"(p) : "memory"); return v; }
__device__ __forceinline__ void ld_g64(uint32_t* v, const void* p) { asm volatile("ld.relaxed.gpu.global.v2.u32 {%0,%1}, [%2];" : "=r"(v[0]), "=r"(v[1]) : "l"(p) : "memory"); }
__device__ __forceinline__ void ld_g128(uint32_t* v, const void* p) {
    asm volatile("ld.relaxed.gpu.global.v4.u32 {%0,%1,%2,%3}, [%4];" : "=r"(v[0]), "=r"(v[1]), "=r"(v[2]), "=r"(v[3]) : "l"(p) : "memory");
}
__device__ __forceinline__ void st_g64(void* p, uint32_t a, uint32_t b) { asm volatile("st.relaxed.gpu.global.v2.u32 [%0], {%1,%2};" :: "l"(p), "r"(a), "r"(b) : "memory"); }
__device__ __forceinline__ void lds128f(float* v, uint32_t a) { asm volatile("ld.shared.v4.f32 {%0,%1,%2,%3}, [%4];" : "=f"(v[0]), "=f"(v[1]), "=f"(v[2]), "=f"(v[3]) : "r"(a) : "memory"); }
__device__ __forceinline__ void sts128f(uint32_t a, float x, float y, float z, float w) { asm volatile("st.shared.v4.f32 [%0], {%1,%2,%3,%4};" :: "r"(a), "f"(x), "f"(y), "f"(z), "f"(w) : "memory"); }
__device__ __forceinline__ void stsm4(uint32_t a, uint32_t r0, uint32_t r1, uint32_t r2, uint32_t r3) {
    asm volatile("stmatrix.sync.aligned.m8n8.x4.shared.b16 [%0], {%1,%2,%3,%4};" :: "r"(a), "r"(r0), "r"(r1), "r"(r2), "r"(r3) : "memory");
}
__device__ __forceinline__ void mmaq(float* c, const uint32_t* a, uint32_t b0, uint32_t b1) { mma16(c, a[0], a[1], a[2], a[3], b0, b1); }
template <int LUT> __device__ __forceinline__ uint32_t lop3(uint32_t a, uint32_t b, uint32_t c) { uint32_t r; asm("lop3.b32 %0, %1, %2, %3, %4;" : "=r"(r) : "r"(a), "r"(b), "r"(c), "n"(LUT)); return r; }
template <int N, int S> __device__ __forceinline__ uint32_t stale(const uint32_t* x, uint32_t tau) {
    if constexpr (N == 2) return lop3<0x7E>(x[0], tau, x[S]);
    else if constexpr (N == 3) return lop3<0xF6>(stale<2, S>(x, tau), x[2 * S], tau);
    else if constexpr (N == 4 || N == 16) return lop3<0xFC>(stale<N / 2, S>(x, tau), stale<N / 2, S>(x + N / 2 * S, tau), 0);
    else return lop3<0xFE>(stale<3, S>(x, tau), stale<3, S>(x + 3 * S, tau), stale<2, S>(x + 6 * S, tau));
}
__device__ __forceinline__ uint32_t late(uint32_t a, uint32_t b, uint32_t mask) {
    uint32_t r;
    asm volatile("{ .reg .pred p; .reg .b32 t; lop3.b32 t, %1, %2, %3, 0xA8; setp.ne.b32 p, t, 0; vote.sync.any.pred p, p, 0xFFFFFFFF; selp.u32 %0, 1, 0, p; }" : "=r"(r) : "r"(a), "r"(b), "r"(mask));
    return r;
}
#define AGAIN(id, reload, ...) _Pragma("unroll 1") for (int n_ = 0; __builtin_expect(__VA_ARGS__, 0) && n_ < SPIN_LIMIT; n_++) { RETRY(id, 1); reload; }
__device__ __forceinline__ uint32_t tile_off(int lane, int chunk0) {
    return ((lane >> 4) * 8 + (lane & 7)) * 128 + (((chunk0 + ((lane >> 3) & 1)) ^ (lane & 7)) << 4);
}
template <int K0, int K1>
__device__ __forceinline__ void load_tile(uint32_t a, uint32_t* T) {
    #pragma unroll
    for (int ks = K0; ks < K1; ks++) ldsm4t(T[4 * ks], T[4 * ks + 1], T[4 * ks + 2], T[4 * ks + 3], a + ks * 2048);
}
__device__ __forceinline__ void lds128u(uint32_t* v, uint32_t a) { asm volatile("ld.shared.v4.u32 {%0,%1,%2,%3}, [%4];" : "=r"(v[0]), "=r"(v[1]), "=r"(v[2]), "=r"(v[3]) : "r"(a) : "memory"); }
template <int K0, int K1, int STRIDE = 4096>
__device__ __forceinline__ void load_frag(uint32_t a, uint32_t* T) {
    #pragma unroll
    for (int ks = K0; ks < K1; ks++) lds128u(&T[4 * ks], a + ks * STRIDE);
}
template <int L0, int L1, bool INIT = false>
__device__ __forceinline__ void wg_run(float* acc, const uint32_t* A, const uint64_t* d) {
    if (L1 > L0) {
        wg_fence();
        #pragma unroll
        for (int l = L0; l < L1; l++) wgmma_n32_rs(acc, &A[4 * l], d[l], INIT || l != 0);
        wg_commit();
    }
}
__device__ __forceinline__ void load_x(const CUtensorMap* tmX, int c, int seg, uint32_t dst, bool on) {
    asm volatile("{ .reg .pred p; elect.sync _|p, 0xFFFFFFFF; setp.ne.and.b32 p, %6, 0, p;\n"
        "@p mbarrier.arrive.expect_tx.shared::cta.b64 _, [%3], 32768;\n"
        "@p cp.async.bulk.tensor.3d.shared::cluster.global.mbarrier::complete_tx::bytes [%4], [%0, {%5, %1, %2}], [%3]; }"
        :: "l"(tmX), "r"(seg * 32), "r"((c & 1) * 8), "r"(mk::MB_X), "r"(dst), "r"(0), "r"((int)on) : "memory");
}
__device__ __forceinline__ void bulk_expect(uint32_t mb, uint32_t bytes) {
    asm volatile("{ .reg .pred p; elect.sync _|p, 0xFFFFFFFF; @p mbarrier.arrive.expect_tx.shared::cta.b64 _, [%0], %1; }" :: "r"(mb), "r"(bytes) : "memory");
}
__device__ __forceinline__ void bulk_copy(uint32_t dst, const void* src, uint32_t bytes, uint32_t mb) {
    asm volatile("{ .reg .pred p; elect.sync _|p, 0xFFFFFFFF; @p cp.async.bulk.shared::cluster.global.mbarrier::complete_tx::bytes [%0], [%1], %2, [%3]; }"
        :: "r"(dst), "l"(src), "r"(bytes), "r"(mb) : "memory");
    __syncwarp();
}
__device__ __forceinline__ void bulk_copy_if(bool on, uint32_t dst, const void* src, uint32_t bytes, uint32_t mb) {
    asm volatile("{ .reg .pred p; elect.sync _|p, 0xFFFFFFFF; setp.ne.and.b32 p, %4, 0, p; @p cp.async.bulk.shared::cluster.global.mbarrier::complete_tx::bytes [%0], [%1], %2, [%3]; }"
        :: "r"(dst), "l"(src), "r"(bytes), "r"(mb), "r"((int)on) : "memory");
    __syncwarp();
}
__device__ __forceinline__ void kv_expect(uint32_t bytes) { bulk_expect(mk::MB_KV, bytes); }
__device__ __forceinline__ void kv_copy(uint32_t dst, const void* src, uint32_t bytes) { bulk_copy(dst, src, bytes, mk::MB_KV); }
__device__ __forceinline__ uint32_t gtime() { uint32_t c; asm volatile("mov.u32 %0, %%globaltimer_lo;" : "=r"(c) :: "memory"); return c; }
__device__ __forceinline__ void wait_g(uint32_t tgt, uint32_t any) {
    asm volatile("{ .reg .pred p, q; .reg .u32 t; mov.u32 t, %0; setp.ne.u32 q, %1, 0xFFFFFFFF;\n"
                 "WG_%=: @q mov.u32 t, %%globaltimer_lo; sub.u32 t, t, %0; setp.gt.u32 p, t, 0xFFFF0000; @p bra.uni WG_%=; }" :: "r"(tgt), "r"(any) : "memory");
    __syncwarp();
}
__device__ __forceinline__ uint32_t clkv(uint32_t any) {
    uint32_t c; asm volatile("{ .reg .pred q; setp.ne.u32 q, %1, 0xFFFFFFFF; mov.u32 %0, 0; @q mov.u32 %0, %%clock; }" : "=r"(c) : "r"(any) : "memory"); return c;
}
__device__ __forceinline__ char* kv_src(int c, int seg) { return (char*)g_T + ((seg & 1) * mk::TSLOT + (c >> 2) * 49152); }
__device__ __forceinline__ void prefetch_l2(const void* p, uint32_t bytes) {
    asm volatile("{ .reg .pred p; elect.sync _|p, 0xFFFFFFFF; @p cp.async.bulk.prefetch.L2.global [%0], %1; }" :: "l"(p), "r"(bytes) : "memory");
}
__device__ __forceinline__ uint32_t phase(int i) { return (~i >> 1) & 1; }
__device__ __forceinline__ void qk_pack(const float* acc, uint32_t* p) {
    #pragma unroll
    for (int i = 0; i < 4; i++) { p[i] = pack2(acc[4 * i], acc[4 * i + 1]); p[4 + i] = pack2(acc[4 * i + 2], acc[4 * i + 3]); }
}
__device__ __forceinline__ void sts128_if(bool on, uint32_t a, const uint32_t* p) {
    asm volatile("{ .reg .pred p; setp.ne.b32 p, %5, 0; @p st.shared.v4.u32 [%0], {%1,%2,%3,%4}; }" :: "r"(a), "r"(p[0]), "r"(p[1]), "r"(p[2]), "r"(p[3]), "r"((int)on) : "memory");
}
__device__ __forceinline__ void st_if(bool on, char* a, const uint32_t* p) {
    asm volatile("{ .reg .pred p; setp.ne.b32 p, %5, 0; @p st.relaxed.gpu.global.v4.u32 [%0], {%1,%2,%3,%4}; }" :: "l"(a), "r"(p[0]), "r"(p[1]), "r"(p[2]), "r"(p[3]), "r"((int)on) : "memory");
}
__device__ __forceinline__ char* tok_dst(int c, int seg, int wg) { return kv_src(c, seg) + (wg ? (c & 1) * 8192 + (c & 2) * 2048 : 32768 + (c & 1) * 2048 + (c & 2) * 512); }
#define HI8 (wg ? 0x220 : 0xC0)
#define TAGM() uint32_t tm[4]; tag_masks(tm, (t16 >> (wg ? 4 : 6)) & 24)
__device__ __forceinline__ void acc_init(float* acc, const uint32_t* p) {
    #pragma unroll
    for (int i = 0; i < 4; i++) { acc[4 * i] = bflo(p[i]); acc[4 * i + 1] = bfhi(p[i]); acc[4 * i + 2] = bflo(p[4 + i]); acc[4 * i + 3] = bfhi(p[4 + i]); }
}
__device__ __forceinline__ void acc_add(float* acc, const uint32_t* p) {
    #pragma unroll
    for (int i = 0; i < 4; i++) { acc[4 * i] += bflo(p[i]); acc[4 * i + 1] += bfhi(p[i]); acc[4 * i + 2] += bflo(p[4 + i]); acc[4 * i + 3] += bfhi(p[4 + i]); }
}
__device__ __forceinline__ void tag_masks(uint32_t* m, uint32_t j8) {
    const uint32_t x = 1u << j8;
    #pragma unroll
    for (int i = 0; i < 4; i++) m[i] = opq(__byte_perm(x, 0, 0x4440 + i));
}
__device__ __forceinline__ void pack_tag(const float* acc, uint32_t* p, uint32_t tau, const uint32_t* m) {
    qk_pack(acc, p);
    #pragma unroll
    for (int i = 0; i < 8; i++) p[i] = lop3<0xB8>(p[i], m[i & 3], tau);
}
__device__ __forceinline__ uint32_t kv_stale(uint32_t w, uint32_t l16, uint32_t tau) {
    uint32_t x[12];
    const uint32_t a = opq(l16 * 2 + ((l16 >> 4) & 0x1C) + w * 12288), aq = w == 2 ? opq(l16 * 2 + ((l16 >> 2) & 0x10) + ((l16 >> 5) & 0xC) + 24576) : a;
    #pragma unroll
    for (int i = 0; i < 12; i++) x[i] = lds32(mk::TK + i * 1024 + (i < 8 ? a : aq));
    return late(stale<8, 1>(x, tau), stale<4, 1>(x + 8, tau), 1);
}
__device__ __forceinline__ void refetch_kv(int c, int seg, int w, uint32_t l16) {
    #pragma unroll 1
    for (int i = w * 24; i < w * 24 + 24; i++) {
        uint32_t v[4];
        ld_g128(v, kv_src(c, seg) + (i * 512 + (i >> 6) * (c & 3) * 4096) + l16);
        sts128(mk::TK + i * 512 + l16, make_uint4(v[0], v[1], v[2], v[3]));
    }
    __syncwarp();
}
__device__ __forceinline__ void get_kv(int c, int seg) {
    kv_expect(36864); kv_copy(mk::TK, kv_src(c, seg), 32768); kv_copy(mk::TQ, kv_src(c, seg) + (32768 + (c & 3) * 4096), 4096);
}
constexpr uint32_t ONES = 0x3F803F80u;
__device__ __forceinline__ float rcpf(float x) { float r; asm("rcp.approx.ftz.f32 %0, %1;" : "=f"(r) : "f"(x)); return r; }

#define ANN 2
#define POL 8
#define PRE0 4
#define PRE1 4
#define HC 2
#define HR 4
#define BL 1
#define NA 2
#define QF 0
#define DEEP 6
#define AHEAD(n) (PRE0 + 2 * (n) < (n) + DEEP ? PRE0 + 2 * (n) : (n) + DEEP < 16 ? (n) + DEEP : 16)
#define CO 1
#define HS 2
#define VP 0
#define KM 1
#define NLDS 2
#define AL 2
#define RP 26
#define RQ 2
#define RL 29
#define R4 1
#define KVP 12
#define LD7 8
#define XP 3
#define G2 0
#define NB 26
#define BD 8
#define NP 22
#define TA 4
#define TA0 2
#define NT 19
#define VH 1
#define TRIES 200
#define NPW 3
#define EV0 5
#define EV1 8
#define WA1 6
#define WA2 9
#define H2 10
#define QV 1
#define QD 0
#define KD 0
#define VD 0
#define WA0 4
#define ONE 0
#define PP 12
#define OBA 3
#define WA3 1
#define WB1 0
#define WB2 12
#define WB3 13
#define H0 6
#define H3 10
__device__ __forceinline__ uint32_t tagm(uint32_t w, uint32_t mask, uint32_t tau) { return lop3<0xB8>(w, mask, tau); }
__device__ __forceinline__ char* at(uint32_t lo, uint32_t hi) { char* p; asm("mov.b64 %0, {%1,%2};" : "=l"(p) : "r"(lo), "r"(hi)); return p; }
__device__ __forceinline__ float ex2(float x) { float r; asm("ex2.approx.ftz.f32 %0, %1;" : "=f"(r) : "f"(x)); return r; }
__device__ __forceinline__ float max8(const float* x) { return fmaxf(fmaxf(fmaxf(x[0], x[1]), fmaxf(x[2], x[3])), fmaxf(fmaxf(x[4], x[5]), fmaxf(x[6], x[7]))); }
__device__ __forceinline__ float max4lanes(float m) { return fmaxf(fmaxf(m, __shfl_xor_sync(~0u, m, 1)), fmaxf(__shfl_xor_sync(~0u, m, 2), __shfl_xor_sync(~0u, m, 3))); }
constexpr float SCL = 0.08838834764831845f * 1.4426950408889634f;
__device__ __forceinline__ void tok_scores(float* x, uint32_t sa) {
    float y[8];
    lds128f(x, sa); lds128f(y, sa + 1024); lds128f(x + 4, sa + 512); lds128f(y + 4, sa + 1536);
    #pragma unroll
    for (int i = 0; i < 8; i++) x[i] += y[i];
}
__device__ __forceinline__ void mem_scores(float* x, uint32_t sa) {
    float z[8];
    lds128f(z, sa + 2048); lds128f(z + 4, sa + 2560);
    x[8] = (z[0] + z[2]) + (z[4] + z[6]); x[9] = (z[1] + z[3]) + (z[5] + z[7]);
}

struct Ctx { uint32_t u_rs, u_rl, u_bs, u_bl, rblo, rbhi; int w8, c; };
template <int wg>
__device__ __forceinline__ void steps(uint32_t* W, uint32_t* T, uint32_t t16, uint32_t pa, uint32_t pb, const Ctx& cx, const CUtensorMap* tmX, const MainParams& prm) {
    using namespace mk;
    const int c = cx.c, kap = c & 1, w8 = cx.w8;
    const uint32_t rbhi = cx.rbhi;
    uint32_t u_rs = cx.u_rs, u_rl = cx.u_rl, u_bs = cx.u_bs, u_bl = cx.u_bl ^ ((c & 2) << 14);
    uint32_t u_x = cx.rblo + RB_X + (c >> 2) * 16384, u_xs = u_x + kap * 2048 + (c & 2) * 512;
    uint32_t u_ta = ((cx.u_bl & ~0x10000u) ^ (kap << 12)) + (RB_T - RB_B) + 1024;
    uint32_t u_rp = cx.rblo + RB_T + 1024 + c * 4;
    uint32_t u_og = (c & 3) * 65536 + (c >> 2) * 2048 + (w8 & 3) * 256;
    const uint32_t u_sa = (w8 & 2) * 256 + (w8 & 1) * 8;
    #define TOK_DST() tok_dst(c, seg, wg)
    constexpr int EV = wg ? EV1 : EV0;
    constexpr uint32_t VEB = VE + (wg ? EV0 * 2048 - 2048 : 0) - (16 - EV) * 2048;
    static_assert((EV0 + EV1) * 2048 <= 28672, "");
    __syncthreads();
    #pragma unroll
    for (int i = 16 - EV; i < 16; i++) sts128(VEB + i * 2048 + t16, make_uint4(T[4 * i], T[4 * i + 1], T[4 * i + 2], T[4 * i + 3]));
    asm volatile("fence.proxy.async.shared::cta;" ::: "memory");
    #pragma unroll 1
    for (int s = 0, bc = 0, redo = 0;;) {
        bc = opq(bc + 1);
        t16 |= prm.zero & bc;
        const int seg = s + 2;
        const uint32_t tau = phase(s);
        const uint32_t l16 = opq(t16 & 0x1F0);
        uint32_t F[64];
        float ot[3][2][4];
        uint32_t an[4];
        #define LDB(i) ldsm4t(b[i][0], b[i][1], b[i][2], b[i][3], MEM + l16 + (i) * 512)
        #define ST_X() do { char* xs = at(u_xs + (pb >> 16), rbhi) + wg * 4096; \
            st_g32(xs, tagm(pack2((a[0][0] + a[1][0]) + (a[2][0] + a[3][0]), (a[0][2] + a[1][2]) + (a[2][2] + a[3][2])), mG, tau * 0x10001u)); \
            st_g32(xs + 32, tagm(pack2((a[0][1] + a[1][1]) + (a[2][1] + a[3][1]), (a[0][3] + a[1][3]) + (a[2][3] + a[3][3])), mG, tau * 0x10001u)); } while (0)
        #define ST_V() st_g64(at(u_xs + (t16 >> 1), rbhi) + (8192 + wg * 3072), \
            tagm(pack2((v[0][0] + v[1][0]) + (v[2][0] + v[3][0]), (v[0][1] + v[1][1]) + (v[2][1] + v[3][1])), mT, tau), \
            pack2((v[0][2] + v[1][2]) + (v[2][2] + v[3][2]), (v[0][3] + v[1][3]) + (v[2][3] + v[3][3])))
        #define V_MMA(i, o) do { mmaq(v[2 * ((i) & 1)], &T[8 * (i)], b[(o) + (i)][0], b[(o) + (i)][1]); mmaq(v[2 * ((i) & 1) + 1], &T[8 * (i) + 4], b[(o) + (i)][2], b[(o) + (i)][3]); } while (0)
        #define ST_R(i) do { \
                const uint32_t r0 = pack2((r[i][0][0] + r[i][1][0]) * i0, (r[i][0][1] + r[i][1][1]) * i1); \
                const uint32_t r1 = pack2((r[i][0][2] + r[i][1][2]) * i0, (r[i][0][3] + r[i][1][3]) * i1); \
                st_g64(at(ra ^ (i * 0x3000), rbhi), tagm(r0, mT, tau), r1); } while (0)
        #define LD_OB(i) ldsm4t(ob[4 * (i)], ob[4 * (i) + 1], ob[4 * (i) + 2], ob[4 * (i) + 3], OB + l16 + (i) * 512)
        #define WO_MMA(have, more, mid, tail) uint32_t ob[16], ra; float r[2][2][4] = {}; \
            LD_OB(0); __syncwarp(); LD_OB(1); __syncwarp(); if (OBA > 2) { LD_OB(2); __syncwarp(); } \
            _Pragma("unroll") for (int i = have; i < have + more; i++) { lds128u(&F[4 * i], WO + t16 + i * 4096); __syncwarp(); } \
            _Pragma("unroll") for (int i = 0; i < 16; i++) { \
                if (!(i & 1) || (i > 4 && i < 8)) CUT(pb); \
                if (i == 4) LD_OB(OBA); \
                if (i == 5 && OBA == 2) LD_OB(3); \
                { const int n = have + more + i - 8 + OBA; if (i >= 8 - OBA && n < 16) lds128u(&F[4 * n], WO + t16 + n * 4096); } \
                if (wg == 0 && i == 4) { const float2 su = lds64f(SUM + (l16 >> 1)); i0 = su.x; i1 = su.y; } \
                mmaq(r[(i >> 1) & 1][i & 1], &F[4 * i], ob[(i >> 2) * 4 + 2 * (i & 1)], ob[(i >> 2) * 4 + 2 * (i & 1) + 1]); \
                if (wg && i == 2) { i0 = opqf(rcpf(i0)); i1 = opqf(rcpf(i1)); } \
                if (i == PP) { mid; } \
                if (wg && i == POL) POLL(); \
                if (!wg && i == KVP) bulk_copy(TK + 16384 + w8 * 4096, kv_src(c, s + 1) + (16384 + w8 * 4096), 4096, MB_KV); \
                if (i == 12) ra = opq(lop3<0x6A>((l16 >> 1) * 33, 0x1078, u_rs)); } \
            CUT(pb); tail; \
            if (!wg) { i0 = rcpf(i0); i1 = rcpf(i1); } \
            ST_R(0); ST_R(1)
        #define LD_X(r, o) do { ld_g64(r, xa + (o)); ld_g64(r + 2, xa + ((o) + 2048)); ld_g64(r + 4, xa + ((o) + 1024)); ld_g64(r + 6, xa + ((o) + 3072)); } while (0)
        #define REPORT(w, add) asm volatile("{ .reg .pred p; .reg .u32 t; setp.lt.u32 p, %1, 32; mov.u32 t, %1; @p mov.u32 t, %%globaltimer_lo; add.u32 t, t, %3; lop3.b32 t, t, 31, %2, 0xB8; @p st.relaxed.gpu.global.u32 [%0], t; }" \
            :: "l"(at(u_rp + (l16 << 8), rbhi)), "r"(t16 - (w) * 512), "r"(s), "r"(add) : "memory")
        #define POLL() asm volatile("{ .reg .pred p; setp.ge.u32 p, %5, 3584; mov.u32 %0, 0; mov.u32 %1, 0; mov.u32 %2, 0; mov.u32 %3, 0; @p ld.relaxed.gpu.global.v4.u32 {%0,%1,%2,%3}, [%4]; }" \
            : "=&r"(an[0]), "=&r"(an[1]), "=&r"(an[2]), "=&r"(an[3]) : "l"(at(u_ta + l16, rbhi)), "r"(t16) : "memory")
        #define GET_B(sl) do { const uint32_t a_ = u_bl ^ (sl); bulk_copy(MEM, at(a_, rbhi), 4096, MB_B); bulk_copy(MEM + 4096, at(a_ ^ 0x3000, rbhi), 4096, MB_B); } while (0)
        if constexpr (wg == 0) {
            float a[4][4], v[4][4] = {};
            uint32_t b[16][4];
            if (__builtin_expect(redo, 0)) {
                RETRY(6, 1);
                bsync<B_RD, 256>();
                if (w8 == 3) { bulk_expect(MB_B, 8192); GET_B(1 << 20); }
                __syncwarp();
            }
            const uint32_t ck = opq(t16 * 2 + ((l16 >> 4) & 0x1C)), tp = opq(phase(s - 1)), cm = opq((2 * bc + (s > 0 && bc < SPIN_LIMIT)) | (t16 >> 19));
            CUT(pa);
            mbar_wait(MB_B, ~bc & 1);
            #define ORD(n) (n)
            LDB(ORD(0)); __syncwarp(); LDB(ORD(1)); __syncwarp();
            const uint32_t c0 = lds32(MEM + ck), c1 = lds32(MEM + 4096 + ck);
            __syncwarp();
            #pragma unroll
            for (int n = 2; n < PRE0; n++) { LDB(ORD(n)); __syncwarp(); }
            PROF(0);
            uint32_t vw[2];
            #pragma unroll
            for (int n = 0; n < 16; n++) {
                const int i = ORD(n);
                CUT(pa);
                #pragma unroll
                for (int m = AHEAD(n); m < AHEAD(n + 1); m++) { LDB(ORD(m)); __syncwarp(); }
                if (n == HC) redo = opq(lop3<0x7E>(c0, tp, c1) & cm);
                if (n == HC + 1) asm volatile("{ .reg .pred p; setp.ne.u32 p, %2, 0; @p st.shared.u32 [%0], %1; }" :: "r"(SUM + 256), "r"(cm), "r"(redo & 1) : "memory");
                if (n == H0) barrive<B_H0, 256>();
                if (n == HR + 1) { redo = lds32(SUM + 256 + opq(t16 >> 20)); __syncwarp(); }
                if (n == HR) bsync<B_START, 128>();
                if (n == 12) redo = !late(redo ^ (2 * bc + 1), 0, ~0u);
                const int e = n < 8 ? 0 : 2 * (~n & 1);
                if (!(n & 7)) a[e][0] = a[e][1] = a[e][2] = a[e][3] = a[e + 1][0] = a[e + 1][1] = a[e + 1][2] = a[e + 1][3] = 0.f;
                mmaq(a[e], &W[8 * i], b[i][0], b[i][1]);
                if (n < 8) { mmaq(v[0], &T[8 * i], b[i][0], b[i][1]); CUT(pa); }
                mmaq(a[e + 1], &W[8 * i + 4], b[i][2], b[i][3]);
                if (n < 8) mmaq(v[1], &T[8 * i + 4], b[i][2], b[i][3]);
                if (n == 10) { vw[0] = opq(pack2(v[0][0] + v[1][0], v[0][1] + v[1][1])); vw[1] = opq(pack2(v[0][2] + v[1][2], v[0][3] + v[1][3])); }
            }
            CUT(pa);
            if (__builtin_expect(redo, 0)) { __syncwarp(); continue; }
            CUT(pa); CUT(pb);
            const uint32_t mG = (l16 & 0x1C0) ? 0 : 0x10001u, mT = (l16 & 0x30) ? 0 : 1;
            ST_X();
            CUT(pa);
            PROF(1);
            const char* const xa = at(u_x + (t16 >> 1), rbhi);
            float sc[4][4];
            uint32_t k[8], A[16], q[16], kf[16];
            #define LD_Q(xb) do { LD_X(q, 0); { const char* const xa = xb; LD_X(q + 8, 0); } } while (0)
            #define XB() at((u_x + (opq(t16) >> 1)) ^ 256, rbhi)
            #define LD_A(i) ldsm4t(A[4 * i], A[4 * i + 1], A[4 * i + 2], A[4 * i + 3], TQ + (i & 1) * 1024 + ((i & 2) ? qb : qa))
            uint32_t k1[16];
            #define LD_K(i) do { ldsm4t(kf[4 * i], kf[4 * i + 1], kf[4 * i + 2], kf[4 * i + 3], TK + ka[i]); ldsm4t(k1[4 * i], k1[4 * i + 1], k1[4 * i + 2], k1[4 * i + 3], TK + 8192 + ka[i]); __syncwarp(); } while (0)
            const char* const xb = XB();
            const uint32_t ka[4] = {opq(pa & 0xFFFF), opq((pa & 0xFFFF) ^ 0x400), opq((pa & 0xFFFF) ^ 0x10), opq((pa & 0xFFFF) ^ 0x410)}, qa = opq(pa >> 16), qb = opq(qa ^ 0x100);
            st_g64(at(u_xs + (t16 >> 1), rbhi) + 8192, tagm(vw[0], mT, tau), vw[1]);
            CUT(pb);
            bsync<B_H2, 256>();
            if (QF) { LD_Q(xb); __syncwarp(); }
            #pragma unroll
            for (int i = 0; i < NA; i++) LD_K(i);
            CUT(pb);
            #pragma unroll
            for (int i = 0; i < 4 * NA; i++) kf[i] = opq(hadd2(kf[i], k1[i]));
            CUT(pb);
            if (!QF) { DELAY(QD); LD_Q(xb); CUT(pb); }
            bsync<B_H3, 256>();
            #pragma unroll
            for (int i = NA; i < 4; i++) LD_K(i);
            LD_A(0); LD_A(1); LD_A(2); LD_A(3);
            CUT(pb);
            if (KM == 1) {
                #pragma unroll
                for (int i = 4 * NA; i < 16; i++) kf[i] = opq(hadd2(kf[i], k1[i]));
                CUT(pb);
            }
            DELAY(KD);
            LD_X(k, 4096);
            barrive<B_VX, 256>();
            CUT(pb);
            PROF(3);
            if (KM == 2) {
                #pragma unroll
                for (int i = 4 * NA; i < 16; i++) kf[i] = opq(hadd2(kf[i], k1[i]));
            }
            #pragma unroll
            for (int i = 0; i < 8; i++) A[2 * i + 1] = opq(hadd2(A[2 * i], A[2 * i + 1]));
            CUT(pb);
            AGAIN(1, LD_Q(XB()); LD_X(k, 4096); sts32(SUM + 268, s + 1), late(stale<4, 2>(q, tau), stale<4, 2>(q + 8, tau), mT))
            #pragma unroll
            for (int i = 0; i < 4; i++) {
                A[4 * i] = hadd2(q[4 * i], q[4 * i + 2]); A[4 * i + 2] = hadd2(q[4 * i + 1], q[4 * i + 3]);
                if (i < 2) { sc[i][0] = sc[i][1] = sc[i][2] = sc[i][3] = sc[2 + i][0] = sc[2 + i][1] = sc[2 + i][2] = sc[2 + i][3] = 0.f; }
                mmaq(sc[i & 1], A + 4 * i, kf[2 * i], kf[2 * i + 1]); mmaq(sc[2 + (i & 1)], A + 4 * i, kf[8 + 2 * i], kf[9 + 2 * i]);
            }
            sts128f(SC + t16, sc[0][0] + sc[1][0], sc[0][1] + sc[1][1], sc[2][0] + sc[3][0], sc[2][1] + sc[3][1]);
            barrive<B_S1, 256>();
            sts128f(SC + 3072 + t16, sc[0][2] + sc[1][2], sc[0][3] + sc[1][3], sc[2][2] + sc[3][2], sc[2][3] + sc[3][3]);
            load_frag<0, WB1>(WO + t16, F);
            const uint32_t sa = opq(l16 + u_sa);
            CUT(pb);
            PROF(4);
            float d[16];
            #pragma unroll 1
            for (int n_ = 0;; n_++) {
                #pragma unroll
                for (int i = 0; i < 4; i++) { d[4 * i] = d[4 * i + 1] = d[4 * i + 2] = d[4 * i + 3] = 0.f; mmaq(d + 4 * i, A + 4 * (i >> 1), k[2 * i], k[2 * i + 1]); }
                if (__builtin_expect(!late(stale<2, 2>(k, tau), stale<2, 2>(k + 4, tau), mT), 1) || n_ >= SPIN_LIMIT) break;
                RETRY(2, 1);
                LD_X(k, 4096);
            }
            sts64f(SC + 2048 + sa, (d[0] + d[4]) + (d[8] + d[12]), (d[1] + d[5]) + (d[9] + d[13]));
            barrive<B_SC, 256>();
            CUT(pb);
            sts64f(SC + 5120 + sa, (d[2] + d[6]) + (d[10] + d[14]), (d[3] + d[7]) + (d[11] + d[15]));
            PROF(5);
            if (w8 == 0) {
                float x[10];
                bsync<B_S0, 128>();
                tok_scores(x, SC + 3072 + l16); mem_scores(x, SC + 3072 + l16);
                __syncwarp();
                load_frag<WB1, WB2>(WO + t16, F);
                const int g = l16 >> 6, lim = 8 * (g >> 1) + 2 * (c & 3) + (g & 1) - ((l16 >> 1) & 0x18);
                #pragma unroll
                for (int i = 0; i < 8; i++) if (i > lim) x[i] = -INFINITY;
                const float ms = opqf(-SCL * max4lanes(fmaxf(max8(x), fmaxf(x[8], x[9]))));
                CUT(pb);
                #pragma unroll
                for (int i = 0; i < 10; i++) x[i] = ex2(fmaf(x[i], SCL, ms));
                load_frag<WB2, WB3>(WO + t16, F);
                sts128(PT + l16, make_uint4(pack2(x[0], x[1]), pack2(x[2], x[3]), pack2(x[4], x[5]), pack2(x[6], x[7])));
                sts32(PT + 512 + (l16 >> 2), pack2(x[8], x[9]));
                if (!ONE) barrive<B_PT, 160>();
            } else {
                if (ANN == 2) { bsync<B_S0, 128>(); const uint32_t f = lds32(SUM + 268 + opq(t16 >> 16)); REPORT(3, f == s + 1 ? P(2) : 0); } else barrive<B_S0, 128>();
                if (w8 == 1) { if (seg < NSEG) mbar_wait(MB_X, seg & 1); }
                else if (w8 == 2) {
                    bulk_expect(MB_KV, 36864);
                    bulk_copy(TK, kv_src(c, s + 1), 16384, MB_KV); bulk_copy(TQ, kv_src(c, s + 1) + (32768 + (c & 3) * 4096), 4096, MB_KV);
                    bulk_expect(MB_B, 8192); bulk_expect(MB_R, 4096);
                    __syncwarp();
                }
                bsync<B_SC2, 224>();
                load_frag<WB1, WB3>(WO + t16, F);
                __syncwarp();
                CUT(pb);
            }
            bsync<B_O2, 256>();
            PROF(6);
            float i0, i1;
            WO_MMA(WB3, 0, , );
        } else {
            float a[4][4], v[4][4] = {};
            uint32_t b[16][4];
            barrive_if<B_RD, 256>(redo);
            CUT(pa);
            bsync<B_H0, 256>();
            #pragma unroll
            for (int n = 0; n < PRE1; n++) { LDB(n); __syncwarp(); }
            redo = lds32(SUM + 256 + opq(t16 >> 20));
            PROF(0);
            #pragma unroll
            for (int i = 0; i < 16; i++) {
                if (!(i & 1)) {
                    CUT(pa);
                    if (PRE1 < 8 && i + PRE1 < 16) { LDB(i + PRE1); __syncwarp(); LDB(i + PRE1 + 1); __syncwarp(); }
                    if (PRE1 == 8 && i >= 2 && i < 10) { LDB(i + 6); __syncwarp(); LDB(i + 7); __syncwarp(); }
                    if (i == 6) redo = !late(redo ^ (2 * bc + 1), 0, ~0u);
                    if (i == H2) { barrive_if<B_H2, 256>(!redo); CUT(pa); }
                }
                else if (CO) CUT(pa);
                if (i < 2) { a[2 * i][0] = a[2 * i][1] = a[2 * i][2] = a[2 * i][3] = a[2 * i + 1][0] = a[2 * i + 1][1] = a[2 * i + 1][2] = a[2 * i + 1][3] = 0.f; }
                mmaq(a[2 * (i & 1)], &W[8 * i], b[i][0], b[i][1]); mmaq(a[2 * (i & 1) + 1], &W[8 * i + 4], b[i][2], b[i][3]);
            }
            if (__builtin_expect(redo, 0)) { __syncwarp(); continue; }
            CUT(pa); CUT(pb);
            const uint32_t mG = (l16 & 0x1C0) ? 0 : 0x10001u, mT = (l16 & 0x30) ? 0 : 1;
            ST_X();
            barrive<B_H3, 256>();
            CUT(pa);
            PROF(1);
            #pragma unroll
            for (int i = 7; i >= 0; i--) V_MMA(i, 8);
            ST_V();
            CUT(pb);
            bsync<B_VX, 256>();
            PROF(2);
            uint32_t vf[16], vm[16];
            const uint32_t va = opq(pa), vb = opq(va ^ 0x20);
            #define LD_V() do { _Pragma("unroll") for (int i = 0; i < 4; i++) { const uint32_t a_ = TK + 16384 + ((i & 1) ? vb : va) + (i >> 1) * 4096; \
                ldsm4(vf[4 * i], vf[4 * i + 1], vf[4 * i + 2], vf[4 * i + 3], a_); ldsm4(vm[4 * i], vm[4 * i + 1], vm[4 * i + 2], vm[4 * i + 3], a_ + 8192); } } while (0)
            LD_V();
            __syncwarp();
            load_frag<0, WA0>(WO + t16, F);
            #pragma unroll
            for (int i = 0; i < 16; i++) vf[i] = opq(hadd2(vf[i], vm[i]));
            const char* const xa = at(u_x + (t16 >> 1), rbhi) + (8192 - 1024);
            if (VP) CUT(pb);
            DELAY(VD);
            LD_X(vm, 0); LD_X(vm + 8, 4096);
            __syncwarp();
            load_frag<WA0, WA1>(WO + t16, F);
            CUT(pb);
            float x[10];
            bsync<B_S1, 256>();
            tok_scores(x, SC + l16);
            const float mt = opqf(max8(x));
            if (ANN == 3) REPORT(7, 0);
            CUT(pb);
            PROF(3);
            bsync<B_SC, 256>();
            mem_scores(x, SC + l16);
            const float m1 = fmaxf(mt, fmaxf(x[8], x[9]));
            const float m2 = __shfl_xor_sync(~0u, m1, 1), m3 = __shfl_xor_sync(~0u, m1, 2), m4 = __shfl_xor_sync(~0u, m1, 3);
            CUT(pb);
            load_frag<WA1, WA2>(WO + t16, F);
            barrive<B_SC2, 224>();
            uint32_t p[5], vs[4];
            #define SUM_V() do { _Pragma("unroll") for (int i = 0; i < 4; i++) { const int e = (i >> 1) * 4 + (i & 1); vs[i] = hadd2(hadd2(vm[e], vm[e + 8]), hadd2(vm[e + 2], vm[e + 10])); } } while (0)
            CUT(pb);
            const float ms = -SCL * fmaxf(fmaxf(m1, m2), fmaxf(m3, m4));
            PROF(5);
            #pragma unroll
            for (int i = 0; i < 10; i++) x[i] = fmaf(x[i], SCL, ms);
            x[8] = opqf(ex2(x[8])); x[9] = opqf(ex2(x[9]));
            CUT(pb);
            uint32_t badv = late(stale<4, 2>(vm, tau), stale<4, 2>(vm + 8, tau), mT);
            SUM_V();
            #pragma unroll
            for (int i = 0; i < 4; i++) { x[i] = opqf(ex2(x[i])); vs[i] = opq(vs[i]); }
            const uint32_t z0 = t16 >> 16;
            uint32_t one[4] = {opq(ONES | z0), opq(ONES ^ z0), opq(ONES + z0), opq(ONES - z0)};
            CUT(pb);
            #pragma unroll
            for (int i = 4; i < 8; i++) x[i] = ex2(x[i]);
            #pragma unroll
            for (int i = 0; i < 5; i++) p[i] = pack2(x[2 * i], x[2 * i + 1]);
            float sm[4] = {};
            #define PV(also) do { float o[8] = {}; \
                mma8(o, vs[0], vs[1], p[4]); mma8(o + 4, vs[2], vs[3], p[4]); if (also) mma8(sm, one[0], one[1], p[4]); \
                mmaq(o, vf, p[0], p[1]); mmaq(o + 4, vf + 8, p[0], p[1]); if (also) mmaq(sm, one, p[0], p[1]); \
                mmaq(o, vf + 4, p[2], p[3]); mmaq(o + 4, vf + 12, p[2], p[3]); if (also) mmaq(sm, one, p[2], p[3]); \
                stsm4(OB - 2048 + opq(t16), pack2(o[0], o[1]), pack2(o[2], o[3]), pack2(o[4], o[5]), pack2(o[6], o[7])); } while (0)
            PV(true);
            if (w8 == 4) sts64f(SUM + (l16 >> 1), sm[0], sm[1]);
            if (__builtin_expect(badv, 0)) {
                int n_ = 0;
                uint32_t vm[16];
                const char* const xa = at(u_x + (8192 - 1024) + (opq(t16) >> 1), rbhi);
                do { RETRY(3, 1); LD_X(vm, 0); LD_X(vm + 8, 4096); } while (late(stale<4, 2>(vm, tau), stale<4, 2>(vm + 8, tau), mT) && ++n_ < SPIN_LIMIT);
                SUM_V();
                PV(false);
            }
            if (ONE) bsync<B_O2, 256>(); else { barrive<B_O2, 256>(); bsync<B_O, 128>(); }
            PROF(6);
            float i0 = sm[0], i1 = sm[1];
            #define GET_P() if (!ONE) bsync<B_PT, 160>(); lds128u(p, PT + l16); p[4] = lds32(PT + 512 + (l16 >> 2))
            #define TOK_PV() { const uint32_t z = t16 >> 17; one[0] = ONES | z; one[1] = ONES ^ z; one[2] = ONES + z; one[3] = ONES - z; } \
                _Pragma("unroll") for (int i = 0; i < 12; i++) ot[i >> 2][0][i & 3] = ot[i >> 2][1][i & 3] = 0.f; \
                mma8(ot[0][0], vs[0], vs[1], p[4]); mma8(ot[1][0], vs[2], vs[3], p[4]); mma8(ot[2][0], one[0], one[1], p[4]); \
                mmaq(ot[0][1], vf + 4, p[2], p[3]); mmaq(ot[1][1], vf + 12, p[2], p[3]); mmaq(ot[2][1], one, p[2], p[3]); CUT(pa)
            WO_MMA(WA2, WA3, GET_P(), TOK_PV());
            CUT(pa);
            mmaq(ot[0][0], vf, p[0], p[1]); mmaq(ot[1][0], vf + 8, p[0], p[1]); mmaq(ot[2][0], one, p[0], p[1]);
            CUT(pb);
            barrive<B_GO, 256>();
        }
        CUT(pb);
        PROF(7);
        #define PK_O() const float j0 = rcpf(ot[2][0][0] + ot[2][1][0]), j1 = rcpf(ot[2][0][1] + ot[2][1][1]); uint32_t ow[4]; \
            _Pragma("unroll") for (int i = 0; i < 4; i++) \
                ow[i] = opq(pack2((ot[i >> 1][0][2 * (i & 1)] + ot[i >> 1][1][2 * (i & 1)]) * j0, (ot[i >> 1][0][2 * (i & 1) + 1] + ot[i >> 1][1][2 * (i & 1) + 1]) * j1))
        #define ST_O() do { uint32_t* og = (uint32_t*)((char*)g_O + (u_og + (l16 >> 2))); \
            _Pragma("unroll") for (int i = 0; i < 4; i++) og[(i >> 1) * 256 + (i & 1) * 32] = ow[i]; } while (0)
        #define BSO() ((u_bs) ^ ((l16 & 0x10) + ((l16 >> 3) & 0xC) + (l16 & 0x80) * 0x20 + (l16 & 0x100) * 0x80))
        const uint32_t taus = phase(seg);
        const uint64_t* const dq = c_xd + (s & 1) * 32; const uint64_t* const dv = dq + (wg * 16 | (prm.zero & s));
        float acc[16], acv[16];
        uint32_t u[8];
        if constexpr (wg == 0) {
            if (s == NSEG - 1) { bsync<B_GO, 256>(); st_g32(at(BSO(), rbhi), 0); mbar_wait(MB_KV, 0); break; }
            load_frag<16 - EV, 16, 2048>(VEB + t16, T);
            bsync<B_GO, 256>();
            PROF(8);
            wg_run<0, 16 - EV>(acv, T, dv);
            wg_run<16 - EV, 16>(acv, T, dv);
            wg_run<0, 5>(acc, W, dq); wg_wait<1>();
            qk_pack(acv, u);
            #pragma unroll
            for (int i = 0; i < 8; i++) u[i] = opq(u[i]);
            CUT(pa);
            wg_run<5, 8>(acc, W, dq);
            __syncwarp();
            sts128(SC + opq(t16), make_uint4(u[0], u[1], u[2], u[3])); sts128(SC + 2048 + opq(t16), make_uint4(u[4], u[5], u[6], u[7]));
            barrive<B_VX, 256>();
            __syncwarp();
            PROF(9);
            wg_run<8, 12>(acc, W, dq);
            CUT(pa);
            char* const bs = at(opq(BSO()), opq(rbhi));
            CUT(pa);
            wg_run<12, 15>(acc, W, dq);
            CUT(pa);
            const uint32_t ro = opq(l16 * 8 + ((l16 & 0x70) ^ ((w8 & 3) << 5))), ro2 = opq(ro ^ 0x10);
            const uint32_t mG = opq((l16 & 0x1C0) ? 0 : 0x10001u), mB = opq((((l16 >> 2) & 4) + ((l16 >> 5) & 3)) == ((u_bs >> 7) & 7) ? 1 : 0), zz = t16 >> 18;
            CUT(pa);
            wg_run<15, 18>(acc, W, dq);
            CUT(pa);
            const uint32_t one[4] = {opq(ONES | zz), opq(ONES ^ zz), opq(ONES + zz), opq(ONES - zz)};
            const uint32_t par = s & 1, tt = tau * 0x10001u;
            CUT(pa);
            wg_run<18, RP>(acc, W, dq);
            CUT(pa);
            PROF(10);
            mbar_wait(MB_R, par);
            PROF(14);
            uint32_t x[8], bad;
            float d[4][4];
            #define SUM_R() do { ldsm4t(x[0], x[1], x[2], x[3], RS + ro); ldsm4t(x[4], x[5], x[6], x[7], RS + ro2); \
                _Pragma("unroll") for (int i = 0; i < 4; i++) { d[i][0] = d[i][1] = d[i][2] = d[i][3] = 0.f; mmaq(d[i], one, x[2 * i], x[2 * i + 1]); } } while (0)
            #define PUT_B() do { bad = late(stale<2, 1>(x, tt), stale<2, 1>(x + 2, tt), mG); \
                const uint32_t w0 = pack2(d[0][0] + d[1][0], d[0][1] + d[1][1]), w1 = pack2(d[2][0] + d[3][0], d[2][1] + d[3][1]); \
                asm volatile("{ .reg .pred p; setp.eq.b32 p, %2, 0; @p st.relaxed.gpu.global.u32 [%0], %1; }" :: "l"(bs), "r"(tagm((l16 & 0x40) ? w1 : w0, mB, tt)), "r"(bad) : "memory"); } while (0)
            SUM_R();
            CUT(pa);
            wg_run<RP, (RP + RQ < 32 ? RP + RQ : 32)>(acc, W, dq);
            if (RP + RQ >= RL) barrive<B_BT, 256>();
            CUT(pa);
            PUT_B();
            const uint32_t tb = lds32(SUM + 272 + 28 + zz);
            CUT(pa);
            PROF(11);
            if (RP + RQ < RL) { wg_run<RP + RQ, RL>(acc, W, dq); __syncwarp(); barrive<B_BT, 256>(); __syncwarp(); }
            wg_run<(RP + RQ < RL ? RL : RP + RQ), 32>(acc, W, dq);
            CUT(pa);
            AGAIN(5, ld_g128(x, at(u_rl + opq(ro), rbhi)); ld_g128(x + 4, at(u_rl + opq(ro2), rbhi)); sts128(RS + ro, make_uint4(x[0], x[1], x[2], x[3])); sts128(RS + ro2, make_uint4(x[4], x[5], x[6], x[7]));
                     CUT(pa); __syncwarp(); SUM_R(); PUT_B(), bad)
            #define REQ_B() if (w8 == 3) { TRC(13, gtime() - tb); wait_g(tb, t16); GET_B(0); PROFW(13, 3); }
            if (!BL) REQ_B();
            const uint32_t ps = opq(pb & 0xFFFF), ps2 = opq(ps ^ HI8);
            char* const qd0 = TOK_DST() + ps; char* const qd1 = TOK_DST() + ps2;
            TAGM();
            wg_wait<0>();
            pack_tag(acc, u, taus, tm);
            #pragma unroll
            for (int i = 0; i < 8; i++) u[i] = opq(u[i]);
            CUT(pa);
            if (BL) REQ_B();
            bsync<B_S0, 128>();
            st_if(seg < NSEG, qd0, u); st_if(seg < NSEG, qd1, u + 4);
            if (XP == 1) load_x(tmX, c, seg + 1, (s & 1) ? XT : XT2, w8 == 1 && seg + 1 < NSEG);
            PROF(12);
        } else {
            #define LAST() __reduce_max_sync(~0u, max(max(an[0], an[1]), max(an[2], an[3])))
            PK_O();
            CUT(pa);
            if (s == NSEG - 1) { ST_O(); break; }
            PROF(8);
            if (w8 != 7) {
                load_frag<16 - EV, 16 - EV + TA0, 2048>(VEB + t16, T);
                mbar_wait(MB_KV, ~s & 1);
                AGAIN(0, refetch_kv(c, s + 1, w8 - 4, l16), kv_stale(w8 - 4, l16, phase(s + 1)))
            } else {
                uint32_t tr = LAST();
                AGAIN(8, ld_g128(an, at(u_ta + l16, rbhi)); tr = LAST(), late(stale<2, 1>(an, s), stale<2, 1>(an + 2, s), 31))
                tr = (tr & ~31u) + P(0);
                TRC(14, gtime() - tr);
                wait_g(tr, t16);
                if (R4) { for (int i = 0; i < 4; i++) bulk_copy(RS + i * 1024, at(u_rl + i * 1024, rbhi), 1024, MB_R); }
                else bulk_copy(RS, at(u_rl, rbhi), 4096, MB_R);
                PROFW(14, 3);
                if (XP == 3) load_x(tmX, c, seg + 1, (s & 1) ? XT : XT2, seg + 1 < NSEG);
                sts32(SUM + 272 + 28, tr + P(1));
                load_frag<16 - EV, 16 - EV + TA0, 2048>(VEB + t16, T);
            }
            CUT(pa);
            bsync<B_VX, 256>();
            lds128u(u, SC - 2048 + opq(t16)); lds128u(u + 4, SC + opq(t16));
            CUT(pa);
            ST_O();
            CUT(pa);
            load_frag<16 - EV + TA0, 16 - EV + TA, 2048>(VEB + t16, T);
            acc_init(acv, u);
            #pragma unroll
            for (int i = 0; i < 16; i++) acv[i] = opqf(acv[i]);
            const uint32_t ps = opq(pb & 0xFFFF), ps2 = opq(ps ^ HI8);
            CUT(pa);
            PROF(9);
            bsync<B_BT, 256>();
            CUT(pa);
            wg_run<0, 3>(acc, W, dq);
            PROF(11);
            wg_run<3, NT, true>(acc, W, dq);
            __syncwarp();
            load_frag<16 - EV + TA, 16, 2048>(VEB + t16, T);
            __syncwarp();
            wg_run<NT, NB>(acc, W, dq);
            char* const qd0 = TOK_DST() + ps; char* const qd1 = TOK_DST() + ps2;
            TAGM();
            wg_run<NB, 32>(acc, W, dq);
            wg_run<0, 5, true>(acv, T, dv);
            wg_wait<1>();
            PROF(12);
            pack_tag(acc, u, taus, tm);
            #pragma unroll
            for (int i = 0; i < 8; i++) u[i] = opq(u[i]);
            CUT(pa);
            wg_run<5, 16 - EV>(acv, T, dv);
            __syncwarp();
            st_if(seg < NSEG, qd0, u); st_if(seg < NSEG, qd1, u + 4);
            __syncwarp();
            wg_run<16 - EV, 16>(acv, T, dv);
            CUT(pa);
            PROF(10);
            wg_wait<0>();
            PROF(13);
            pack_tag(acv, u, taus, tm);
            if (XP == 2) load_x(tmX, c, seg + 1, (s & 1) ? XT : XT2, w8 == 5 && seg + 1 < NSEG);
            st_if(seg < NSEG, qd0 + 16384, u); st_if(seg < NSEG, qd1 + 16384, u + 4);
        }
        s++;
        u_rs ^= 1 << 20; u_rl ^= 1 << 20; u_bs ^= 1 << 20; u_bl ^= 1 << 20; u_x ^= 1 << 20; u_xs ^= 1 << 20; u_ta ^= 1 << 20; u_rp ^= 1 << 20; u_og += 262144;
    }
}

__device__ __forceinline__ uint32_t round_trips(char* line, int n) {
    uint32_t best[2] = {0xFFFFu, 0xFFFFu};
    #pragma unroll 1
    for (int i = 0; i < n; i++) {
        uint32_t v; const uint32_t t0 = clk();
        asm volatile("atom.relaxed.gpu.global.exch.b32 %0, [%1], %2;" : "=r"(v) : "l"(line + (i & 1) * 4096), "r"(i) : "memory");
        if (v == 0x7FC1A5A5u) g_err = 2;
        const uint32_t dt = clk() - t0;
        if (i & 1) best[1] = min(best[1], dt); else best[0] = min(best[0], dt);
    }
    return (__popc((uint32_t)(uintptr_t)line & HOME_BITS) & 1) ? best[1] | best[0] << 16 : best[0] | best[1] << 16;
}
__device__ __forceinline__ int role(char* rb) {
    const int b = blockIdx.x, t = threadIdx.x;
    if (!(t & 31)) { const int i = b * 8 + (t >> 5); sts32(mk::SUM + (t >> 3), round_trips(rb + RB_P + (i & 31) * 128 + (i >> 5) * 8192, NPR)); }
    __syncthreads();
    if (t == 0) {
        const uint4 x = lds128(mk::SUM), y = lds128(mk::SUM + 16);
        const uint32_t m = __vminu2(__vminu2(__vminu2(x.x, x.y), __vminu2(x.z, x.w)), __vminu2(__vminu2(y.x, y.y), __vminu2(y.z, y.w)));
        uint32_t sm; asm volatile("mov.u32 %0, %%smid;" : "=r"(sm));
        const uint32_t g = sm < 64 ? (sm & 15) >> 1 : 1 + (sm - 64) % 14 / 2, i = sm < 64 ? sm >> 4 : 4 + (sm - 64) / 14;
        const uint32_t pos = sm < 120 ? g * 16 + i * 2 + (sm & 1) : sm + 8;
        st_g32(g_cls + b, 0x80000000u | (m >> 16 < (m & 0xFFFF)) << 24 | pos << 8 | b);
    }
    uint32_t e = ~0u, own;
    int n = 0;
    do { own = ld_g32(g_cls + b); if (t < NCTA) e = ld_g32(g_cls + t); } while (!((e & own) >> 31) && ++n < SPIN_LIMIT);
    const int below = __syncthreads_count(e < own), n0 = __syncthreads_count(!(e >> 24 & 1));
    const int c0 = 4 * min(max(16, 32 - (NCTA - n0) / 4), n0 / 4);
    return below < c0 ? below : below < n0 ? 128 + below - c0 : below - n0 + c0 < 128 ? below - n0 + c0 : below;
}

__global__ void __launch_bounds__(256, 1)
main_kernel(const __grid_constant__ CUtensorMap tmWq, const __grid_constant__ CUtensorMap tmWk, const __grid_constant__ CUtensorMap tmWv,
            const __grid_constant__ CUtensorMap tmWo, const __grid_constant__ CUtensorMap tmX, const bf16* __restrict__ mem0,
            const bf16* Wo, const __grid_constant__ MainParams prm) {
    using namespace mk;
    extern __shared__ __align__(1024) uint8_t smem_raw[];
    if (smem_u32(smem_raw) != SB) __trap();
    TL(2);
    const int tid0 = threadIdx.x, w8 = __shfl_sync(~0u, tid0 >> 5, 0), wg = w8 >> 2;
    asm volatile("griddepcontrol.wait;" ::: "memory");
    const int c = __shfl_sync(~0u, role(prm.rb), 0), kap = c & 1;
    if (c >= 128) return;
    if (tid0 == 0) {
        for (int i = 0; i < 8; i++) mbar_init(BAR + i * 8, 1);
        sts32(SUM + 256, 0); sts32(SUM + 268, 0); mbar_arrive(MB_B);
        asm volatile("fence.mbarrier_init.release.cluster;" ::: "memory");
        asm volatile("fence.proxy.async.shared::cta;" ::: "memory");
        const int col = (c >> 1) * 64, k0 = kap * 512;
        mbar_expect(MB_WQ, 65536); tma2d(WO, &tmWq, col, k0, MB_WQ); tma2d(WO + 32768, &tmWq, col, k0 + 256, MB_WQ);
        mbar_expect(MB_WK, 65536); tma2d(WV, &tmWk, col, k0, MB_WK); tma2d(WV + 32768, &tmWk, col, k0 + 256, MB_WK);
    }
    __syncwarp();
    load_x(&tmX, c, 0, XT, w8 == 0);
    for (int i = tid0; i < 4096; i += 256) {
        const int row = i >> 9, col = i & 511;
        const unsigned short v = __bfloat16_as_ushort(mem0[row * DM + kap * 512 + col]);
        asm volatile("st.shared.u16 [%0], %1;" :: "r"(MEM + col * 16 + row * 2), "h"(v) : "memory");
    }
    asm volatile("fence.proxy.async.shared::cta;" ::: "memory");
    __syncthreads();
    uint32_t W[128], T[64];
    mbar_wait(wg ? MB_WK : MB_WQ, 0);
    load_tile<0, 32>(tile_off(tid0 & 31, 2 * (w8 & 3)) + (wg ? WV : WO), W);
    __syncthreads();
    if (tid0 == 0) {
        mbar_expect(MB_WV, 65536); tma2d(WV, &tmWv, (c >> 1) * 64, kap * 512, MB_WV); tma2d(WV + 32768, &tmWv, (c >> 1) * 64, kap * 512 + 256, MB_WV);
        mbar_expect(MB_WO, 65536);
        for (int i = 0; i < 4; i++) tma2d(WO + i * 16384, &tmWo, (c & 3) * 256 + i * 64, (c >> 2) * DH, MB_WO);
    }
    asm volatile("griddepcontrol.launch_dependents;" ::: "memory");
    uint32_t t16 = tid0 * 16, pa, pb;
    {
        const int lane = tid0 & 31, w = w8 & 3, g = lane >> 2, t = lane & 3;
        auto vec = [](int hf, int gg, int ch) { return hf * 512 + (gg >> 1) * 128 + (gg & 1) * 64 + ((ch ^ (gg >> 1) ^ (hf << 1)) << 4); };
        const int kg = ((lane >> 3) & 1) * 4 + ((lane & 7) >> 1);
        pa = wg ? w * 1024 + vec((lane >> 3) & 1, lane & 7, lane >> 4)
                : ((lane >> 4) * 4096 + w * 1024 + vec(lane & 1, kg, 2 * (w & 1))) | ((lane & 8) * 256 + w * 256 + (lane & 1) * 128 + ((((lane >> 4) ^ (lane & 1)) * 4 + ((lane & 7) >> 1)) << 4)) << 16;
        pb = (wg ? w * 1024 + vec(0, g, t) : t * 4096 + w * 256 + g * 16) | (w * 256 + t * 64 + (g & 3) * 8 + (g >> 2) * 4) << 16;
    }
    mbar_wait(MB_WV, 0);
    load_tile<0, 16>(tile_off(tid0 & 31, 2 * (w8 & 3)) + wg * 32768 + WV, T);
    __syncthreads();
    #pragma unroll
    for (int i = 0; i < 16; i++) sts128(WV + i * 4096 + t16, make_uint4(T[4 * i], T[4 * i + 1], T[4 * i + 2], T[4 * i + 3]));
    int budget = SPIN_LIMIT;
    #pragma unroll 1
    for (int seg = 0; seg < 2; seg++) {
        const uint32_t tau = phase(seg), ps = pb & 0xFFFF;
        float acc[16], acv[16];
        uint32_t u[8];
        mbar_wait(MB_X, seg & 1);
        wg_run<0, 32>(acc, W, c_xd + (prm.zero & seg));
        wg_run<0, 16>(acv, T, c_xd + (wg * 16 | (prm.zero & (seg + 1))));
        wg_wait<0>();
        if (!wg) { qk_pack(acv, u); sts128(SC + t16, make_uint4(u[0], u[1], u[2], u[3])); sts128(SC + 2048 + t16, make_uint4(u[4], u[5], u[6], u[7])); }
        __syncthreads();
        load_x(&tmX, c, seg + 1, XT, w8 == 0);
        if (wg) { lds128u(u, SC - 2048 + t16); lds128u(u + 4, SC + t16); acc_add(acv, u); }
        #pragma unroll 1
        for (int m = 0; m <= wg; m++) {
            TAGM(); pack_tag(acc, u, tau, tm);
            st_if(true, tok_dst(c, seg, wg) + (m * 16384 + ps), u); st_if(true, tok_dst(c, seg, wg) + (m * 16384 + (ps ^ HI8)), u + 4);
            #pragma unroll
            for (int i = 0; i < 16; i++) acc[i] = acv[i];
        }
        __syncthreads();
    }
    {
        mbar_wait(MB_WO, 0);
        const int lane = tid0 & 31;
        const uint32_t a = (tid0 >> 6) * 16384 + tile_off(lane, (w8 & 1) * 4) + WO;
        #pragma unroll
        for (int i = 0; i < 16; i++) ldsm4t(T[4 * i], T[4 * i + 1], T[4 * i + 2], T[4 * i + 3], ((i & 2) ? a ^ 32 : a) + ((i >> 2) + 4 * (i & 1)) * 2048);
        __syncthreads();
        const uint32_t d = WO + w8 * 512 + ((lane >> 3) * 4 + (lane & 3)) * 16 + ((lane >> 2) & 1) * 4;
        #pragma unroll
        for (int i = 0; i < 64; i++) sts32(d + (i >> 2) * 4096 + (i & 1) * 256 + (i & 2) * 4, T[i]);
        load_frag<0, 16>(WV + t16, T);
    }
    uint32_t u_rs, u_rl, u_bs, u_bl;
    const uint32_t rbhi = (uint32_t)((uintptr_t)prm.rb >> 32);
    {
        const int lane = tid0 & 31, h = c >> 2, j = c & 3;
        uint32_t cl;
        const int G = h >> 4, rk = h & 15;
        auto half = [&](uint32_t off) { return (uint32_t)(uintptr_t)prm.rb + off + ((__popc(off & HOME_BITS) ^ G) & 1) * 4096; };
        auto rpair = [&](int m) { return RB_R + (j << 16) + ((m & 1) << 13) + (((m >> 1) & 3) << 14) + ((m >> 3) << 18); };
        u_rs = (half(rpair(2 * w8)) ^ (G << 12)) + h * 128 + (h & 7) * 16;
        u_rl = half(rpair(rk));
        u_bs = (uint32_t)(uintptr_t)prm.rb + RB_B + ((j & 1) << 13) + ((j >> 1) << 16) + rk * 256 + G * 128 + (w8 & 3) * 32;
        u_bl = half(RB_B + (kap << 16));
        if (w8 == 0) {
            const char* v0 = kv_src(c, 0) + 16384 + lane * 128 + (lane & 3) * 4;
            do cl = ld_g32(v0) & ld_g32(v0 + 4096) & ld_g32(v0 + 8192) & ld_g32(v0 + 12288); while (__any_sync(~0u, !(cl & 1)) && --budget > 0);
            get_kv(c, 0);
        }
    }
    mbar_wait(MB_KV, 0);
    if (w8 < 3) while (kv_stale(w8, t16 & 0x1F0, 1) && --budget > 0) refetch_kv(c, 0, w8, t16 & 0x1F0);
    asm volatile("fence.proxy.async.shared::cta;" ::: "memory");
    TLX(7);
    __syncwarp();
    const Ctx cx = {u_rs, u_rl, u_bs, u_bl, (uint32_t)(uintptr_t)prm.rb, rbhi, w8, c};
    if (wg) steps<1>(W, T, t16, pa, pb, cx, &tmX, prm); else steps<0>(W, T, t16, pa, pb, cx, &tmX, prm);
    TLX(3);
}

namespace ck {
constexpr uint32_t U = 0;
constexpr uint32_t UPL = 136 * 16 + 64;
constexpr uint32_t UCH = 2 * UPL;
constexpr uint32_t F = 8 * UCH;
constexpr uint32_t FCP = 4160;
constexpr uint32_t FCH = 2 * FCP;
constexpr uint32_t SK = F + 8 * FCH;
constexpr uint32_t SKP = 257 * 16;
constexpr uint32_t SV = SK + 8 * SKP;
constexpr uint32_t SQ = SV + 32768;
constexpr uint32_t TOTAL = SQ + 32768;
}
__global__ void __launch_bounds__(288, 1)
conv_kernel(const bf16* __restrict__ q, const bf16* __restrict__ k, const bf16* __restrict__ v, const bf16* __restrict__ shift_k,
            const bf16* __restrict__ ssm_k, const bf16* __restrict__ ssm_D, const bf16* __restrict__ gate_w,
            const bf16* Wq, const bf16* Wk, const bf16* Wv, const bf16* Wo,
            const __grid_constant__ CUtensorMap tmWq, const __grid_constant__ CUtensorMap tmWk, const __grid_constant__ CUtensorMap tmWv,
            const __grid_constant__ CUtensorMap tmWo, char* rb) {
    using namespace ck;
    extern __shared__ uint8_t smem_raw[];
    const uint32_t sb = smem_u32(smem_raw);
    const int tid = threadIdx.x, w = tid >> 5, lane = tid & 31, c = blockIdx.x;
    TL(0);
    const int d0 = c * 8, t0 = tid * 8;
    if (w == 8) {
        bsync<1, 288>();
        if (lane < 10) {
            const CUtensorMap* m = lane < 2 ? &tmWq : lane < 4 ? &tmWk : lane < 6 ? &tmWv : &tmWo;
            const int c0 = lane < 6 ? (c >> 1) * 64 : (c & 3) * 256 + (lane - 6) * 64, c1 = lane < 6 ? (c & 1) * 512 + (lane & 1) * 256 : (c >> 2) * DH;
            asm volatile("cp.async.bulk.prefetch.tensor.2d.L2.global [%0, {%1, %2}];" :: "l"(m), "r"(c0), "r"(c1) : "memory");
        }
        return;
    }
    #pragma unroll
    for (int i = 0; i < 8; i++) {
        cpa16(sb + SK + i * SKP + (tid + 1) * 16, k + (size_t)(t0 + i) * DM + d0);
        cpa16(sb + SV + i * 4096 + tid * 16, v + (size_t)(t0 + i) * DM + d0);
    }
    cpa_commit();
    #pragma unroll
    for (int i = 0; i < 8; i++) cpa16(sb + SQ + i * 4096 + tid * 16, q + (size_t)(t0 + i) * DM + d0);
    cpa_commit();
    uint4 fx[8], gw[4], x0[4], x1[4], skr[4];
    const uint4* fp = (const uint4*)(ssm_k + (size_t)(d0 + w) * SEQ);
    #pragma unroll
    for (int i = 0; i < 8; i++) fx[i] = fp[lane + 32 * i];
    const int gr = c * 16 + w * 2;
    #pragma unroll
    for (int i = 0; i < 4; i++) {
        gw[i] = ((const uint4*)gate_w)[lane + 32 * i];
        x0[i] = ((const uint4*)(q + (size_t)gr * DM))[lane + 32 * i];
        x1[i] = ((const uint4*)(q + (size_t)(gr + 1) * DM))[lane + 32 * i];
        skr[i] = ((const uint4*)(shift_k + d0 * 4))[i];
    }
    if (c == 0 && tid < 160) g_cls[tid] = 0;
    if (tid < 128) sts128(sb + U + (tid >> 4) * UCH + ((tid >> 3) & 1) * UPL + (tid & 7) * 16, make_uint4(0, 0, 0, 0));
    else if (tid < 136) sts128(sb + SK + (tid & 7) * SKP, make_uint4(0, 0, 0, 0));
    {
        const uint32_t fb = sb + F + w * FCH;
        if (lane < 8) { sts32(fb + 4128 + lane * 4, 0); if (lane) sts32(fb + FCP + 4128 + lane * 4, 0); }
        #pragma unroll
        for (int i = 0; i < 8; i++) {
            const int vi = lane + 32 * i;
            const uint4 x = fx[i];
            const uint32_t a = __shfl_down_sync(~0u, x.x, 1), b = __shfl_sync(~0u, i < 7 ? fx[i < 7 ? i + 1 : 7].x : 0u, 0);
            const uint32_t nxt = lane == 31 ? b : a;
            const uint32_t ea = fb + (2056 - 8 * vi) * 2;
            sts128(ea, make_uint4(__byte_perm(x.w, 0, 0x1032), __byte_perm(x.z, 0, 0x1032), __byte_perm(x.y, 0, 0x1032), __byte_perm(x.x, 0, 0x1032)));
            sts128(ea + FCP, make_uint4(__byte_perm(nxt, x.w, 0x7610), __byte_perm(x.w, x.z, 0x7610), __byte_perm(x.z, x.y, 0x7610), __byte_perm(x.y, x.x, 0x7610)));
            if (vi == 0) sts32(fb + FCP + 4128, x.x & 0xFFFFu);
        }
    }
    {
        float a0 = 0.f, a1 = 0.f;
        #pragma unroll
        for (int i = 0; i < 16; i++) {
            const uint32_t gg = ((const uint32_t*)gw)[i], u0 = ((const uint32_t*)x0)[i], u1 = ((const uint32_t*)x1)[i];
            a0 = fmaf(bflo(u0), bflo(gg), fmaf(bfhi(u0), bfhi(gg), a0));
            a1 = fmaf(bflo(u1), bflo(gg), fmaf(bfhi(u1), bfhi(gg), a1));
        }
        #pragma unroll
        for (int o = 16; o; o >>= 1) { a0 += __shfl_xor_sync(~0u, a0, o); a1 += __shfl_xor_sync(~0u, a1, o); }
        if (lane < 2) g_gate[gr + lane] = 1.f / (1.f + __expf(lane ? -a1 : -a0));
    }
    cpa_wait();
    bsync<1, 288>();
    TLX(14);
    const uint4 dd = *(const uint4*)(ssm_D + d0);
    {
        uint4 kr[11], vr[8];
        #pragma unroll
        for (int i = 0; i < 11; i++) kr[i] = lds128(sb + SK + ((i + 5) & 7) * SKP + (tid + (i >= 3)) * 16);
        #pragma unroll
        for (int i = 0; i < 8; i++) vr[i] = lds128(sb + SV + i * 4096 + tid * 16);
        #pragma unroll
        for (int ch = 0; ch < 8; ch++) {
            const uint32_t s01 = ((const uint32_t*)skr)[2 * ch], s23 = ((const uint32_t*)skr)[2 * ch + 1];
            const float sk[4] = {bflo(s01), bfhi(s01), bflo(s23), bfhi(s23)};
            float kf[11], kv[8];
            #pragma unroll
            for (int i = 0; i < 11; i++) { const uint32_t wd = ((const uint32_t*)&kr[i])[ch >> 1]; kf[i] = (ch & 1) ? bfhi(wd) : bflo(wd); }
            #pragma unroll
            for (int i = 0; i < 8; i++) {
                const uint32_t wv = ((const uint32_t*)&vr[i])[ch >> 1];
                kv[i] = fmaf(kf[i + 3], sk[0], fmaf(kf[i + 2], sk[1], fmaf(kf[i + 1], sk[2], kf[i] * sk[3]))) * ((ch & 1) ? bfhi(wv) : bflo(wv));
            }
            sts128(sb + U + ch * UCH + (tid & 1) * UPL + (8 + (tid >> 1)) * 16,
                   make_uint4(pack2(kv[0], kv[1]), pack2(kv[2], kv[3]), pack2(kv[4], kv[5]), pack2(kv[6], kv[7])));
        }
    }
    bsync<2, 256>();
    TL(9);
    {
        const int g = lane >> 2, t = lane & 3;
        float acc[16][4];
        #pragma unroll
        for (int i = 0; i < 16; i++) acc[i][0] = acc[i][1] = acc[i][2] = acc[i][3] = 0.f;
        const uint32_t fa = sb + F + w * FCH + ((g & 1) ? (2063 - g + 2 * t) * 2 : FCP + (2064 - g + 2 * t) * 2);
        const uint32_t ua = sb + U + w * UCH + ((lane >> 3) & 1) * UPL + (8 + (lane >> 4) * 8 + (lane & 7)) * 16;
        #pragma unroll 1
        for (int r = 0; r < 8; r++) {
            uint32_t Fr[32];
            #pragma unroll
            for (int m = 0; m < 8; m++) ldsm4(Fr[4 * m], Fr[4 * m + 1], Fr[4 * m + 2], Fr[4 * m + 3], ua - r * 16 + m * 256);
            #pragma unroll
            for (int qq = 0; qq < 16; qq++) {
                const uint32_t o = fa - r * 32 - qq * 256;
                const uint32_t f0 = lds32(o), fp8 = lds32(o - 16), fm8 = lds32(o + 16);
                #pragma unroll
                for (int nt = qq; nt < 16; nt++) mma16(acc[nt], f0, fp8, fm8, f0, Fr[2 * (nt - qq)], Fr[2 * (nt - qq) + 1]);
            }
        }
        __syncwarp();
        const uint32_t ya = sb + F + w * FCH + ((lane >> 3) & 1) * 2048 + ((lane >> 4) * 8 + (lane & 7)) * 16;
        #pragma unroll
        for (int nt = 0; nt < 16; nt += 2)
            stsm4t(ya + nt * 128, pack2(acc[nt][0], acc[nt][1]), pack2(acc[nt][2], acc[nt][3]), pack2(acc[nt + 1][0], acc[nt + 1][1]), pack2(acc[nt + 1][2], acc[nt + 1][3]));
    }
    TL(11);
    bsync<2, 256>();
    {
        uint32_t outw[8][4];
        uint4 qr[8];
        #pragma unroll
        for (int i = 0; i < 8; i++) qr[i] = lds128(sb + SQ + i * 4096 + tid * 16);
        #pragma unroll
        for (int cp = 0; cp < 4; cp++) {
            const uint4 y0 = lds128(sb + F + (2 * cp) * FCH + (tid & 1) * 2048 + (tid >> 1) * 16), y1 = lds128(sb + F + (2 * cp + 1) * FCH + (tid & 1) * 2048 + (tid >> 1) * 16);
            const uint4 u0 = lds128(sb + U + (2 * cp) * UCH + (tid & 1) * UPL + (8 + (tid >> 1)) * 16), u1 = lds128(sb + U + (2 * cp + 1) * UCH + (tid & 1) * UPL + (8 + (tid >> 1)) * 16);
            const uint32_t dw = ((const uint32_t*)&dd)[cp];
            const float D0 = bflo(dw), D1 = bfhi(dw);
            #pragma unroll
            for (int i = 0; i < 8; i++) {
                const uint32_t a0 = ((const uint32_t*)&y0)[i >> 1], a1 = ((const uint32_t*)&y1)[i >> 1], b0 = ((const uint32_t*)&u0)[i >> 1], b1 = ((const uint32_t*)&u1)[i >> 1];
                const float yy0 = fmaf((i & 1) ? bfhi(b0) : bflo(b0), D0, (i & 1) ? bfhi(a0) : bflo(a0));
                const float yy1 = fmaf((i & 1) ? bfhi(b1) : bflo(b1), D1, (i & 1) ? bfhi(a1) : bflo(a1));
                const uint32_t qw = ((const uint32_t*)&qr[i])[cp];
                outw[i][cp] = pack2(bflo(qw) * yy0, bfhi(qw) * yy1);
            }
        }
        #pragma unroll
        for (int i = 0; i < 8; i++) g_A[c * 2048 + i * 256 + tid] = make_uint4(outw[i][0], outw[i][1], outw[i][2], outw[i][3]);
    }
    TL(1);
}

namespace ok {
constexpr int STAGES = 4;
constexpr uint32_t STG = 49152, TOTAL = STAGES * STG + 32768 + 256;
}
#define R8(o) F4(d, o), F4(d, o + 4)
__device__ __forceinline__ void wgmma_n256_ss_tt(float* d, uint64_t da, uint64_t db, int accum) {
    asm volatile("{.reg .pred p; setp.ne.b32 p, %130, 0;\n"
        "wgmma.mma_async.sync.aligned.m64n256k16.f32.bf16.bf16 {%0,%1,%2,%3,%4,%5,%6,%7,%8,%9,%10,%11,%12,%13,%14,%15,"
        "%16,%17,%18,%19,%20,%21,%22,%23,%24,%25,%26,%27,%28,%29,%30,%31,%32,%33,%34,%35,%36,%37,%38,%39,%40,%41,%42,%43,%44,%45,%46,%47,"
        "%48,%49,%50,%51,%52,%53,%54,%55,%56,%57,%58,%59,%60,%61,%62,%63,%64,%65,%66,%67,%68,%69,%70,%71,%72,%73,%74,%75,%76,%77,%78,%79,"
        "%80,%81,%82,%83,%84,%85,%86,%87,%88,%89,%90,%91,%92,%93,%94,%95,%96,%97,%98,%99,%100,%101,%102,%103,%104,%105,%106,%107,%108,%109,%110,%111,"
        "%112,%113,%114,%115,%116,%117,%118,%119,%120,%121,%122,%123,%124,%125,%126,%127}, %128, %129, p, 1, 1, 1, 1;}"
        : R8(0), R8(8), R8(16), R8(24), R8(32), R8(40), R8(48), R8(56), R8(64), R8(72), R8(80), R8(88), R8(96), R8(104), R8(112), R8(120)
        : "l"(da), "l"(db), "r"(accum));
}
#undef R8
__global__ void __cluster_dims__(2, 1, 1) __launch_bounds__(288, 1)
out_kernel(const __grid_constant__ CUtensorMap tmO, const __grid_constant__ CUtensorMap tmWo, const __grid_constant__ CUtensorMap tmA,
           const __grid_constant__ CUtensorMap tmOut, const __grid_constant__ MainParams prm) {
    using namespace ok;
    extern __shared__ __align__(1024) uint8_t smem_raw[];
    const uint32_t SB = smem_u32(smem_raw), AT = SB + STAGES * STG, BAR = AT + 32768;
    if (SB & 1023) __trap();
    const int tid = threadIdx.x, w = tid >> 5, lane = tid & 31;
    const int rank = blockIdx.x & 1, mt = blockIdx.x >> 3, nt = (blockIdx.x >> 1) & 3;
    const uint32_t full = BAR, empty = BAR + 64, afull = BAR + 128;
    if (tid == 0) {
        for (int i = 0; i < STAGES; i++) { mbar_init(full + i * 8, 1); mbar_init(empty + i * 8, 8); }
        mbar_init(afull, 1);
        asm volatile("fence.mbarrier_init.release.cluster;" ::: "memory");
    }
    __syncthreads();
    asm volatile("griddepcontrol.wait;" ::: "memory");
    TL(4);
    if (w == 8) {
        if (lane == 0) {
            int st = 0, ph = 1;
            for (int kb = 0; kb < 32; kb++) {
                if (kb >= STAGES) mbar_wait(empty + st * 8, ph);
                mbar_expect(full + st * 8, STG);
                tma3d(SB + st * STG, &tmO, 0, (rank * 32 + kb) * 2, mt * 16, full + st * 8);
                tma3d(SB + st * STG + 16384, &tmWo, 0, (rank * 32 + kb) * 64, nt * 4, full + st * 8);
                if (kb == STAGES - 1) { mbar_expect(afull, 32768); tma3d(AT, &tmA, mt * 128, 0, (nt * 2 + rank) * 16, afull); }
                if (++st == STAGES) { st = 0; ph ^= 1; }
            }
        }
        __syncwarp();
        asm volatile("barrier.cluster.arrive.aligned; barrier.cluster.wait.aligned;" ::: "memory");
        asm volatile("barrier.cluster.arrive.aligned; barrier.cluster.wait.aligned;" ::: "memory");
    } else {
        const int wg = w >> 2, g = lane >> 2;
        float acc[128];
        const int tok0 = 32 * (4 * mt + (w >> 1)) + 8 * (g >> 1) + 4 * (w & 1) + (g & 1);
        const float g0 = g_gate[tok0], g1 = g_gate[tok0 + 2];
        int st = 0, ph = 0, pst = 0;
        #pragma unroll 1
        for (int kb = 0; kb < 32; kb++) {
            mbar_wait(full + st * 8, ph);
            const uint64_t da = mkdesc(SB + st * STG + wg * 8192, 128, 1024, 0), db = mkdesc(SB + st * STG + 16384, 8192, 1024, 1);
            wg_fence();
            #pragma unroll
            for (int ks = 0; ks < 4; ks++) wgmma_n256_ss_tt(acc, da + ks * 16, db + ks * 128, (kb | ks) != 0);
            wg_commit();
            wg_wait<1>();
            if (kb > 0 && lane == 0) mbar_arrive(empty + pst * 8);
            pst = st;
            if (++st == STAGES) { st = 0; ph ^= 1; }
        }
        wg_wait<0>();
        TLX(12);
        asm volatile("barrier.cluster.arrive.aligned; barrier.cluster.wait.aligned;" ::: "memory");
        uint32_t peer;
        asm volatile("mapa.shared::cluster.u32 %0, %1, %2;" : "=r"(peer) : "r"(SB + 65536 + tid * 16), "r"(rank ^ 1));
        #define SND(e) pack2(rank ? acc[8 * i + (e)] : acc[64 + 8 * i + (e)], rank ? acc[8 * i + (e) + 1] : acc[65 + 8 * i + (e)])
        #pragma unroll
        for (int i = 0; i < 8; i++)
            asm volatile("st.shared::cluster.v4.b32 [%0], {%1,%2,%3,%4};" :: "r"(peer + i * 4096), "r"(SND(0)), "r"(SND(2)), "r"(SND(4)), "r"(SND(6)) : "memory");
        #undef SND
        asm volatile("barrier.cluster.arrive.aligned; barrier.cluster.wait.aligned;" ::: "memory");
        mbar_wait(afull, 0);
        const float h0 = 1.f - g0, h1 = 1.f - g1;
        const uint32_t la = AT + (lane >> 4) * 2048 + (4 * (w & 1) + 2 * ((lane >> 3) & 1) + (lane & 1)) * 256 + (4 * (w >> 1) + ((lane & 7) >> 1)) * 16;
        const uint32_t ra = SB + (w * 16 + (lane & 15)) * 128;
        #pragma unroll
        for (int i = 0; i < 8; i++) {
            const uint32_t a = ra + (i >> 2) * 16384 + ((((i & 3) * 2 + (lane >> 4)) ^ (lane & 7)) << 4);
            uint32_t r0, r1, r2, r3;
            ldsm4(r0, r1, r2, r3, la + i * 4096);
            const uint4 u = lds128(SB + 65536 + tid * 16 + i * 4096);
            float p[8];
            #pragma unroll
            for (int e = 0; e < 8; e++) { const uint32_t x = ((const uint32_t*)&u)[e >> 1]; p[e] = (rank ? acc[64 + 8 * i + e] : acc[8 * i + e]) + ((e & 1) ? bfhi(x) : bflo(x)); }
            stsm4(a, pack2(fmaf(g0, bflo(r0), h0 * p[0]), fmaf(g0, bfhi(r0), h0 * p[1])), pack2(fmaf(g1, bflo(r1), h1 * p[2]), fmaf(g1, bfhi(r1), h1 * p[3])),
                     pack2(fmaf(g0, bflo(r2), h0 * p[4]), fmaf(g0, bfhi(r2), h0 * p[5])), pack2(fmaf(g1, bflo(r3), h1 * p[6]), fmaf(g1, bfhi(r3), h1 * p[7])));
        }
        asm volatile("fence.proxy.async.shared::cta;" ::: "memory");
        bsync<1, 256>();
        if (tid == 0) {
            for (int hf = 0; hf < 2; hf++)
                asm volatile("cp.async.bulk.tensor.5d.global.shared::cta.bulk_group [%0, {%2, %3, %3, %3, %4}], [%1];"
                    :: "l"(&tmOut), "r"(SB + hf * 16384), "r"(nt * 256 + rank * 128 + hf * 64), "r"(0), "r"(mt * 4) : "memory");
            asm volatile("cp.async.bulk.commit_group;" ::: "memory");
            asm volatile("cp.async.bulk.wait_group 0;" ::: "memory");
        }
        TL(5);
    }
}

typedef CUresult (*EncodeFn)(CUtensorMap*, CUtensorMapDataType, cuuint32_t, void*, const cuuint64_t*, const cuuint64_t*, const cuuint32_t*,
                             const cuuint32_t*, CUtensorMapInterleave, CUtensorMapSwizzle, CUtensorMapL2promotion, CUtensorMapFloatOOBfill);
static void enc(EncodeFn fn, CUtensorMap* m, void* base, int rank, const cuuint64_t* dims, const cuuint64_t* strides, const cuuint32_t* box, CUtensorMapSwizzle sw) {
    cuuint32_t es[5] = {1, 1, 1, 1, 1};
    fn(m, CU_TENSOR_MAP_DATA_TYPE_BFLOAT16, rank, base, dims, strides, box, es, CU_TENSOR_MAP_INTERLEAVE_NONE, sw,
       CU_TENSOR_MAP_L2_PROMOTION_L2_128B, CU_TENSOR_MAP_FLOAT_OOB_FILL_NONE);
}
static MainParams h_prm = {{768, 512, 512, 0, 0, 0, 0, 0, 0, 0, 0, 0}, 0, nullptr};

extern "C" void kernel_launch(void* const* d_in, const int* in_sizes, int n_in, void* d_out, int out_size) {
    const bf16* q = (const bf16*)d_in[0];
    const bf16* k = (const bf16*)d_in[1];
    const bf16* v = (const bf16*)d_in[2];
    const bf16* shift_k = (const bf16*)d_in[3];
    const bf16* ssm_k = (const bf16*)d_in[4];
    const bf16* ssm_D = (const bf16*)d_in[5];
    const bf16* mem0 = (const bf16*)d_in[7];
    const bf16* gate_w = (const bf16*)d_in[13];

    static EncodeFn fn = nullptr;
    static void* pO = nullptr;
    static void* pA = nullptr;
    if (!fn) {
        cudaDriverEntryPointQueryResult qr;
        cudaGetDriverEntryPoint("cuTensorMapEncodeTiled", (void**)&fn, cudaEnableDefault, &qr);
        cudaGetSymbolAddress(&pO, g_O);
        cudaGetSymbolAddress(&pA, g_A);
        void* pRB; cudaGetSymbolAddress(&pRB, g_RB);
        h_prm.rb = (char*)(((uintptr_t)pRB + (4u << 20) - 1) & ~(uintptr_t)((4u << 20) - 1));
        cudaFuncSetAttribute(main_kernel, cudaFuncAttributeMaxDynamicSharedMemorySize, mk::TOTAL);
        cudaFuncSetAttribute(conv_kernel, cudaFuncAttributeMaxDynamicSharedMemorySize, ck::TOTAL);
        cudaFuncSetAttribute(out_kernel, cudaFuncAttributeMaxDynamicSharedMemorySize, ok::TOTAL);
    }
    CUtensorMap mWq, mWk, mWv, mWo, mX, mO, mWo2, mA, mOut;
    {
        cuuint64_t d[2] = {4096, 1024}, s[1] = {8192}; cuuint32_t b[2] = {64, 256};
        enc(fn, &mWq, d_in[8], 2, d, s, b, CU_TENSOR_MAP_SWIZZLE_128B);
        enc(fn, &mWk, d_in[9], 2, d, s, b, CU_TENSOR_MAP_SWIZZLE_128B);
        enc(fn, &mWv, d_in[10], 2, d, s, b, CU_TENSOR_MAP_SWIZZLE_128B);
    }
    {
        cuuint64_t d[2] = {1024, 4096}, s[1] = {2048}; cuuint32_t b[2] = {64, 128};
        enc(fn, &mWo, d_in[11], 2, d, s, b, CU_TENSOR_MAP_SWIZZLE_128B);
        cuuint64_t d2[3] = {64, 4096, 16}, s2[2] = {2048, 128}; cuuint32_t b2[3] = {64, 64, 4};
        enc(fn, &mWo2, d_in[11], 3, d2, s2, b2, CU_TENSOR_MAP_SWIZZLE_128B);
    }
    {
        cuuint64_t d[3] = {64, 2048, 16}, s[2] = {2048, 128}; cuuint32_t b[3] = {64, 32, 8};
        enc(fn, &mX, d_in[0], 3, d, s, b, CU_TENSOR_MAP_SWIZZLE_128B);
    }
    {
        cuuint64_t d[3] = {256, 128, 256}, s[2] = {512, 65536}; cuuint32_t b[3] = {256, 2, 16};
        enc(fn, &mO, pO, 3, d, s, b, CU_TENSOR_MAP_SWIZZLE_NONE);
    }
    {
        cuuint64_t d[5] = {1024, 2, 4, 4, 64}, s[4] = {2048, 16384, 4096, 65536}; cuuint32_t b[5] = {64, 2, 4, 4, 4};
        cuuint64_t da[3] = {2048, 8, 128}, sa[2] = {4096, 32768}; cuuint32_t ba[3] = {128, 8, 16};
        enc(fn, &mA, pA, 3, da, sa, ba, CU_TENSOR_MAP_SWIZZLE_NONE);
        enc(fn, &mOut, d_out, 5, d, s, b, CU_TENSOR_MAP_SWIZZLE_128B);
    }
    cudaStream_t st = cudaStreamPerThread;
    conv_kernel<<<128, 288, ck::TOTAL, st>>>(q, k, v, shift_k, ssm_k, ssm_D, gate_w, (const bf16*)d_in[8], (const bf16*)d_in[9],
                                             (const bf16*)d_in[10], (const bf16*)d_in[11], mWq, mWk, mWv, mWo, h_prm.rb);
    cudaLaunchAttribute at[1];
    at[0].id = cudaLaunchAttributeProgrammaticStreamSerialization;
    at[0].val.programmaticStreamSerializationAllowed = 1;
    cudaLaunchConfig_t cfg = {};
    cfg.stream = st; cfg.attrs = at; cfg.numAttrs = PDL;
    cfg.gridDim = dim3(NCTA); cfg.blockDim = dim3(256); cfg.dynamicSmemBytes = mk::TOTAL;
    cudaLaunchKernelEx(&cfg, main_kernel, mWq, mWk, mWv, mWo, mX, mem0, (const bf16*)d_in[11], h_prm);
    cfg.gridDim = dim3(128); cfg.blockDim = dim3(288); cfg.dynamicSmemBytes = ok::TOTAL;
    cudaLaunchKernelEx(&cfg, out_kernel, mO, mWo2, mA, mOut, h_prm);
}
```

```cpp
#include <cuda_runtime.h>
#include <cuda_bf16.h>
#include <cuda.h>
#include <stdint.h>

typedef __nv_bfloat16 bf16;

constexpr int SEQ = 2048, DM = 1024, NH = 32, DH = 128, NSEG = 64;
constexpr int SPIN_LIMIT = 1 << 13, NCTA = 132;
#define NPR 2
#define RF 0
#define CC 1
#define XDL 10
#define NSP 16
#define XPF 2
#define FRONT __forceinline__
#define PDL 1
#define TPF 1

constexpr uint32_t HOME_BITS = 0xB3000;
constexpr uint32_t RB_R = 0;
constexpr uint32_t RB_B = 0x80000;
constexpr uint32_t RB_T = RB_B + 0x4000;
constexpr uint32_t RB_P = RB_B + 0x20000;
constexpr uint32_t RB_X = 2u << 20;
__device__ uint4 g_RB[(8 << 20) / 16];
__device__ uint32_t g_cls[160];
__device__ uint4 g_T[2 * NH * 3072];
__device__ uint4 g_O[NSEG * 4 * 4096];
__device__ uint4 g_Y[SEQ * DM / 8];
__device__ float g_gate[SEQ];
__device__ uint32_t g_err;
#define TL(i) do {} while (0)
#define TLX(i)

__device__ __forceinline__ uint32_t smem_u32(const void* p) { return (uint32_t)__cvta_generic_to_shared(p); }
__device__ __forceinline__ uint32_t clk() { uint32_t c; asm volatile("mov.u32 %0, %%clock;" : "=r"(c) :: "memory"); return c; }
__device__ __forceinline__ void ldsm4(uint32_t& r0, uint32_t& r1, uint32_t& r2, uint32_t& r3, uint32_t a) {
    asm volatile("ldmatrix.sync.aligned.m8n8.x4.shared.b16 {%0,%1,%2,%3}, [%4];" : "=r"(r0), "=r"(r1), "=r"(r2), "=r"(r3) : "r"(a) : "memory");
}
__device__ __forceinline__ void ldsm4t(uint32_t& r0, uint32_t& r1, uint32_t& r2, uint32_t& r3, uint32_t a) {
    asm volatile("ldmatrix.sync.aligned.m8n8.x4.trans.shared.b16 {%0,%1,%2,%3}, [%4];" : "=r"(r0), "=r"(r1), "=r"(r2), "=r"(r3) : "r"(a) : "memory");
}
__device__ __forceinline__ void ldsm2(uint32_t& r0, uint32_t& r1, uint32_t a) {
    asm volatile("ldmatrix.sync.aligned.m8n8.x2.shared.b16 {%0,%1}, [%2];" : "=r"(r0), "=r"(r1) : "r"(a) : "memory");
}
__device__ __forceinline__ void stsm4t(uint32_t a, uint32_t r0, uint32_t r1, uint32_t r2, uint32_t r3) {
    asm volatile("stmatrix.sync.aligned.m8n8.x4.trans.shared.b16 [%0], {%1,%2,%3,%4};" :: "r"(a), "r"(r0), "r"(r1), "r"(r2), "r"(r3) : "memory");
}
__device__ __forceinline__ void mma16(float* c, uint32_t a0, uint32_t a1, uint32_t a2, uint32_t a3, uint32_t b0, uint32_t b1) {
    asm volatile("mma.sync.aligned.m16n8k16.row.col.f32.bf16.bf16.f32 {%0,%1,%2,%3}, {%4,%5,%6,%7}, {%8,%9}, {%0,%1,%2,%3};"
        : "+f"(c[0]), "+f"(c[1]), "+f"(c[2]), "+f"(c[3]) : "r"(a0), "r"(a1), "r"(a2), "r"(a3), "r"(b0), "r"(b1));
}
__device__ __forceinline__ void mma8(float* c, uint32_t a0, uint32_t a1, uint32_t b0) {
    asm volatile("mma.sync.aligned.m16n8k8.row.col.f32.bf16.bf16.f32 {%0,%1,%2,%3}, {%4,%5}, {%6}, {%0,%1,%2,%3};"
        : "+f"(c[0]), "+f"(c[1]), "+f"(c[2]), "+f"(c[3]) : "r"(a0), "r"(a1), "r"(b0));
}
__device__ __forceinline__ uint32_t pack2(float lo, float hi) {
    uint32_t r; asm("cvt.rn.bf16x2.f32 %0, %1, %2;" : "=r"(r) : "f"(hi), "f"(lo)); return r;
}
__device__ __forceinline__ uint32_t hadd2(uint32_t a, uint32_t b) {
    uint32_t r; asm("add.rn.bf16x2 %0, %1, %2;" : "=r"(r) : "r"(a), "r"(b)); return r;
}
__device__ __forceinline__ float bflo(uint32_t w) { return __uint_as_float(w << 16); }
__device__ __forceinline__ float bfhi(uint32_t w) { return __uint_as_float(w & 0xFFFF0000u); }
__device__ __forceinline__ void st_g32(void* p, uint32_t v) { asm volatile("st.relaxed.gpu.global.u32 [%0], %1;" :: "l"(p), "r"(v) : "memory"); }
__device__ __forceinline__ void st_g128(void* p, uint32_t a, uint32_t b, uint32_t c, uint32_t d) {
    asm volatile("st.relaxed.gpu.global.v4.u32 [%0], {%1,%2,%3,%4};" :: "l"(p), "r"(a), "r"(b), "r"(c), "r"(d) : "memory");
}
__device__ __forceinline__ uint4 lds128(uint32_t a) { uint4 v; asm volatile("ld.shared.v4.u32 {%0,%1,%2,%3}, [%4];" : "=r"(v.x), "=r"(v.y), "=r"(v.z), "=r"(v.w) : "r"(a) : "memory"); return v; }
__device__ __forceinline__ void sts128(uint32_t a, uint4 v) { asm volatile("st.shared.v4.u32 [%0], {%1,%2,%3,%4};" :: "r"(a), "r"(v.x), "r"(v.y), "r"(v.z), "r"(v.w) : "memory"); }
__device__ __forceinline__ float2 lds64f(uint32_t a) { float2 v; asm volatile("ld.shared.v2.f32 {%0,%1}, [%2];" : "=f"(v.x), "=f"(v.y) : "r"(a) : "memory"); return v; }
__device__ __forceinline__ void sts64f(uint32_t a, float x, float y) { asm volatile("st.shared.v2.f32 [%0], {%1,%2};" :: "r"(a), "f"(x), "f"(y) : "memory"); }
__device__ __forceinline__ void sts32f(uint32_t a, float x) { asm volatile("st.shared.f32 [%0], %1;" :: "r"(a), "f"(x) : "memory"); }
__device__ __forceinline__ void sts32(uint32_t a, uint32_t x) { asm volatile("st.shared.u32 [%0], %1;" :: "r"(a), "r"(x) : "memory"); }
__device__ __forceinline__ uint32_t lds32(uint32_t a) { uint32_t v; asm volatile("ld.shared.u32 %0, [%1];" : "=r"(v) : "r"(a) : "memory"); return v; }
__device__ __forceinline__ void cpa16(uint32_t dst, const void* src) { asm volatile("cp.async.cg.shared.global [%0], [%1], 16;" :: "r"(dst), "l"(src) : "memory"); }
__device__ __forceinline__ void cpa_commit() { asm volatile("cp.async.commit_group;" ::: "memory"); }
__device__ __forceinline__ void cpa_wait() { asm volatile("cp.async.wait_all;" ::: "memory"); }
template <int ID, int N> __device__ __forceinline__ void bsync() { asm volatile("bar.sync %0, %1;" :: "n"(ID), "n"(N) : "memory"); }
template <int ID, int N> __device__ __forceinline__ void barrive() { asm volatile("bar.arrive %0, %1;" :: "n"(ID), "n"(N) : "memory"); }
template <int ID, int N> __device__ __forceinline__ void bsync_if(bool on) { asm volatile("{ .reg .pred p; setp.ne.b32 p, %2, 0; @p bar.sync %0, %1; }" :: "n"(ID), "n"(N), "r"((int)on) : "memory"); }
template <int ID, int N> __device__ __forceinline__ void barrive_if(bool on) { asm volatile("{ .reg .pred p; setp.ne.b32 p, %2, 0; @p bar.arrive %0, %1; }" :: "n"(ID), "n"(N), "r"((int)on) : "memory"); }
template <int ID> __device__ __forceinline__ uint32_t any128(uint32_t x) {
    uint32_t r; asm volatile("{ .reg .pred p; setp.ne.b32 p, %1, 0; bar.red.or.pred p, %2, 128, p; selp.u32 %0, 1, 0, p; }" : "=r"(r) : "r"(x), "n"(ID) : "memory"); return r;
}
__device__ __forceinline__ bool elect() {
    uint32_t p; asm volatile("{ .reg .pred p; elect.sync _|p, 0xFFFFFFFF; selp.u32 %0, 1, 0, p; }" : "=r"(p)); return p;
}
__device__ __forceinline__ void mbar_init(uint32_t mb, uint32_t n) { asm volatile("mbarrier.init.shared::cta.b64 [%0], %1;" :: "r"(mb), "r"(n) : "memory"); }
__device__ __forceinline__ void mbar_expect(uint32_t mb, uint32_t bytes) { asm volatile("mbarrier.arrive.expect_tx.shared::cta.b64 _, [%0], %1;" :: "r"(mb), "r"(bytes) : "memory"); }
__device__ __forceinline__ void mbar_arrive(uint32_t mb) { asm volatile("mbarrier.arrive.shared::cta.b64 _, [%0];" :: "r"(mb) : "memory"); }
__device__ __forceinline__ void mbar_wait(uint32_t mb, uint32_t ph) {
    asm volatile("{ .reg .pred p; .reg .u32 n; mov.u32 n, 0;\n"
                 "MW_%=: mbarrier.try_wait.parity.shared::cta.b64 p, [%0], %1; add.u32 n, n, 1; setp.lt.and.u32 p, n, %2, !p; @p bra.uni MW_%=; }"
                 :: "r"(mb), "r"(ph), "n"(SPIN_LIMIT) : "memory");
}
__device__ __forceinline__ void tma2d(uint32_t dst, const CUtensorMap* m, int c0, int c1, uint32_t mb) {
    asm volatile("cp.async.bulk.tensor.2d.shared::cluster.global.mbarrier::complete_tx::bytes [%0], [%1, {%3, %4}], [%2];"
        :: "r"(dst), "l"(m), "r"(mb), "r"(c0), "r"(c1) : "memory");
}
__device__ __forceinline__ void tma3d(uint32_t dst, const CUtensorMap* m, int c0, int c1, int c2, uint32_t mb) {
    asm volatile("cp.async.bulk.tensor.3d.shared::cluster.global.mbarrier::complete_tx::bytes [%0], [%1, {%3, %4, %5}], [%2];"
        :: "r"(dst), "l"(m), "r"(mb), "r"(c0), "r"(c1), "r"(c2) : "memory");
}
__device__ __forceinline__ void bulk_ld(uint32_t dst, const void* src, uint32_t bytes, uint32_t mb) {
    asm volatile("cp.async.bulk.shared::cluster.global.mbarrier::complete_tx::bytes [%0], [%1], %2, [%3];" :: "r"(dst), "l"(src), "r"(bytes), "r"(mb) : "memory");
}
__device__ __forceinline__ uint64_t mkdesc(uint32_t addr, uint32_t lbo, uint32_t sbo, uint32_t swz) {
    return (uint64_t)((addr & 0x3FFFF) >> 4) | ((uint64_t)(lbo >> 4) << 16) | ((uint64_t)(sbo >> 4) << 32) | ((uint64_t)swz << 62);
}
__device__ __forceinline__ void wg_fence() { asm volatile("wgmma.fence.sync.aligned;" ::: "memory"); }
__device__ __forceinline__ void wg_commit() { asm volatile("wgmma.commit_group.sync.aligned;" ::: "memory"); }
template <int N> __device__ __forceinline__ void wg_wait() { asm volatile("wgmma.wait_group.sync.aligned %0;" :: "n"(N) : "memory"); }
#define F4(d, o) "+f"(d[o]), "+f"(d[o + 1]), "+f"(d[o + 2]), "+f"(d[o + 3])
__device__ __forceinline__ void wgmma_n32_rs(float* d, const uint32_t* a, uint64_t db, int accum) {
    asm volatile("{.reg .pred p; setp.ne.b32 p, %21, 0;\n"
        "wgmma.mma_async.sync.aligned.m64n32k16.f32.bf16.bf16 {%0,%1,%2,%3,%4,%5,%6,%7,%8,%9,%10,%11,%12,%13,%14,%15}, {%16,%17,%18,%19}, %20, p, 1, 1, 0;}"
        : F4(d, 0), F4(d, 4), F4(d, 8), F4(d, 12) : "r"(a[0]), "r"(a[1]), "r"(a[2]), "r"(a[3]), "l"(db), "r"(accum));
}
__device__ __forceinline__ void wait_until(uint32_t tgt, uint32_t any) {
    asm volatile("{ .reg .pred p, q; .reg .u32 t; .reg .s32 d; mov.u32 t, %0; setp.ne.u32 q, %1, 0xFFFFFFFF;\n"
                 "WU_%=: @q mov.u32 t, %%clock; sub.s32 d, t, %0; setp.lt.s32 p, d, 0; @p bra.uni WU_%=; }" :: "r"(tgt), "r"(any) : "memory");
}

namespace mk {
constexpr uint32_t SB = 1024;
constexpr uint32_t WV = SB, WO = SB + 65536, XT = SB + 131072, TK = SB + 163840  , TQ = TK + 32768, MEM = TQ + 4096,
                   SC = MEM + 8192  , PT = SC + 6144,
                   OB = SC + 8192, SUM = OB + 2048, BAR = SUM + 512, GRP = BAR + 128, PROFB = BAR + 192,
                   TOTAL = PROFB - SB;
static_assert(TOTAL <= 232448, "shared memory");
constexpr uint32_t MB_WQ = BAR, MB_WK = BAR + 8, MB_WV = BAR + 16, MB_WO = BAR + 24, MB_X = BAR + 32, MB_KV = BAR + 40, MB_R = BAR + 48, MB_B = BAR + 56, MB_C = BAR + 64;
constexpr uint32_t XT2 = WV, RS = WV + 32768, VE = RS + 4096;
enum { B_START = 1, B_H0, B_H2, B_H3, B_S1, B_SC, B_SC2, B_S0, B_O, B_O2, B_PT, B_GO, B_VX, B_RD, B_BT };
constexpr uint64_t XD0 = (uint64_t)(XT >> 4) | ((uint64_t)1 << 16) | ((uint64_t)64 << 32) | ((uint64_t)1 << 62);
constexpr uint32_t TSLOT = NH * 49152;
}
struct MainParams { int d[12]; uint32_t zero; int by_sm; char* rb; const char* x; };
#define XD(i) (mk::XD0 - (((i) >> 5) & 1) * ((mk::XT - mk::XT2) >> 4) + ((i) >> 6) * ((mk::TK - mk::XT) >> 4) + (((i) & 31) >> 2) * 256 + ((i) & 3) * 2)
#define XD4(i) XD(i), XD(i + 1), XD(i + 2), XD(i + 3)
#define XD16(i) XD4(i), XD4(i + 4), XD4(i + 8), XD4(i + 12)
__constant__ __align__(256) uint64_t c_xd[96] = {XD16(0), XD16(16), XD16(32), XD16(48), XD16(64), XD16(80)};
#define CUT(r) asm volatile("{ .reg .pred q; setp.eq.u32 q, %1, 0xFFFFFFFF; @q mov.u32 %0, %%clock; }" : "+r"(r) : "r"(t16) : "memory")
__device__ __forceinline__ uint32_t opq(uint32_t x) { asm volatile("" : "+r"(x)); return x; }
__device__ __forceinline__ float opqf(float x) { asm volatile("" : "+f"(x)); return x; }
#define PROF(i)
#define PROFW(i, w)
#define TRC(i, v)
#define RETRY(i, on)
#define P(i) prm.d[i]
#define DELAY(n) do { if (n) { _Pragma("unroll") for (int i_ = 0; i_ < n; i_++) asm volatile("mad.lo.u32 %0, %0, %1, %0;" : "+r"(pb) : "r"(prm.zero)); CUT(pa); } } while (0)

__device__ __forceinline__ uint32_t tagw(uint32_t w, uint32_t tau) { return (w & ~1u) | tau; }
__device__ __forceinline__ uint32_t ld_g32(const void* p) { uint32_t v; asm volatile("ld.relaxed.gpu.global.u32 %0, [%1];" : "=r"(v) : "l"(p) : "memory"); return v; }
__device__ __forceinline__ void ld_g64(uint32_t* v, const void* p) { asm volatile("ld.relaxed.gpu.global.v2.u32 {%0,%1}, [%2];" : "=r"(v[0]), "=r"(v[1]) : "l"(p) : "memory"); }
__device__ __forceinline__ void ld_g128(uint32_t* v, const void* p) {
    asm volatile("ld.relaxed.gpu.global.v4.u32 {%0,%1,%2,%3}, [%4];" : "=r"(v[0]), "=r"(v[1]), "=r"(v[2]), "=r"(v[3]) : "l"(p) : "memory");
}
__device__ __forceinline__ void st_g64(void* p, uint32_t a, uint32_t b) { asm volatile("st.relaxed.gpu.global.v2.u32 [%0], {%1,%2};" :: "l"(p), "r"(a), "r"(b) : "memory"); }
__device__ __forceinline__ void lds128f(float* v, uint32_t a) { asm volatile("ld.shared.v4.f32 {%0,%1,%2,%3}, [%4];" : "=f"(v[0]), "=f"(v[1]), "=f"(v[2]), "=f"(v[3]) : "r"(a) : "memory"); }
__device__ __forceinline__ void sts128f(uint32_t a, float x, float y, float z, float w) { asm volatile("st.shared.v4.f32 [%0], {%1,%2,%3,%4};" :: "r"(a), "f"(x), "f"(y), "f"(z), "f"(w) : "memory"); }
__device__ __forceinline__ void stsm4(uint32_t a, uint32_t r0, uint32_t r1, uint32_t r2, uint32_t r3) {
    asm volatile("stmatrix.sync.aligned.m8n8.x4.shared.b16 [%0], {%1,%2,%3,%4};" :: "r"(a), "r"(r0), "r"(r1), "r"(r2), "r"(r3) : "memory");
}
__device__ __forceinline__ void mmaq(float* c, const uint32_t* a, uint32_t b0, uint32_t b1) { mma16(c, a[0], a[1], a[2], a[3], b0, b1); }
template <int LUT> __device__ __forceinline__ uint32_t lop3(uint32_t a, uint32_t b, uint32_t c) { uint32_t r; asm("lop3.b32 %0, %1, %2, %3, %4;" : "=r"(r) : "r"(a), "r"(b), "r"(c), "n"(LUT)); return r; }
template <int N, int S> __device__ __forceinline__ uint32_t stale(const uint32_t* x, uint32_t tau) {
    if constexpr (N == 2) return lop3<0x7E>(x[0], tau, x[S]);
    else if constexpr (N == 3) return lop3<0xF6>(stale<2, S>(x, tau), x[2 * S], tau);
    else if constexpr (N == 4 || N == 16) return lop3<0xFC>(stale<N / 2, S>(x, tau), stale<N / 2, S>(x + N / 2 * S, tau), 0);
    else return lop3<0xFE>(stale<3, S>(x, tau), stale<3, S>(x + 3 * S, tau), stale<2, S>(x + 6 * S, tau));
}
__device__ __forceinline__ uint32_t late(uint32_t a, uint32_t b, uint32_t mask) {
    uint32_t r;
    asm volatile("{ .reg .pred p; .reg .b32 t; lop3.b32 t, %1, %2, %3, 0xA8; setp.ne.b32 p, t, 0; vote.sync.any.pred p, p, 0xFFFFFFFF; selp.u32 %0, 1, 0, p; }" : "=r"(r) : "r"(a), "r"(b), "r"(mask));
    return r;
}
#define AGAIN(id, reload, ...) _Pragma("unroll 1") for (int n_ = 0; __builtin_expect(__VA_ARGS__, 0) && n_ < SPIN_LIMIT; n_++) { RETRY(id, 1); reload; }
__device__ __forceinline__ uint32_t tile_off(int lane, int chunk0) {
    return ((lane >> 4) * 8 + (lane & 7)) * 128 + (((chunk0 + ((lane >> 3) & 1)) ^ (lane & 7)) << 4);
}
template <int K0, int K1>
__device__ __forceinline__ void load_tile(uint32_t a, uint32_t* T) {
    #pragma unroll
    for (int ks = K0; ks < K1; ks++) ldsm4t(T[4 * ks], T[4 * ks + 1], T[4 * ks + 2], T[4 * ks + 3], a + ks * 2048);
}
__device__ __forceinline__ void lds128u(uint32_t* v, uint32_t a) { asm volatile("ld.shared.v4.u32 {%0,%1,%2,%3}, [%4];" : "=r"(v[0]), "=r"(v[1]), "=r"(v[2]), "=r"(v[3]) : "r"(a) : "memory"); }
template <int K0, int K1, int STRIDE = 4096>
__device__ __forceinline__ void load_frag(uint32_t a, uint32_t* T) {
    #pragma unroll
    for (int ks = K0; ks < K1; ks++) lds128u(&T[4 * ks], a + ks * STRIDE);
}
template <int L0, int L1, bool INIT = false>
__device__ __forceinline__ void wg_run(float* acc, const uint32_t* A, const uint64_t* d) {
    if (L1 > L0) {
        wg_fence();
        #pragma unroll
        for (int l = L0; l < L1; l++) wgmma_n32_rs(acc, &A[4 * l], d[l], INIT || l != 0);
        wg_commit();
    }
}
__device__ __forceinline__ void load_x(const CUtensorMap* tmX, int c, int seg, uint32_t dst) {
    asm volatile("{ .reg .pred p; elect.sync _|p, 0xFFFFFFFF;\n"
        "@p cp.async.bulk.tensor.3d.shared::cluster.global.mbarrier::complete_tx::bytes [%4], [%0, {%5, %1, %2}], [%3]; }"
        :: "l"(tmX), "r"(seg * 32), "r"((c & 1) * 8), "r"(mk::MB_X), "r"(dst), "r"(0) : "memory");
    __syncwarp();
}
__device__ __forceinline__ void bulk_expect(uint32_t mb, uint32_t bytes) {
    asm volatile("{ .reg .pred p; elect.sync _|p, 0xFFFFFFFF; @p mbarrier.arrive.expect_tx.shared::cta.b64 _, [%0], %1; }" :: "r"(mb), "r"(bytes) : "memory");
}
__device__ __forceinline__ void bulk_copy(uint32_t dst, const void* src, uint32_t bytes, uint32_t mb) {
    asm volatile("{ .reg .pred p; elect.sync _|p, 0xFFFFFFFF; @p cp.async.bulk.shared::cluster.global.mbarrier::complete_tx::bytes [%0], [%1], %2, [%3]; }"
        :: "r"(dst), "l"(src), "r"(bytes), "r"(mb) : "memory");
    __syncwarp();
}
__device__ __forceinline__ void bulk_copy_if(bool on, uint32_t dst, const void* src, uint32_t bytes, uint32_t mb) {
    asm volatile("{ .reg .pred p; elect.sync _|p, 0xFFFFFFFF; setp.ne.and.b32 p, %4, 0, p; @p cp.async.bulk.shared::cluster.global.mbarrier::complete_tx::bytes [%0], [%1], %2, [%3]; }"
        :: "r"(dst), "l"(src), "r"(bytes), "r"(mb), "r"((int)on) : "memory");
    __syncwarp();
}
__device__ __forceinline__ void kv_expect(uint32_t bytes) { bulk_expect(mk::MB_KV, bytes); }
__device__ __forceinline__ void kv_copy(uint32_t dst, const void* src, uint32_t bytes) { bulk_copy(dst, src, bytes, mk::MB_KV); }
__device__ __forceinline__ uint32_t gtime() { uint32_t c; asm volatile("mov.u32 %0, %%globaltimer_lo;" : "=r"(c) :: "memory"); return c; }
__device__ __forceinline__ void wait_g(uint32_t tgt, uint32_t any) {
    asm volatile("{ .reg .pred p, q; .reg .u32 t; mov.u32 t, %0; setp.ne.u32 q, %1, 0xFFFFFFFF;\n"
                 "WG_%=: @q mov.u32 t, %%globaltimer_lo; sub.u32 t, t, %0; setp.gt.u32 p, t, 0xFFFF0000; @p bra.uni WG_%=; }" :: "r"(tgt), "r"(any) : "memory");
    __syncwarp();
}
__device__ __forceinline__ uint32_t clkv(uint32_t any) {
    uint32_t c; asm volatile("{ .reg .pred q; setp.ne.u32 q, %1, 0xFFFFFFFF; mov.u32 %0, 0; @q mov.u32 %0, %%clock; }" : "=r"(c) : "r"(any) : "memory"); return c;
}
__device__ __forceinline__ char* kv_src(int c, int seg) { return (char*)g_T + ((seg & 1) * mk::TSLOT + (c >> 2) * 49152); }
__device__ __forceinline__ void prefetch_l2(const void* p, uint32_t bytes) {
    asm volatile("{ .reg .pred p; elect.sync _|p, 0xFFFFFFFF; @p cp.async.bulk.prefetch.L2.global [%0], %1; }" :: "l"(p), "r"(bytes) : "memory");
}
__device__ __forceinline__ uint32_t phase(int i) { return (~i >> 1) & 1; }
__device__ __forceinline__ void qk_pack(const float* acc, uint32_t* p) {
    #pragma unroll
    for (int i = 0; i < 4; i++) { p[i] = pack2(acc[4 * i], acc[4 * i + 1]); p[4 + i] = pack2(acc[4 * i + 2], acc[4 * i + 3]); }
}
__device__ __forceinline__ void sts128_if(bool on, uint32_t a, const uint32_t* p) {
    asm volatile("{ .reg .pred p; setp.ne.b32 p, %5, 0; @p st.shared.v4.u32 [%0], {%1,%2,%3,%4}; }" :: "r"(a), "r"(p[0]), "r"(p[1]), "r"(p[2]), "r"(p[3]), "r"((int)on) : "memory");
}
__device__ __forceinline__ void st_if(bool on, char* a, const uint32_t* p) {
    asm volatile("{ .reg .pred p; setp.ne.b32 p, %5, 0; @p st.relaxed.gpu.global.v4.u32 [%0], {%1,%2,%3,%4}; }" :: "l"(a), "r"(p[0]), "r"(p[1]), "r"(p[2]), "r"(p[3]), "r"((int)on) : "memory");
}
__device__ __forceinline__ char* tok_dst(int c, int seg, int wg) { return kv_src(c, seg) + (wg ? (c & 1) * 8192 + (c & 2) * 2048 : 32768 + (c & 1) * 2048 + (c & 2) * 512); }
#define HI8 (wg ? 0x220 : 0xC0)
#define TAGM() uint32_t tm[4]; tag_masks(tm, (t16 >> (wg ? 4 : 6)) & 24)
__device__ __forceinline__ void acc_init(float* acc, const uint32_t* p) {
    #pragma unroll
    for (int i = 0; i < 4; i++) { acc[4 * i] = bflo(p[i]); acc[4 * i + 1] = bfhi(p[i]); acc[4 * i + 2] = bflo(p[4 + i]); acc[4 * i + 3] = bfhi(p[4 + i]); }
}
__device__ __forceinline__ void acc_add(float* acc, const uint32_t* p) {
    #pragma unroll
    for (int i = 0; i < 4; i++) { acc[4 * i] += bflo(p[i]); acc[4 * i + 1] += bfhi(p[i]); acc[4 * i + 2] += bflo(p[4 + i]); acc[4 * i + 3] += bfhi(p[4 + i]); }
}
__device__ __forceinline__ void tag_masks(uint32_t* m, uint32_t j8) {
    const uint32_t x = 1u << j8;
    #pragma unroll
    for (int i = 0; i < 4; i++) m[i] = opq(__byte_perm(x, 0, 0x4440 + i));
}
__device__ __forceinline__ void pack_tag(const float* acc, uint32_t* p, uint32_t tau, const uint32_t* m) {
    qk_pack(acc, p);
    #pragma unroll
    for (int i = 0; i < 8; i++) p[i] = lop3<0xB8>(p[i], m[i & 3], tau);
}
__device__ __forceinline__ uint32_t kv_stale(uint32_t w, uint32_t l16, uint32_t tau) {
    uint32_t x[12];
    const uint32_t a = opq(l16 * 2 + ((l16 >> 4) & 0x1C) + w * 12288), aq = w == 2 ? opq(l16 * 2 + ((l16 >> 2) & 0x10) + ((l16 >> 5) & 0xC) + 24576) : a;
    #pragma unroll
    for (int i = 0; i < 12; i++) x[i] = lds32(mk::TK + i * 1024 + (i < 8 ? a : aq));
    return late(stale<8, 1>(x, tau), stale<4, 1>(x + 8, tau), 1);
}
__device__ __forceinline__ void refetch_kv(int c, int seg, int w, uint32_t l16) {
    #pragma unroll 1
    for (int i = w * 24; i < w * 24 + 24; i++) {
        uint32_t v[4];
        ld_g128(v, kv_src(c, seg) + (i * 512 + (i >> 6) * (c & 3) * 4096) + l16);
        sts128(mk::TK + i * 512 + l16, make_uint4(v[0], v[1], v[2], v[3]));
    }
    __syncwarp();
}
__device__ __forceinline__ void get_kv(int c, int seg) {
    kv_expect(36864); kv_copy(mk::TK, kv_src(c, seg), 32768); kv_copy(mk::TQ, kv_src(c, seg) + (32768 + (c & 3) * 4096), 4096);
}
constexpr uint32_t ONES = 0x3F803F80u;
__device__ __forceinline__ float rcpf(float x) { float r; asm("rcp.approx.ftz.f32 %0, %1;" : "=f"(r) : "f"(x)); return r; }

#define ANN 2
#define POL 8
#define PRE0 4
#define PRE1 4
#define HC 2
#define HR 4
#define BL 1
#define NA 2
#define QF 0
#define DEEP 6
#define AHEAD(n) (PRE0 + 2 * (n) < (n) + DEEP ? PRE0 + 2 * (n) : (n) + DEEP < 16 ? (n) + DEEP : 16)
#define CO 1
#define HS 2
#define VP 0
#define KM 1
#define NLDS 2
#define AL 2
#define RP 26
#define RQ 2
#define RL 29
#define R4 1
#define KVP 12
#define LD7 8
#define XP 3
#define G2 0
#define NB 26
#define BD 8
#define NP 22
#define TA 4
#define TA0 2
#define NT 19
#define VH 1
#define TRIES 200
#define NPW 3
#define EV0 5
#define EV1 8
#define WA1 6
#define WA2 9
#define H2 10
#define QV 1
#define QD 0
#define KD 0
#define VD 0
#define WA0 4
#define ONE 0
#define PP 12
#define OBA 3
#define WA3 1
#define WB1 0
#define WB2 12
#define WB3 13
#define H0 6
#define H3 10
__device__ __forceinline__ uint32_t tagm(uint32_t w, uint32_t mask, uint32_t tau) { return lop3<0xB8>(w, mask, tau); }
__device__ __forceinline__ char* at(uint32_t lo, uint32_t hi) { char* p; asm("mov.b64 %0, {%1,%2};" : "=l"(p) : "r"(lo), "r"(hi)); return p; }
__device__ __forceinline__ float ex2(float x) { float r; asm("ex2.approx.ftz.f32 %0, %1;" : "=f"(r) : "f"(x)); return r; }
__device__ __forceinline__ float max8(const float* x) { return fmaxf(fmaxf(fmaxf(x[0], x[1]), fmaxf(x[2], x[3])), fmaxf(fmaxf(x[4], x[5]), fmaxf(x[6], x[7]))); }
__device__ __forceinline__ float max4lanes(float m) { return fmaxf(fmaxf(m, __shfl_xor_sync(~0u, m, 1)), fmaxf(__shfl_xor_sync(~0u, m, 2), __shfl_xor_sync(~0u, m, 3))); }
constexpr float SCL = 0.08838834764831845f * 1.4426950408889634f;
__device__ __forceinline__ void tok_scores(float* x, uint32_t sa) {
    float y[8];
    lds128f(x, sa); lds128f(y, sa + 1024); lds128f(x + 4, sa + 512); lds128f(y + 4, sa + 1536);
    #pragma unroll
    for (int i = 0; i < 8; i++) x[i] += y[i];
}
__device__ __forceinline__ void mem_scores(float* x, uint32_t sa) {
    float z[8];
    lds128f(z, sa + 2048); lds128f(z + 4, sa + 2560);
    x[8] = (z[0] + z[2]) + (z[4] + z[6]); x[9] = (z[1] + z[3]) + (z[5] + z[7]);
}

struct Ctx { uint32_t u_rs, u_rl, u_bs, u_bl, rblo, rbhi; int w8, c; };
template <int wg>
__device__ __forceinline__ void steps(uint32_t* W, uint32_t* T, uint32_t t16, uint32_t pa, uint32_t pb, const Ctx& cx, const CUtensorMap* tmX, const MainParams& prm) {
    using namespace mk;
    const int c = cx.c, kap = c & 1, w8 = cx.w8;
    const uint32_t rbhi = cx.rbhi;
    uint32_t u_rs = cx.u_rs, u_rl = cx.u_rl, u_bs = cx.u_bs, u_bl = cx.u_bl ^ ((c & 2) << 14);
    uint32_t u_x = cx.rblo + RB_X + (c >> 2) * 16384, u_xs = u_x + kap * 2048 + (c & 2) * 512;
    uint32_t u_ta = ((cx.u_bl & ~0x10000u) ^ (kap << 12)) + (RB_T - RB_B) + 1024;
    uint32_t u_rp = cx.rblo + RB_T + 1024 + c * 4;
    uint32_t u_og = (c & 3) * 65536 + (c >> 2) * 2048 + (w8 & 3) * 256;
    const uint32_t u_sa = (w8 & 2) * 256 + (w8 & 1) * 8;
    #define TOK_DST() tok_dst(c, seg, wg)
    constexpr int EV = wg ? EV1 : EV0;
    constexpr uint32_t VEB = VE + (wg ? EV0 * 2048 - 2048 : 0) - (16 - EV) * 2048;
    static_assert((EV0 + EV1) * 2048 <= 28672, "");
    __syncthreads();
    #pragma unroll
    for (int i = 16 - EV; i < 16; i++) sts128(VEB + i * 2048 + t16, make_uint4(T[4 * i], T[4 * i + 1], T[4 * i + 2], T[4 * i + 3]));
    asm volatile("fence.proxy.async.shared::cta;" ::: "memory");
    #pragma unroll 1
    for (uint32_t sb = 0, redo = 0, uz = prm.zero;;) {
        sb = opq(sb + 256);
        const int s = sb & 255, bc = sb >> 8;
        t16 |= uz;
        uz &= sb;
        const int seg = s + 2;
        const uint32_t tau = phase(s);
        const uint32_t l16 = opq(t16 & 0x1F0);
        uint32_t F[64];
        float ot[3][2][4];
        uint32_t an[4];
        #define LDB(i) ldsm4t(b[i][0], b[i][1], b[i][2], b[i][3], MEM + l16 + (i) * 512)
        #define ST_X() do { char* xs = at(u_xs + (pb >> 16), rbhi) + wg * 4096; \
            st_g32(xs, tagm(pack2((a[0][0] + a[1][0]) + (a[2][0] + a[3][0]), (a[0][2] + a[1][2]) + (a[2][2] + a[3][2])), mG, tau * 0x10001u)); \
            st_g32(xs + 32, tagm(pack2((a[0][1] + a[1][1]) + (a[2][1] + a[3][1]), (a[0][3] + a[1][3]) + (a[2][3] + a[3][3])), mG, tau * 0x10001u)); } while (0)
        #define ST_V() st_g64(at(u_xs + (t16 >> 1), rbhi) + (8192 + wg * 3072), \
            tagm(pack2((v[0][0] + v[1][0]) + (v[2][0] + v[3][0]), (v[0][1] + v[1][1]) + (v[2][1] + v[3][1])), mT, tau), \
            pack2((v[0][2] + v[1][2]) + (v[2][2] + v[3][2]), (v[0][3] + v[1][3]) + (v[2][3] + v[3][3])))
        #define V_MMA(i, o) do { mmaq(v[2 * ((i) & 1)], &T[8 * (i)], b[(o) + (i)][0], b[(o) + (i)][1]); mmaq(v[2 * ((i) & 1) + 1], &T[8 * (i) + 4], b[(o) + (i)][2], b[(o) + (i)][3]); } while (0)
        #define ST_R(i) do { \
                const uint32_t r0 = pack2((r[i][0][0] + r[i][1][0]) * i0, (r[i][0][1] + r[i][1][1]) * i1); \
                const uint32_t r1 = pack2((r[i][0][2] + r[i][1][2]) * i0, (r[i][0][3] + r[i][1][3]) * i1); \
                st_g64(at(ra ^ (i * 0x3000), rbhi), tagm(r0, mT, tau), r1); } while (0)
        #define LD_OB(i) ldsm4t(ob[4 * (i)], ob[4 * (i) + 1], ob[4 * (i) + 2], ob[4 * (i) + 3], OB + l16 + (i) * 512)
        #define WO_MMA(have, more, mid, tail) uint32_t ob[16], ra; float r[2][2][4] = {}; \
            LD_OB(0); __syncwarp(); LD_OB(1); __syncwarp(); if (OBA > 2) { LD_OB(2); __syncwarp(); } \
            _Pragma("unroll") for (int i = have; i < have + more; i++) { lds128u(&F[4 * i], WO + t16 + i * 4096); __syncwarp(); } \
            _Pragma("unroll") for (int i = 0; i < 16; i++) { \
                if (!(i & 1) || (i > 4 && i < 8)) CUT(pb); \
                if (i == 4) LD_OB(OBA); \
                if (i == 5 && OBA == 2) LD_OB(3); \
                { const int n = have + more + i - 8 + OBA; if (i >= 8 - OBA && n < 16) lds128u(&F[4 * n], WO + t16 + n * 4096); } \
                if (wg == 0 && i == 4) { const float2 su = lds64f(SUM + (l16 >> 1)); i0 = su.x; i1 = su.y; } \
                mmaq(r[(i >> 1) & 1][i & 1], &F[4 * i], ob[(i >> 2) * 4 + 2 * (i & 1)], ob[(i >> 2) * 4 + 2 * (i & 1) + 1]); \
                if (wg && i == 2) { i0 = opqf(rcpf(i0)); i1 = opqf(rcpf(i1)); } \
                if (i == PP) { mid; } \
                if (wg && i == POL) POLL(); \
                if (!wg && i == KVP) bulk_copy(TK + 16384 + w8 * 4096, kv_src(c, s + 1) + (16384 + w8 * 4096), 4096, MB_KV); \
                if (i == 11) { ra = (l16 >> 1) * 33 & 0x1078; CUT(ra); } \
                if (i == 13) ra = opq(ra ^ u_rs); } \
            CUT(pb); tail; \
            if (!wg) { i0 = rcpf(i0); i1 = rcpf(i1); } \
            ST_R(0); ST_R(1)
        #define LD_X(r, o) do { ld_g64(r, xa + (o)); ld_g64(r + 2, xa + ((o) + 2048)); ld_g64(r + 4, xa + ((o) + 1024)); ld_g64(r + 6, xa + ((o) + 3072)); } while (0)
        #define REPORT(w, add) asm volatile("{ .reg .pred p; .reg .u32 t; setp.lt.u32 p, %1, 32; mov.u32 t, %1; @p mov.u32 t, %%globaltimer_lo; add.u32 t, t, %3; lop3.b32 t, t, 31, %2, 0xB8; @p st.relaxed.gpu.global.u32 [%0], t; }" \
            :: "l"(at(u_rp + (l16 << 8), rbhi)), "r"(t16 - (w) * 512), "r"(s), "r"(add) : "memory")
        #define POLL() asm volatile("{ .reg .pred p; setp.ge.u32 p, %5, 3584; mov.u32 %0, 0; mov.u32 %1, 0; mov.u32 %2, 0; mov.u32 %3, 0; @p ld.relaxed.gpu.global.v4.u32 {%0,%1,%2,%3}, [%4]; }" \
            : "=&r"(an[0]), "=&r"(an[1]), "=&r"(an[2]), "=&r"(an[3]) : "l"(at(u_ta + l16, rbhi)), "r"(t16) : "memory")
        #define GET_B(sl) do { const uint32_t a_ = u_bl ^ (sl); bulk_copy(MEM, at(a_, rbhi), 4096, MB_B); bulk_copy(MEM + 4096, at(a_ ^ 0x3000, rbhi), 4096, MB_B); } while (0)
        if constexpr (wg == 0) {
            float a[4][4], v[4][4] = {};
            uint32_t b[16][4];
            if (__builtin_expect(redo, 0)) {
                RETRY(6, 1);
                bsync<B_RD, 256>();
                if (w8 == 3) { bulk_expect(MB_B, 8192); GET_B(1 << 20); }
                __syncwarp();
            }
            const uint32_t ck = opq(t16 * 2 + ((l16 >> 4) & 0x1C)), tp = opq(phase(s - 1)), cm = opq((2 * bc + (s > 0 && bc < SPIN_LIMIT)) | (t16 >> 19));
            CUT(pa);
            mbar_wait(MB_B, ~bc & 1);
            #define ORD(n) (n)
            LDB(ORD(0)); __syncwarp(); LDB(ORD(1)); __syncwarp();
            const uint32_t c0 = lds32(MEM + ck), c1 = lds32(MEM + 4096 + ck);
            __syncwarp();
            #pragma unroll
            for (int n = 2; n < PRE0; n++) { LDB(ORD(n)); __syncwarp(); }
            PROF(0);
            uint32_t vw[2];
            #pragma unroll
            for (int n = 0; n < 16; n++) {
                const int i = ORD(n);
                CUT(pa);
                #pragma unroll
                for (int m = AHEAD(n); m < AHEAD(n + 1); m++) { LDB(ORD(m)); __syncwarp(); }
                if (n == HC) redo = opq(lop3<0x7E>(c0, tp, c1) & cm);
                if (n == HC + 1) asm volatile("{ .reg .pred p; setp.ne.u32 p, %2, 0; @p st.shared.u32 [%0], %1; }" :: "r"(SUM + 256), "r"(cm), "r"(redo & 1) : "memory");
                if (n == H0) barrive<B_H0, 256>();
                if (n == HR + 1) { redo = lds32(SUM + 256 + opq(t16 >> 20)); __syncwarp(); }
                if (n == HR) bsync<B_START, 128>();
                if (n == 12) redo = !late(redo ^ (2 * bc + 1), 0, ~0u);
                const int e = n < 8 ? 0 : 2 * (~n & 1);
                if (!(n & 7)) a[e][0] = a[e][1] = a[e][2] = a[e][3] = a[e + 1][0] = a[e + 1][1] = a[e + 1][2] = a[e + 1][3] = 0.f;
                mmaq(a[e], &W[8 * i], b[i][0], b[i][1]);
                if (n < 8) { mmaq(v[0], &T[8 * i], b[i][0], b[i][1]); CUT(pa); }
                mmaq(a[e + 1], &W[8 * i + 4], b[i][2], b[i][3]);
                if (n < 8) mmaq(v[1], &T[8 * i + 4], b[i][2], b[i][3]);
                if (n == 10) { vw[0] = opq(pack2(v[0][0] + v[1][0], v[0][1] + v[1][1])); vw[1] = opq(pack2(v[0][2] + v[1][2], v[0][3] + v[1][3])); }
            }
            CUT(pa);
            if (__builtin_expect(redo, 0)) { __syncwarp(); continue; }
            CUT(pa); CUT(pb);
            const uint32_t mG = (l16 & 0x1C0) ? 0 : 0x10001u, mT = (l16 & 0x30) ? 0 : 1;
            ST_X();
            CUT(pa);
            PROF(1);
            const char* const xa = at(u_x + (t16 >> 1), rbhi);
            float sc[4][4];
            uint32_t k[8], A[16], q[16], kf[16];
            #define LD_Q(xb) do { LD_X(q, 0); { const char* const xa = xb; LD_X(q + 8, 0); } } while (0)
            #define XB() at((u_x + (opq(t16) >> 1)) ^ 256, rbhi)
            #define LD_A(i) ldsm4t(A[4 * i], A[4 * i + 1], A[4 * i + 2], A[4 * i + 3], TQ + (i & 1) * 1024 + ((i & 2) ? qb : qa))
            uint32_t k1[16];
            #define LD_K(i) do { ldsm4t(kf[4 * i], kf[4 * i + 1], kf[4 * i + 2], kf[4 * i + 3], TK + ka[i]); ldsm4t(k1[4 * i], k1[4 * i + 1], k1[4 * i + 2], k1[4 * i + 3], TK + 8192 + ka[i]); __syncwarp(); } while (0)
            const char* const xb = XB();
            const uint32_t ka[4] = {opq(pa & 0xFFFF), opq((pa & 0xFFFF) ^ 0x400), opq((pa & 0xFFFF) ^ 0x10), opq((pa & 0xFFFF) ^ 0x410)}, qa = opq(pa >> 16), qb = opq(qa ^ 0x100);
            st_g64(at(u_xs + (t16 >> 1), rbhi) + 8192, tagm(vw[0], mT, tau), vw[1]);
            CUT(pb);
            bsync<B_H2, 256>();
            if (QF) { LD_Q(xb); __syncwarp(); }
            #pragma unroll
            for (int i = 0; i < NA; i++) LD_K(i);
            CUT(pb);
            #pragma unroll
            for (int i = 0; i < 4 * NA; i++) kf[i] = opq(hadd2(kf[i], k1[i]));
            CUT(pb);
            if (!QF) { DELAY(QD); LD_Q(xb); CUT(pb); }
            bsync<B_H3, 256>();
            #pragma unroll
            for (int i = NA; i < 4; i++) LD_K(i);
            LD_A(0); LD_A(1); LD_A(2); LD_A(3);
            CUT(pb);
            if (KM == 1) {
                #pragma unroll
                for (int i = 4 * NA; i < 16; i++) kf[i] = opq(hadd2(kf[i], k1[i]));
                CUT(pb);
            }
            DELAY(KD);
            LD_X(k, 4096);
            barrive<B_VX, 256>();
            CUT(pb);
            PROF(3);
            if (KM == 2) {
                #pragma unroll
                for (int i = 4 * NA; i < 16; i++) kf[i] = opq(hadd2(kf[i], k1[i]));
            }
            #pragma unroll
            for (int i = 0; i < 8; i++) A[2 * i + 1] = opq(hadd2(A[2 * i], A[2 * i + 1]));
            CUT(pb);
            AGAIN(1, LD_Q(XB()); LD_X(k, 4096); sts32(SUM + 268, s + 1), late(stale<4, 2>(q, tau), stale<4, 2>(q + 8, tau), mT))
            #pragma unroll
            for (int i = 0; i < 4; i++) {
                A[4 * i] = hadd2(q[4 * i], q[4 * i + 2]); A[4 * i + 2] = hadd2(q[4 * i + 1], q[4 * i + 3]);
                if (i < 2) { sc[i][0] = sc[i][1] = sc[i][2] = sc[i][3] = sc[2 + i][0] = sc[2 + i][1] = sc[2 + i][2] = sc[2 + i][3] = 0.f; }
                mmaq(sc[i & 1], A + 4 * i, kf[2 * i], kf[2 * i + 1]); mmaq(sc[2 + (i & 1)], A + 4 * i, kf[8 + 2 * i], kf[9 + 2 * i]);
            }
            sts128f(SC + t16, sc[0][0] + sc[1][0], sc[0][1] + sc[1][1], sc[2][0] + sc[3][0], sc[2][1] + sc[3][1]);
            barrive<B_S1, 256>();
            sts128f(SC + 3072 + t16, sc[0][2] + sc[1][2], sc[0][3] + sc[1][3], sc[2][2] + sc[3][2], sc[2][3] + sc[3][3]);
            load_frag<0, WB1>(WO + t16, F);
            const uint32_t sa = opq(l16 + u_sa);
            CUT(pb);
            PROF(4);
            float d[16];
            #pragma unroll 1
            for (int n_ = 0;; n_++) {
                #pragma unroll
                for (int i = 0; i < 4; i++) { d[4 * i] = d[4 * i + 1] = d[4 * i + 2] = d[4 * i + 3] = 0.f; mmaq(d + 4 * i, A + 4 * (i >> 1), k[2 * i], k[2 * i + 1]); }
                if (__builtin_expect(!late(stale<2, 2>(k, tau), stale<2, 2>(k + 4, tau), mT), 1) || n_ >= SPIN_LIMIT) break;
                RETRY(2, 1);
                LD_X(k, 4096);
            }
            sts64f(SC + 2048 + sa, (d[0] + d[4]) + (d[8] + d[12]), (d[1] + d[5]) + (d[9] + d[13]));
            barrive<B_SC, 256>();
            CUT(pb);
            sts64f(SC + 5120 + sa, (d[2] + d[6]) + (d[10] + d[14]), (d[3] + d[7]) + (d[11] + d[15]));
            PROF(5);
            if (w8 == 0) {
                float x[10];
                bsync<B_S0, 128>();
                tok_scores(x, SC + 3072 + l16); mem_scores(x, SC + 3072 + l16);
                __syncwarp();
                load_frag<WB1, WB2>(WO + t16, F);
                const int g = l16 >> 6, lim = 8 * (g >> 1) + 2 * (c & 3) + (g & 1) - ((l16 >> 1) & 0x18);
                #pragma unroll
                for (int i = 0; i < 8; i++) if (i > lim) x[i] = -INFINITY;
                const float ms = opqf(-SCL * max4lanes(fmaxf(max8(x), fmaxf(x[8], x[9]))));
                CUT(pb);
                #pragma unroll
                for (int i = 0; i < 10; i++) x[i] = ex2(fmaf(x[i], SCL, ms));
                load_frag<WB2, WB3>(WO + t16, F);
                sts128(PT + l16, make_uint4(pack2(x[0], x[1]), pack2(x[2], x[3]), pack2(x[4], x[5]), pack2(x[6], x[7])));
                sts32(PT + 512 + (l16 >> 2), pack2(x[8], x[9]));
                if (!ONE) barrive<B_PT, 160>();
            } else {
                if (ANN == 2) { bsync<B_S0, 128>(); const uint32_t f = lds32(SUM + 268 + opq(t16 >> 16)); REPORT(3, f == s + 1 ? P(2) : 0); } else barrive<B_S0, 128>();
                if (w8 == 1) {
                    mbar_wait(MB_X, ~seg & 1); bulk_expect(MB_X, 32768);
                    if (XPF) prefetch_l2(prm.x + (((seg + XPF) & 63) * 65536 + c * 512), 512);
                    __syncwarp();
                    if (XDL == 300) load_x(tmX, c, seg + 1, (s & 1) ? XT : XT2);
                }
                else if (w8 == 2) {
                    bulk_expect(MB_KV, 36864);
                    bulk_copy(TK, kv_src(c, s + 1), 16384, MB_KV); bulk_copy(TQ, kv_src(c, s + 1) + (32768 + (c & 3) * 4096), 4096, MB_KV);
                    bulk_expect(MB_B, 8192); bulk_expect(MB_R, 4096);
                    __syncwarp();
                }
                bsync<B_SC2, 224>();
                load_frag<WB1, WB3>(WO + t16, F);
                __syncwarp();
                CUT(pb);
            }
            bsync<B_O2, 256>();
            PROF(6);
            float i0, i1;
            WO_MMA(WB3, 0, , );
        } else {
            float a[4][4], v[4][4] = {};
            uint32_t b[16][4];
            barrive_if<B_RD, 256>(redo);
            CUT(pa);
            bsync<B_H0, 256>();
            #pragma unroll
            for (int n = 0; n < PRE1; n++) { LDB(n); __syncwarp(); }
            redo = lds32(SUM + 256 + opq(t16 >> 20));
            PROF(0);
            #pragma unroll
            for (int i = 0; i < 16; i++) {
                if (!(i & 1)) {
                    CUT(pa);
                    if (PRE1 < 8 && i + PRE1 < 16) { LDB(i + PRE1); __syncwarp(); LDB(i + PRE1 + 1); __syncwarp(); }
                    if (PRE1 == 8 && i >= 2 && i < 10) { LDB(i + 6); __syncwarp(); LDB(i + 7); __syncwarp(); }
                    if (i == 6) redo = !late(redo ^ (2 * bc + 1), 0, ~0u);
                    if (i == H2) { barrive_if<B_H2, 256>(!redo); CUT(pa); }
                }
                else if (CO) CUT(pa);
                if (i < 2) { a[2 * i][0] = a[2 * i][1] = a[2 * i][2] = a[2 * i][3] = a[2 * i + 1][0] = a[2 * i + 1][1] = a[2 * i + 1][2] = a[2 * i + 1][3] = 0.f; }
                mmaq(a[2 * (i & 1)], &W[8 * i], b[i][0], b[i][1]); mmaq(a[2 * (i & 1) + 1], &W[8 * i + 4], b[i][2], b[i][3]);
            }
            if (__builtin_expect(redo, 0)) { __syncwarp(); continue; }
            CUT(pa); CUT(pb);
            const uint32_t mG = (l16 & 0x1C0) ? 0 : 0x10001u, mT = (l16 & 0x30) ? 0 : 1;
            ST_X();
            barrive<B_H3, 256>();
            CUT(pa);
            PROF(1);
            #pragma unroll
            for (int i = 7; i >= 0; i--) V_MMA(i, 8);
            ST_V();
            CUT(pb);
            bsync<B_VX, 256>();
            PROF(2);
            uint32_t vf[16], vm[16];
            const uint32_t va = opq(pa), vb = opq(va ^ 0x20);
            #define LD_V() do { _Pragma("unroll") for (int i = 0; i < 4; i++) { const uint32_t a_ = TK + 16384 + ((i & 1) ? vb : va) + (i >> 1) * 4096; \
                ldsm4(vf[4 * i], vf[4 * i + 1], vf[4 * i + 2], vf[4 * i + 3], a_); ldsm4(vm[4 * i], vm[4 * i + 1], vm[4 * i + 2], vm[4 * i + 3], a_ + 8192); } } while (0)
            LD_V();
            __syncwarp();
            load_frag<0, WA0>(WO + t16, F);
            #pragma unroll
            for (int i = 0; i < 16; i++) vf[i] = opq(hadd2(vf[i], vm[i]));
            const char* const xa = at(u_x + (t16 >> 1), rbhi) + (8192 - 1024);
            if (VP) CUT(pb);
            DELAY(VD);
            LD_X(vm, 0); LD_X(vm + 8, 4096);
            __syncwarp();
            load_frag<WA0, WA1>(WO + t16, F);
            CUT(pb);
            float x[10];
            bsync<B_S1, 256>();
            tok_scores(x, SC + l16);
            const float mt = opqf(max8(x));
            if (ANN == 3) REPORT(7, 0);
            CUT(pb);
            PROF(3);
            bsync<B_SC, 256>();
            mem_scores(x, SC + l16);
            const float m1 = fmaxf(mt, fmaxf(x[8], x[9]));
            const float m2 = __shfl_xor_sync(~0u, m1, 1), m3 = __shfl_xor_sync(~0u, m1, 2), m4 = __shfl_xor_sync(~0u, m1, 3);
            CUT(pb);
            load_frag<WA1, WA2>(WO + t16, F);
            barrive<B_SC2, 224>();
            uint32_t p[5], vs[4];
            #define SUM_V() do { _Pragma("unroll") for (int i = 0; i < 4; i++) { const int e = (i >> 1) * 4 + (i & 1); vs[i] = hadd2(hadd2(vm[e], vm[e + 8]), hadd2(vm[e + 2], vm[e + 10])); } } while (0)
            CUT(pb);
            const float ms = -SCL * fmaxf(fmaxf(m1, m2), fmaxf(m3, m4));
            PROF(5);
            #pragma unroll
            for (int i = 0; i < 10; i++) x[i] = fmaf(x[i], SCL, ms);
            x[8] = opqf(ex2(x[8])); x[9] = opqf(ex2(x[9]));
            CUT(pb);
            uint32_t badv = late(stale<4, 2>(vm, tau), stale<4, 2>(vm + 8, tau), mT);
            SUM_V();
            #pragma unroll
            for (int i = 0; i < 4; i++) { x[i] = opqf(ex2(x[i])); vs[i] = opq(vs[i]); }
            const uint32_t z0 = t16 >> 16;
            uint32_t one[4] = {opq(ONES | z0), opq(ONES ^ z0), opq(ONES + z0), opq(ONES - z0)};
            CUT(pb);
            #pragma unroll
            for (int i = 4; i < 8; i++) x[i] = ex2(x[i]);
            #pragma unroll
            for (int i = 0; i < 5; i++) p[i] = pack2(x[2 * i], x[2 * i + 1]);
            float sm[4] = {};
            #define PV(also) do { float o[8] = {}; \
                mma8(o, vs[0], vs[1], p[4]); mma8(o + 4, vs[2], vs[3], p[4]); if (also) mma8(sm, one[0], one[1], p[4]); \
                mmaq(o, vf, p[0], p[1]); mmaq(o + 4, vf + 8, p[0], p[1]); if (also) mmaq(sm, one, p[0], p[1]); \
                mmaq(o, vf + 4, p[2], p[3]); mmaq(o + 4, vf + 12, p[2], p[3]); if (also) mmaq(sm, one, p[2], p[3]); \
                stsm4(OB - 2048 + opq(t16), pack2(o[0], o[1]), pack2(o[2], o[3]), pack2(o[4], o[5]), pack2(o[6], o[7])); } while (0)
            PV(true);
            if (w8 == 4) sts64f(SUM + (l16 >> 1), sm[0], sm[1]);
            if (__builtin_expect(badv, 0)) {
                int n_ = 0;
                uint32_t vm[16];
                const char* const xa = at(u_x + (8192 - 1024) + (opq(t16) >> 1), rbhi);
                do { RETRY(3, 1); LD_X(vm, 0); LD_X(vm + 8, 4096); } while (late(stale<4, 2>(vm, tau), stale<4, 2>(vm + 8, tau), mT) && ++n_ < SPIN_LIMIT);
                SUM_V();
                PV(false);
            }
            if (ONE) bsync<B_O2, 256>(); else { barrive<B_O2, 256>(); bsync<B_O, 128>(); }
            PROF(6);
            float i0 = sm[0], i1 = sm[1];
            #define GET_P() if (!ONE) bsync<B_PT, 160>(); lds128u(p, PT + l16); p[4] = lds32(PT + 512 + (l16 >> 2))
            #define TOK_PV() { const uint32_t z = t16 >> 17; one[0] = ONES | z; one[1] = ONES ^ z; one[2] = ONES + z; one[3] = ONES - z; } \
                _Pragma("unroll") for (int i = 0; i < 12; i++) ot[i >> 2][0][i & 3] = ot[i >> 2][1][i & 3] = 0.f; \
                mma8(ot[0][0], vs[0], vs[1], p[4]); mma8(ot[1][0], vs[2], vs[3], p[4]); mma8(ot[2][0], one[0], one[1], p[4]); \
                mmaq(ot[0][1], vf + 4, p[2], p[3]); mmaq(ot[1][1], vf + 12, p[2], p[3]); mmaq(ot[2][1], one, p[2], p[3]); CUT(pa)
            WO_MMA(WA2, WA3, GET_P(), TOK_PV());
            CUT(pa);
            mmaq(ot[0][0], vf, p[0], p[1]); mmaq(ot[1][0], vf + 8, p[0], p[1]); mmaq(ot[2][0], one, p[0], p[1]);
            CUT(pb);
            barrive<B_GO, 256>();
        }
        CUT(pb);
        PROF(7);
        #define PK_O() const float j0 = rcpf(ot[2][0][0] + ot[2][1][0]), j1 = rcpf(ot[2][0][1] + ot[2][1][1]); uint32_t ow[4]; \
            _Pragma("unroll") for (int i = 0; i < 4; i++) \
                ow[i] = opq(pack2((ot[i >> 1][0][2 * (i & 1)] + ot[i >> 1][1][2 * (i & 1)]) * j0, (ot[i >> 1][0][2 * (i & 1) + 1] + ot[i >> 1][1][2 * (i & 1) + 1]) * j1))
        #define ST_O() do { uint32_t* og = (uint32_t*)((char*)g_O + (u_og + (l16 >> 2))); \
            _Pragma("unroll") for (int i = 0; i < 4; i++) og[(i >> 1) * 256 + (i & 1) * 32] = ow[i]; } while (0)
        #define BSO() ((u_bs) ^ ((l16 & 0x10) + ((l16 >> 3) & 0xC) + (l16 & 0x80) * 0x20 + (l16 & 0x100) * 0x80))
        const uint32_t taus = phase(seg);
        const uint64_t* const dq = c_xd + (s & 1) * 32; const uint64_t* const dv = dq + (wg * 16 | uz);
        float acc[16], acv[16];
        uint32_t u[8];
        if constexpr (wg == 0) {
            if (s == NSEG - 1) { bsync<B_GO, 256>(); st_g32(at(BSO(), rbhi), 0); mbar_wait(MB_KV, 1); if (XDL == 300) mbar_wait(MB_X, 1); break; }
            load_frag<16 - EV, 16, 2048>(VEB + t16, T);
            bsync<B_GO, 256>();
            PROF(8);
            wg_run<0, 16 - EV>(acv, T, dv);
            wg_run<16 - EV, 16>(acv, T, dv);
            wg_run<0, 5>(acc, W, dq); wg_wait<1>();
            qk_pack(acv, u);
            #pragma unroll
            for (int i = 0; i < 8; i++) u[i] = opq(u[i]);
            CUT(pa);
            wg_run<5, 8>(acc, W, dq);
            __syncwarp();
            sts128(SC + opq(t16), make_uint4(u[0], u[1], u[2], u[3])); sts128(SC + 2048 + opq(t16), make_uint4(u[4], u[5], u[6], u[7]));
            barrive<B_VX, 256>();
            __syncwarp();
            PROF(9);
            wg_run<8, 12>(acc, W, dq);
            CUT(pa);
            char* const bs = at(opq(BSO()), opq(rbhi));
            CUT(pa);
            wg_run<12, 15>(acc, W, dq);
            CUT(pa);
            const uint32_t ro = opq(l16 * 8 + ((l16 & 0x70) ^ ((w8 & 3) << 5))), ro2 = opq(ro ^ 0x10);
            const uint32_t mG = opq((l16 & 0x1C0) ? 0 : 0x10001u), mB = opq((((l16 >> 2) & 4) + ((l16 >> 5) & 3)) == ((u_bs >> 7) & 7) ? 1 : 0), zz = t16 >> 18;
            CUT(pa);
            wg_run<15, 18>(acc, W, dq);
            CUT(pa);
            const uint32_t one[4] = {opq(ONES | zz), opq(ONES ^ zz), opq(ONES + zz), opq(ONES - zz)};
            const uint32_t par = s & 1, tt = tau * 0x10001u;
            CUT(pa);
            wg_run<18, RP>(acc, W, dq);
            CUT(pa);
            PROF(10);
            mbar_wait(MB_R, par);
            PROF(14);
            uint32_t x[8], bad;
            float d[4][4];
            #define SUM_R() do { ldsm4t(x[0], x[1], x[2], x[3], RS + ro); ldsm4t(x[4], x[5], x[6], x[7], RS + ro2); \
                _Pragma("unroll") for (int i = 0; i < 4; i++) { d[i][0] = d[i][1] = d[i][2] = d[i][3] = 0.f; mmaq(d[i], one, x[2 * i], x[2 * i + 1]); } } while (0)
            #define PUT_B() do { bad = late(stale<2, 1>(x, tt), stale<2, 1>(x + 2, tt), mG); \
                const uint32_t w0 = pack2(d[0][0] + d[1][0], d[0][1] + d[1][1]), w1 = pack2(d[2][0] + d[3][0], d[2][1] + d[3][1]); \
                asm volatile("{ .reg .pred p; setp.eq.b32 p, %2, 0; @p st.relaxed.gpu.global.u32 [%0], %1; }" :: "l"(bs), "r"(tagm((l16 & 0x40) ? w1 : w0, mB, tt)), "r"(bad) : "memory"); } while (0)
            SUM_R();
            CUT(pa);
            wg_run<RP, (RP + RQ < 32 ? RP + RQ : 32)>(acc, W, dq);
            if (RP + RQ >= RL) barrive<B_BT, 256>();
            CUT(pa);
            PUT_B();
            const uint32_t tb = lds32(SUM + 272 + 28 + zz);
            CUT(pa);
            PROF(11);
            if (RP + RQ < RL) { wg_run<RP + RQ, RL>(acc, W, dq); __syncwarp(); barrive<B_BT, 256>(); __syncwarp(); }
            wg_run<(RP + RQ < RL ? RL : RP + RQ), 32>(acc, W, dq);
            CUT(pa);
            AGAIN(5, ld_g128(x, at(u_rl + opq(ro), rbhi)); ld_g128(x + 4, at(u_rl + opq(ro2), rbhi)); sts128(RS + ro, make_uint4(x[0], x[1], x[2], x[3])); sts128(RS + ro2, make_uint4(x[4], x[5], x[6], x[7]));
                     CUT(pa); __syncwarp(); SUM_R(); PUT_B(), bad)
            #define REQ_B() if (w8 == 3) { TRC(13, gtime() - tb); wait_g(tb, t16); GET_B(0); PROFW(13, 3); }
            if (!BL) REQ_B();
            const uint32_t ps = opq(pb & 0xFFFF), ps2 = opq(ps ^ HI8);
            char* const qd0 = TOK_DST() + ps; char* const qd1 = TOK_DST() + ps2;
            TAGM();
            wg_wait<0>();
            pack_tag(acc, u, taus, tm);
            #pragma unroll
            for (int i = 0; i < 8; i++) u[i] = opq(u[i]);
            CUT(pa);
            if (BL) REQ_B();
            bsync<B_S0, 128>();
            st_if(seg < NSEG, qd0, u); st_if(seg < NSEG, qd1, u + 4);
            if (XDL >= 200 && XDL < 300 && w8 == 1) { CUT(pb); DELAY(XDL - 200); load_x(tmX, c, seg + 1, (s & 1) ? XT : XT2); }
            PROF(12);
        } else {
            #define LAST() __reduce_max_sync(~0u, max(max(an[0], an[1]), max(an[2], an[3])))
            PK_O();
            CUT(pa);
            if (s == NSEG - 1) { ST_O(); break; }
            PROF(8);
            if (w8 != 7) {
                load_frag<16 - EV, 16 - EV + TA0, 2048>(VEB + t16, T);
                mbar_wait(MB_KV, s & 1);
                AGAIN(0, refetch_kv(c, s + 1, w8 - 4, l16), kv_stale(w8 - 4, l16, phase(s + 1)))
            } else {
                uint32_t tr = LAST();
                AGAIN(8, ld_g128(an, at(u_ta + l16, rbhi)); tr = LAST(), late(stale<2, 1>(an, s), stale<2, 1>(an + 2, s), 31))
                tr = (tr & ~31u) + P(0);
                TRC(14, gtime() - tr);
                wait_g(tr, t16);
                if (R4) { for (int i = 0; i < 4; i++) bulk_copy(RS + i * 1024, at(u_rl + i * 1024, rbhi), 1024, MB_R); }
                else bulk_copy(RS, at(u_rl, rbhi), 4096, MB_R);
                PROFW(14, 3);
                sts32(SUM + 272 + 28, tr + P(1));
                load_frag<16 - EV, 16 - EV + TA0, 2048>(VEB + t16, T);
                if (XDL < 100) { CUT(pb); DELAY(XDL); load_x(tmX, c, seg + 1, (s & 1) ? XT : XT2); }
            }
            CUT(pa);
            bsync<B_VX, 256>();
            lds128u(u, SC - 2048 + opq(t16)); lds128u(u + 4, SC + opq(t16));
            CUT(pa);
            ST_O();
            CUT(pa);
            load_frag<16 - EV + TA0, 16 - EV + TA, 2048>(VEB + t16, T);
            acc_init(acv, u);
            #pragma unroll
            for (int i = 0; i < 16; i++) acv[i] = opqf(acv[i]);
            const uint32_t ps = opq(pb & 0xFFFF), ps2 = opq(ps ^ HI8);
            CUT(pa);
            PROF(9);
            if (XDL == 100 && w8 == 7) load_x(tmX, c, seg + 1, (s & 1) ? XT : XT2);
            bsync<B_BT, 256>();
            CUT(pa);
            wg_run<0, 3>(acc, W, dq);
            PROF(11);
            wg_run<3, NT, true>(acc, W, dq);
            __syncwarp();
            load_frag<16 - EV + TA, 16, 2048>(VEB + t16, T);
            __syncwarp();
            wg_run<NT, NB>(acc, W, dq);
            char* const qd0 = TOK_DST() + ps; char* const qd1 = TOK_DST() + ps2;
            TAGM();
            wg_run<NB, 32>(acc, W, dq);
            wg_run<0, 5, true>(acv, T, dv);
            wg_wait<1>();
            PROF(12);
            pack_tag(acc, u, taus, tm);
            #pragma unroll
            for (int i = 0; i < 8; i++) u[i] = opq(u[i]);
            CUT(pa);
            wg_run<5, 16 - EV>(acv, T, dv);
            __syncwarp();
            st_if(seg < NSEG, qd0, u); st_if(seg < NSEG, qd1, u + 4);
            __syncwarp();
            wg_run<16 - EV, 16>(acv, T, dv);
            CUT(pa);
            PROF(10);
            wg_wait<0>();
            PROF(13);
            pack_tag(acv, u, taus, tm);
            st_if(seg < NSEG, qd0 + 16384, u); st_if(seg < NSEG, qd1 + 16384, u + 4);
        }
        sb++;
        u_rs ^= 1 << 20; u_rl ^= 1 << 20; u_bs ^= 1 << 20; u_bl ^= 1 << 20; u_x ^= 1 << 20; u_xs ^= 1 << 20; u_ta ^= 1 << 20; u_rp ^= 1 << 20; u_og += 262144;
    }
}

namespace ck {
constexpr uint32_t UPL = 144 * 16 + 64, UCH = 2 * UPL;
constexpr uint32_t FCP = 4160, FCH = 2 * FCP;
template <int NW> struct At { static constexpr uint32_t K = NW == 2 ? mk::XT : mk::SB, V = K + 32768, F = NW == 2 ? V : V + 32768, U = F + 8 / NW * FCH; };
static_assert(At<2>::U + 4 * UCH <= mk::OB && At<1>::U + 8 * UCH <= mk::OB, "");
}
struct ConvIn { const bf16 *q, *shift_k, *ssm_k, *ssm_D, *gate_w; };
template <int NW> struct ConvRaw { uint4 f[8 / NW], sk[4 / NW]; uint32_t fn, d; };
template <int NW> __device__ __forceinline__ void strip_request(const CUtensorMap* tmK, int grp) {
    mbar_expect(mk::MB_C, 65536);
    #pragma unroll 1
    for (int i = 0; i < 16; i++) tma3d(ck::At<NW>::K + i * 4096, tmK + (i >> 3), grp * 8, 0, i & 7, mk::MB_C);
}
template <int NW> __device__ __forceinline__ void conv_load(ConvRaw<NW>& r, const ConvIn& in, int ch0) {
    const int tid = threadIdx.x, w = tid >> 5, ch = ch0 + w / NW, e = w % NW;
    const bf16* fp = in.ssm_k + (size_t)ch * SEQ + e * 1024;
    #pragma unroll
    for (int i = 0; i < 8 / NW; i++) r.f[i] = __ldg((const uint4*)fp + (tid & 31) + 32 * i);
    r.fn = e == NW - 1 ? 0 : __ldg((const uint32_t*)(fp + 1024));
    r.d = __ldg((const unsigned short*)in.ssm_D + ch);
    #pragma unroll
    for (int i = 0; i < 4 / NW; i++) r.sk[i] = __ldg((const uint4*)(in.shift_k + ch0 * 4) + i);
}
template <int NW> __device__ __forceinline__ void kv_build(const ConvRaw<NW>& r, int ch0) {
    using namespace ck;
    const int tid = threadIdx.x;
    if (tid < 32 * 8 / NW) sts128(At<NW>::U + (tid >> 4) * UPL + (tid & 15) * 16, make_uint4(0, 0, 0, 0));
    #pragma unroll
    for (int hf = 0; hf < 2 / NW; hf++) {
        const uint32_t a = tid * 16 + (ch0 & 4) * 2 + hf * 8;
        float2 kr[11], vr[8];
        #pragma unroll
        for (int i = 0; i < 11; i++) { kr[i] = lds64f(At<NW>::K + ((i + 5) & 7) * 4096 - (i < 3) * 16 + a); if (i < 3 && !tid) kr[i] = make_float2(0.f, 0.f); }
        #pragma unroll
        for (int i = 0; i < 8; i++) vr[i] = lds64f(At<NW>::V + i * 4096 + a);
        #pragma unroll
        for (int ch = 0; ch < 4; ch++) {
            const uint32_t s01 = ((const uint32_t*)r.sk)[8 * hf + 2 * ch], s23 = ((const uint32_t*)r.sk)[8 * hf + 2 * ch + 1];
            const float sk[4] = {bflo(s01), bfhi(s01), bflo(s23), bfhi(s23)};
            float kf[11], kv[8];
            #pragma unroll
            for (int i = 0; i < 11; i++) { const uint32_t wd = __float_as_uint((ch & 2) ? kr[i].y : kr[i].x); kf[i] = (ch & 1) ? bfhi(wd) : bflo(wd); }
            #pragma unroll
            for (int i = 0; i < 8; i++) {
                const uint32_t wv = __float_as_uint((ch & 2) ? vr[i].y : vr[i].x);
                kv[i] = fmaf(kf[i + 3], sk[0], fmaf(kf[i + 2], sk[1], fmaf(kf[i + 1], sk[2], kf[i] * sk[3]))) * ((ch & 1) ? bfhi(wv) : bflo(wv));
            }
            sts128(At<NW>::U + (hf * 4 + ch) * UCH + (tid & 1) * UPL + (16 + (tid >> 1)) * 16,
                   make_uint4(pack2(kv[0], kv[1]), pack2(kv[2], kv[3]), pack2(kv[4], kv[5]), pack2(kv[6], kv[7])));
        }
    }
}
template <int NW> __device__ __forceinline__ void conv_filter(const ConvRaw<NW>& r) {
    using namespace ck;
    constexpr int N = 8 / NW;
    const int w = threadIdx.x >> 5, lane = threadIdx.x & 31, e = w % NW;
    const uint32_t fb = At<NW>::F + w / NW * FCH;
    if (!e && lane < 8) { sts32(fb + 4128 + lane * 4, 0); sts32(fb + FCP + 4128 + lane * 4, lane ? 0 : r.f[0].x & 0xFFFFu); }
    #pragma unroll
    for (int i = 0; i < N; i++) {
        const int vi = e * 128 + lane + 32 * i;
        const uint4 x = r.f[i];
        const uint32_t a = __shfl_down_sync(~0u, x.x, 1), b = i < N - 1 ? __shfl_sync(~0u, r.f[i < N - 1 ? i + 1 : i].x, 0) : r.fn;
        const uint32_t nxt = lane == 31 ? b : a;
        const uint32_t ea = fb + (2056 - 8 * vi) * 2;
        sts128(ea, make_uint4(__byte_perm(x.w, 0, 0x1032), __byte_perm(x.z, 0, 0x1032), __byte_perm(x.y, 0, 0x1032), __byte_perm(x.x, 0, 0x1032)));
        sts128(ea + FCP, make_uint4(__byte_perm(nxt, x.w, 0x7610), __byte_perm(x.w, x.z, 0x7610), __byte_perm(x.z, x.y, 0x7610), __byte_perm(x.y, x.x, 0x7610)));
    }
}
template <int NW> __device__ __forceinline__ void conv_mma(int ch0, uint32_t d, uint32_t zero) {
    using namespace ck;
    constexpr int N = 16 / NW;
    const int w = threadIdx.x >> 5, lane = threadIdx.x & 31, ch = w / NW, e = w % NW, g = lane >> 2, t = lane & 3;
    float acc[N][4] = {};
    uint32_t fa = At<NW>::F + ch * FCH + ((g & 1) ? (2063 - g + 2 * t) * 2 : FCP + (2064 - g + 2 * t) * 2);
    uint32_t ua = At<NW>::U + ch * UCH + ((lane >> 3) & 1) * UPL + (24 + (e - NW) * 8 + (lane >> 4) * 8 + (lane & 7)) * 16;
    uint32_t Fr[32], A[2][8], yo = (ch0 + ch) * 512 + e * 32 + t * 8 + g;
    const uint32_t t16 = CC ? lane | zero : lane;
    #define LD_U(m0, m1) _Pragma("unroll") for (int m = m0; m < m1; m++) ldsm4(Fr[4 * m], Fr[4 * m + 1], Fr[4 * m + 2], Fr[4 * m + 3], ua + m * 256)
    #define LD_F(b, o, p) _Pragma("unroll") for (int i = 0; i < 2; i++) { const uint32_t x_ = fa - (o) * 32 - (i ? 15 - (p) : (p)) * 256; \
        A[b][4 * i] = lds32(x_); A[b][4 * i + 1] = lds32(x_ - 16); A[b][4 * i + 2] = lds32(x_ + 16); }
    #define ROW(a, q, j0, j1) _Pragma("unroll") for (int j = j0; j < j1; j++) mmaq(acc[j], a, Fr[2 * (NW * j + NW - 1 - (q))], Fr[2 * (NW * j + NW - 1 - (q)) + 1])
    LD_U(0, 8);
    LD_F(0, 0, 0);
    {
        const uint32_t da = (g >> 1) == t ? d << ((g & 1) * 16) : 0, D[4] = {da, zero, zero >> 1, da ^ zero};
        ROW(D, 0, 0, N);
    }
    #pragma unroll 1
    for (int r = 0; r < 8; r++) {
        ua -= 16;
        #pragma unroll
        for (int p = 0; p < 8; p++) {
            uint32_t* const a = A[p & 1];
            a[3] = a[0] ^ zero; a[7] = a[4] ^ zero;
            LD_F(~p & 1, p == 7, (p + 1) & 7);
            if (p >= 2 && !(p & 1)) { LD_U(8 - p / 2, 9 - p / 2); }
            ROW(a, p, p / NW, 3);
            CUT(yo);
            ROW(a + 4, 15 - p, (15 - p) / NW, N);
            CUT(yo);
            ROW(a, p, (p / NW > 3 ? p / NW : 3), N);
            CUT(yo);
        }
        LD_U(0, 5);
        fa -= 32;
    }
    uint2* y = (uint2*)g_Y + yo;
    #pragma unroll
    for (int j = 0; j < N; j++) {
        const uint32_t p0 = pack2(acc[j][0], acc[j][2]), p1 = pack2(acc[j][1], acc[j][3]), x = __shfl_xor_sync(~0u, (g & 1) ? p0 : p1, 4);
        const uint32_t lo = (g & 1) ? x : p0, hi = (g & 1) ? p1 : x;
        y[j * 32 * NW] = make_uint2(__byte_perm(lo, hi, 0x5410), __byte_perm(lo, hi, 0x7632));
    }
}
__device__ __noinline__ void spare(const CUtensorMap* tmK, const ConvIn in, int i, uint32_t zero) {
    const int w = __shfl_sync(~0u, threadIdx.x >> 5, 0), lane = threadIdx.x & 31;
    ConvRaw<1> raw;
    uint4 x[4][4];
    int n = 0;
    #pragma unroll 1
    for (int grp = NCTA / 2 - 4 + i; n <= NSP; grp += 4, n++) {
        const bool on = n && grp < 128;
        if (on) { mbar_wait(mk::MB_C, n & 1); kv_build<1>(raw, grp * 8); conv_filter<1>(raw); }
        const uint32_t d = raw.d;
        asm volatile("fence.proxy.async.shared::cta;" ::: "memory");
        __syncthreads();
        if (grp + 4 < 128) { if (w == 0 && elect()) strip_request<1>(tmK, grp + 4); __syncwarp(); conv_load<1>(raw, in, grp * 8 + 32); }
        const int row = n * 128 - 128 + i * 32 + w * 4;
        if (n) {
            #pragma unroll
            for (int j = 0; j < 16; j++) x[j >> 2][j & 3] = __ldg((const uint4*)(in.q + (size_t)(row + (j >> 2)) * DM) + lane + 32 * (j & 3));
        }
        if (on) conv_mma<1>(grp * 8, d, zero);
        if (n) {
            float a[4] = {};
            #pragma unroll
            for (int k = 0; k < 4; k++) {
                const uint4 gw = __ldg((const uint4*)in.gate_w + lane + 32 * k);
                #pragma unroll
                for (int j = 0; j < 16; j++) { const uint32_t gg = ((const uint32_t*)&gw)[j & 3], u = ((const uint32_t*)&x[j >> 2][k])[j & 3]; a[j >> 2] = fmaf(bflo(u), bflo(gg), fmaf(bfhi(u), bfhi(gg), a[j >> 2])); }
            }
            #pragma unroll
            for (int j = 0; j < 20; j++) a[j & 3] += __shfl_xor_sync(~0u, a[j & 3], 16 >> (j >> 2));
            if (lane < 4) g_gate[row + lane] = 1.f / (1.f + __expf(-(lane & 2 ? (lane & 1 ? a[3] : a[2]) : (lane & 1 ? a[1] : a[0]))));
        }
        __syncthreads();
    }
}

__device__ __forceinline__ uint32_t round_trip(char* a, int n) {
    uint32_t best = 0x7FFFu;
    #pragma unroll 1
    for (int i = 0; i < n; i++) {
        uint32_t v; const uint32_t t0 = clk();
        asm volatile("atom.relaxed.gpu.global.exch.b32 %0, [%1], %2;" : "=r"(v) : "l"(a), "r"(i) : "memory");
        if (v == 0x7FC1A5A5u) g_err = 2;
        best = min(best, clk() - t0);
    }
    return (__popc((uint32_t)(uintptr_t)a & HOME_BITS) & 1) ? best << 16 | 0x7FFFu : best | 0x7FFF0000u;
}
__device__ __forceinline__ int place(int by_sm) {
    uint32_t sm = blockIdx.x;
    if (by_sm) asm volatile("mov.u32 %0, %%smid;" : "=r"(sm));
    const uint32_t g = sm < 64 ? (sm & 15) >> 1 : 1 + (sm - 64) % 14 / 2, j = sm < 64 ? sm >> 4 : 4 + (sm - 64) / 14;
    return sm < 120 ? (g ? g * 16 - 8 : 0) + j * 2 + (sm & 1) : sm;
}
__device__ __forceinline__ void publish(char* rb, int p) {
    const int t = threadIdx.x, i = p * 4 + (t >> 6);
    char* line = rb + RB_P + (i & 31) * 128 + (i >> 5) * 8192 + (t & 32) * 128;
    if ((t & 31) < 2) st_g128(line + (t & 1) * 16, 0, 0, 0, 0);
    __syncwarp();
    if (!(t & 31)) sts32(mk::SUM + (t >> 3), round_trip(line, NPR));
    __syncthreads();
    if (t == 32) {
        const uint4 x = lds128(mk::SUM), y = lds128(mk::SUM + 16);
        st_g32(g_cls + p, 0x80000000u | __vminu2(__vminu2(__vminu2(x.x, x.y), __vminu2(x.z, x.w)), __vminu2(__vminu2(y.x, y.y), __vminu2(y.z, y.w))));
    }
}
__device__ __forceinline__ uint32_t survey(uint32_t& x) {
    const int lane = threadIdx.x & 31;
    uint32_t a[4], b[2];
    int n = 0;
    do { ld_g128(a, g_cls + lane * 4); ld_g64(b, g_cls + 120 + lane % 6 * 2); } while (__any_sync(~0u, !((a[0] & a[1] & a[2] & a[3] & b[0] & b[1]) >> 31)) && ++n < SPIN_LIMIT);
    const uint32_t m = __vminu2(__vminu2(a[0], a[1]), __vminu2(a[2], a[3])), e = __vminu2(b[0], b[1]);
    const uint32_t M = __ballot_sync(~0u, (m >> 16 & 0x7FFF) < (m & 0xFFFF)) & 0x3FFFFFFF, E = __ballot_sync(~0u, (e >> 16 & 0x7FFF) < (e & 0xFFFF)) & 63;
    const int x0 = min(max(max(__popc(M) - 14, 2 - __popc(E) / 2), 0), min(2, (6 - __popc(E)) / 2));
    x = E | x0 << 8;
    return M | (x0 < 1) << 30 | (x0 < 2) << 31;
}
__device__ __forceinline__ int role(int p, uint32_t x) {
    if (p < 120) return p;
    const int i = (p - 120) >> 1, x0 = x >> 8, side = x >> i & 1, r = __popc((side ? x : ~x) & ((1 << i) - 1)), e0 = 6 - __popc(x & 63);
    const int pair = !side ? (r < 2 * x0 ? r : 4 + r - 2 * x0) : (r < 4 - 2 * x0 ? 2 * x0 + r : e0 + r);
    return 120 + 2 * pair + (p & 1);
}
__device__ __forceinline__ void tma_prefetch(const CUtensorMap* m, int c0, int c1) {
    asm volatile("cp.async.bulk.prefetch.tensor.2d.L2.global [%0, {%1, %2}];" :: "l"(m), "r"(c0), "r"(c1) : "memory");
}

struct KVMaps { CUtensorMap m[2]; };
__global__ void __launch_bounds__(256, 1)
main_kernel(const __grid_constant__ CUtensorMap tmWq, const __grid_constant__ CUtensorMap tmWk, const __grid_constant__ CUtensorMap tmWv,
            const __grid_constant__ CUtensorMap tmWo, const __grid_constant__ CUtensorMap tmX,
            const __grid_constant__ KVMaps tmK, const bf16* __restrict__ mem0,
            const __grid_constant__ ConvIn in, const __grid_constant__ MainParams prm) {
    using namespace mk;
    extern __shared__ __align__(1024) uint8_t smem_raw[];
    if (smem_u32(smem_raw) != SB) __trap();
    TL(0); TL(2);
    const int tid0 = threadIdx.x, w8 = __shfl_sync(~0u, tid0 >> 5, 0), wg = w8 >> 2;
    const int p = __shfl_sync(~0u, place(prm.by_sm), 0);
    auto get_qk = [&](int c) {
        mbar_expect(MB_WQ, 65536); mbar_expect(MB_WK, 65536);
        for (int i = 0; i < 2; i++) { tma2d(WO + i * 32768, &tmWq, (c >> 1) * 64, (c & 1) * 512 + i * 256, MB_WQ); tma2d(WV + i * 32768, &tmWk, (c >> 1) * 64, (c & 1) * 512 + i * 256, MB_WK); }
    };
    if (w8 == 0 && elect()) {
        for (int i = 0; i < 9; i++) mbar_init(BAR + i * 8, 1);
        asm volatile("fence.mbarrier_init.release.cluster;" ::: "memory");
        asm volatile("fence.proxy.async.shared::cta;" ::: "memory");
        sts32(SUM + 256, 0); sts32(SUM + 268, 0); mbar_arrive(MB_B);
    }
    if (tid0 >= 252) asm volatile("prefetch.tensormap [%0];" :: "l"(tid0 == 252 ? &tmWq : tid0 == 253 ? &tmWk : tmK.m + (tid0 & 1)) : "memory");
    __syncwarp();
    publish(prm.rb, p);
    TLX(16);
    if (w8 == 0 && elect()) {
        strip_request<2>(tmK.m, p >> 1);
        if (p < 120) get_qk(p);
        else if (p < 128) for (int i = 0; i < 2; i++) { tma_prefetch(&tmWq, (p >> 1) * 64, (p & 1) * 512 + i * 256); tma_prefetch(&tmWk, (p >> 1) * 64, (p & 1) * 512 + i * 256); }
    }
    __syncwarp();
    int c;
    uint32_t M;
    {
        ConvRaw<2> raw;
        conv_load<2>(raw, in, p * 4);
        uint32_t x;
        M = survey(x);
        c = role(p, x);
        TLX(17);
        if (w8 == 0 && p >= 120 && c < 128 && elect()) get_qk(c);
        asm volatile("griddepcontrol.launch_dependents;" ::: "memory");
        mbar_wait(MB_C, 0);
        TLX(22);
        kv_build<2>(raw, p * 4);
        __syncthreads();
        TLX(14);
        if (w8 == 0 && c < 128 && elect()) {
            mbar_expect(MB_X, 32768); tma3d(XT, &tmX, 0, 32, (c & 1) * 8, MB_X);
            for (int i = 0; i < 4; i++) tma_prefetch(&tmWo, (c & 3) * 256 + i * 64, (c >> 2) * DH);
            for (int i = 0; i < 2; i++) tma_prefetch(&tmWv, (c >> 1) * 64, (c & 1) * 512 + i * 256);
        }
        __syncwarp();
        conv_filter<2>(raw);
        __syncthreads();
        TL(9);
        conv_mma<2>(p * 4, raw.d, prm.zero);
    }
    if (c >= 128) { spare(tmK.m, in, c - 128, prm.zero); TLX(18); return; }
    const int kap = c & 1;
    TL(1);
    asm volatile("fence.proxy.async.shared::cta;" ::: "memory");
    __syncthreads();
    if (w8 == 0 && elect()) { mbar_expect(MB_KV, 32768); tma3d(TK, &tmX, 0, 0, kap * 8, MB_KV); }
    {
        uint32_t m[8];
        #pragma unroll
        for (int i = 0; i < 8; i++) m[i] = __ldg((const uint32_t*)(mem0 + i * DM + kap * 512) + tid0);
        sts128(MEM + tid0 * 32, make_uint4(__byte_perm(m[0], m[1], 0x5410), __byte_perm(m[2], m[3], 0x5410), __byte_perm(m[4], m[5], 0x5410), __byte_perm(m[6], m[7], 0x5410)));
        sts128(MEM + tid0 * 32 + 16, make_uint4(__byte_perm(m[0], m[1], 0x7632), __byte_perm(m[2], m[3], 0x7632), __byte_perm(m[4], m[5], 0x7632), __byte_perm(m[6], m[7], 0x7632)));
    }
    uint32_t W[128], T[64];
    mbar_wait(wg ? MB_WK : MB_WQ, 0);
    TLX(19);
    load_tile<0, 32>(tile_off(tid0 & 31, 2 * (w8 & 3)) + (wg ? WV : WO), W);
    __syncthreads();
    if (w8 == 0 && elect()) {
        mbar_expect(MB_WO, 65536);
        for (int i = 0; i < 4; i++) tma2d(WO + i * 16384, &tmWo, (c & 3) * 256 + i * 64, (c >> 2) * DH, MB_WO);
        mbar_expect(MB_WV, 65536); tma2d(WV, &tmWv, (c >> 1) * 64, kap * 512, MB_WV); tma2d(WV + 32768, &tmWv, (c >> 1) * 64, kap * 512 + 256, MB_WV);
    }
    uint32_t t16 = tid0 * 16, pa, pb;
    {
        const int lane = tid0 & 31, w = w8 & 3, g = lane >> 2, t = lane & 3;
        auto vec = [](int hf, int gg, int ch) { return hf * 512 + (gg >> 1) * 128 + (gg & 1) * 64 + ((ch ^ (gg >> 1) ^ (hf << 1)) << 4); };
        const int kg = ((lane >> 3) & 1) * 4 + ((lane & 7) >> 1);
        pa = wg ? w * 1024 + vec((lane >> 3) & 1, lane & 7, lane >> 4)
                : ((lane >> 4) * 4096 + w * 1024 + vec(lane & 1, kg, 2 * (w & 1))) | ((lane & 8) * 256 + w * 256 + (lane & 1) * 128 + ((((lane >> 4) ^ (lane & 1)) * 4 + ((lane & 7) >> 1)) << 4)) << 16;
        pb = (wg ? w * 1024 + vec(0, g, t) : t * 4096 + w * 256 + g * 16) | (w * 256 + t * 64 + (g & 3) * 8 + (g >> 2) * 4) << 16;
    }
    int budget = SPIN_LIMIT;
    const uint32_t ps = pb & 0xFFFF;
    #define ST_TOK(o) do { TAGM(); pack_tag(acc, u, 1, tm); st_if(true, tok_dst(c, seg, wg) + ((o) + ps), u); st_if(true, tok_dst(c, seg, wg) + ((o) + (ps ^ HI8)), u + 4); } while (0)
    #pragma unroll 1
    for (int seg = 1; seg >= 0; seg--) {
        float acc[16];
        uint32_t u[8];
        mbar_wait(seg ? MB_X : MB_KV, 0);
        wg_run<0, 32>(acc, W, c_xd + (seg ? 0 : 64));
        wg_wait<0>();
        ST_TOK(0);
    }
    {
        mbar_wait(MB_WO, 0);
        TLX(20);
        const int lane = tid0 & 31;
        const uint32_t a = (tid0 >> 6) * 16384 + tile_off(lane, (w8 & 1) * 4) + WO;
        #pragma unroll
        for (int i = 0; i < 16; i++) ldsm4t(T[4 * i], T[4 * i + 1], T[4 * i + 2], T[4 * i + 3], ((i & 2) ? a ^ 32 : a) + ((i >> 2) + 4 * (i & 1)) * 2048);
        __syncthreads();
        const uint32_t d = WO + w8 * 512 + ((lane >> 3) * 4 + (lane & 3)) * 16 + ((lane >> 2) & 1) * 4;
        #pragma unroll
        for (int i = 0; i < 64; i++) sts32(d + (i >> 2) * 4096 + (i & 1) * 256 + (i & 2) * 4, T[i]);
    }
    mbar_wait(MB_WV, 0);
    TLX(21);
    load_tile<0, 16>(tile_off(tid0 & 31, 2 * (w8 & 3)) + wg * 32768 + WV, T);
    #pragma unroll 1
    for (int seg = 0; seg < 2; seg++) {
        float acc[16];
        uint32_t u[8];
        wg_run<0, 16>(acc, T, c_xd + (seg ? 0 : 64) + wg * 16);
        wg_wait<0>();
        const uint32_t x = SC + seg * 4096 + (t16 & 2047);
        if (!wg) { qk_pack(acc, u); sts128(x, make_uint4(u[0], u[1], u[2], u[3])); sts128(x + 2048, make_uint4(u[4], u[5], u[6], u[7])); }
        __syncthreads();
        if (wg) { lds128u(u, x); lds128u(u + 4, x + 2048); acc_add(acc, u); ST_TOK(16384); }
    }
    if (w8 == 1) { bulk_expect(MB_X, 32768); load_x(&tmX, c, 2, XT); }
    uint32_t u_rs, u_rl, u_bs, u_bl;
    const uint32_t rbhi = (uint32_t)((uintptr_t)prm.rb >> 32);
    {
        const int lane = tid0 & 31, h = c >> 2, j = c & 3;
        uint32_t cl;
        const uint32_t below = (1u << h) - 1;
        const int pos = ((M >> h) & 1) ? 32 - __popc(M) + __popc(M & below) : __popc(~M & below), G = pos >> 4, rk = pos & 15;
        auto half = [&](uint32_t off) { return (uint32_t)(uintptr_t)prm.rb + off + ((__popc(off & HOME_BITS) ^ G) & 1) * 4096; };
        auto rpair = [&](int m) { return RB_R + (j << 16) + ((m & 1) << 13) + (((m >> 1) & 3) << 14) + ((m >> 3) << 18); };
        u_rs = (half(rpair(2 * w8)) ^ (G << 12)) + h * 128 + (h & 7) * 16;
        u_rl = half(rpair(rk));
        u_bs = (uint32_t)(uintptr_t)prm.rb + RB_B + ((j & 1) << 13) + ((j >> 1) << 16) + rk * 256 + G * 128 + (w8 & 3) * 32;
        u_bl = half(RB_B + (kap << 16));
        if (w8 == 0) {
            const char* v0 = kv_src(c, 0) + 16384 + lane * 128 + (lane & 3) * 4;
            do cl = ld_g32(v0) & ld_g32(v0 + 4096) & ld_g32(v0 + 8192) & ld_g32(v0 + 12288); while (__any_sync(~0u, !(cl & 1)) && --budget > 0);
            get_kv(c, 0);
        }
    }
    mbar_wait(MB_KV, 1);
    if (w8 < 3) while (kv_stale(w8, t16 & 0x1F0, 1) && --budget > 0) refetch_kv(c, 0, w8, t16 & 0x1F0);
    asm volatile("fence.proxy.async.shared::cta;" ::: "memory");
    TLX(7);
    __syncwarp();
    const Ctx cx = {u_rs, u_rl, u_bs, u_bl, (uint32_t)(uintptr_t)prm.rb, rbhi, w8, c};
    if (wg) steps<1>(W, T, t16, pa, pb, cx, &tmX, prm); else steps<0>(W, T, t16, pa, pb, cx, &tmX, prm);
    TLX(3);
}

namespace ok {
constexpr int STAGES = 4;
constexpr uint32_t STG = 49152, TOTAL = STAGES * STG + 32768 + 256;
}
#define R8(o) F4(d, o), F4(d, o + 4)
__device__ __forceinline__ void wgmma_n256_ss_tt(float* d, uint64_t da, uint64_t db, int accum) {
    asm volatile("{.reg .pred p; setp.ne.b32 p, %130, 0;\n"
        "wgmma.mma_async.sync.aligned.m64n256k16.f32.bf16.bf16 {%0,%1,%2,%3,%4,%5,%6,%7,%8,%9,%10,%11,%12,%13,%14,%15,"
        "%16,%17,%18,%19,%20,%21,%22,%23,%24,%25,%26,%27,%28,%29,%30,%31,%32,%33,%34,%35,%36,%37,%38,%39,%40,%41,%42,%43,%44,%45,%46,%47,"
        "%48,%49,%50,%51,%52,%53,%54,%55,%56,%57,%58,%59,%60,%61,%62,%63,%64,%65,%66,%67,%68,%69,%70,%71,%72,%73,%74,%75,%76,%77,%78,%79,"
        "%80,%81,%82,%83,%84,%85,%86,%87,%88,%89,%90,%91,%92,%93,%94,%95,%96,%97,%98,%99,%100,%101,%102,%103,%104,%105,%106,%107,%108,%109,%110,%111,"
        "%112,%113,%114,%115,%116,%117,%118,%119,%120,%121,%122,%123,%124,%125,%126,%127}, %128, %129, p, 1, 1, 1, 1;}"
        : R8(0), R8(8), R8(16), R8(24), R8(32), R8(40), R8(48), R8(56), R8(64), R8(72), R8(80), R8(88), R8(96), R8(104), R8(112), R8(120)
        : "l"(da), "l"(db), "r"(accum));
}
#undef R8
__global__ void __cluster_dims__(2, 1, 1) __launch_bounds__(288, 1)
out_kernel(const __grid_constant__ CUtensorMap tmO, const __grid_constant__ CUtensorMap tmWo, const __grid_constant__ CUtensorMap tmA,
           const __grid_constant__ CUtensorMap tmOut, const __grid_constant__ CUtensorMap tmQ) {
    using namespace ok;
    extern __shared__ __align__(1024) uint8_t smem_raw[];
    const uint32_t SB = smem_u32(smem_raw), AT = SB + STAGES * STG, BAR = AT + 32768;
    if (SB & 1023) __trap();
    const int tid = threadIdx.x, w = tid >> 5, lane = tid & 31;
    const int rank = blockIdx.x & 1, mt = blockIdx.x >> 3, nt = (blockIdx.x >> 1) & 3;
    const uint32_t full = BAR, empty = BAR + 64, afull = BAR + 128;
    if (tid == 0) {
        for (int i = 0; i < STAGES; i++) { mbar_init(full + i * 8, 1); mbar_init(empty + i * 8, 8); }
        mbar_init(afull, 2);
        asm volatile("fence.mbarrier_init.release.cluster;" ::: "memory");
    }
    __syncthreads();
    asm volatile("griddepcontrol.wait;" ::: "memory");
    if (blockIdx.x == 0 && tid < 160) g_cls[tid] = 0;
    TL(4);
    if (w == 8) {
        if (lane == 0) {
            int st = 0, ph = 1;
            for (int kb = 0; kb < 32; kb++) {
                if (kb >= STAGES) mbar_wait(empty + st * 8, ph);
                mbar_expect(full + st * 8, STG);
                tma3d(SB + st * STG, &tmO, 0, (rank * 32 + kb) * 2, mt * 16, full + st * 8);
                tma3d(SB + st * STG + 16384, &tmWo, 0, (rank * 32 + kb) * 64, nt * 4, full + st * 8);
                if (kb == STAGES - 1) { mbar_expect(afull, 32768); tma3d(AT, &tmA, 0, (nt * 2 + rank) * 128, mt * 2, afull); }
                if (++st == STAGES) { st = 0; ph ^= 1; }
            }
            mbar_wait(empty, ph);
            mbar_expect(afull, 32768);
            for (int hf = 0; hf < 2; hf++)
                asm volatile("cp.async.bulk.tensor.5d.shared::cluster.global.mbarrier::complete_tx::bytes [%0], [%1, {%3, %4, %4, %4, %5}], [%2];"
                    :: "r"(SB + hf * 16384), "l"(&tmQ), "r"(afull), "r"(nt * 256 + rank * 128 + hf * 64), "r"(0), "r"(mt * 4) : "memory");
        }
        __syncwarp();
        asm volatile("barrier.cluster.arrive.aligned; barrier.cluster.wait.aligned;" ::: "memory");
        asm volatile("barrier.cluster.arrive.aligned; barrier.cluster.wait.aligned;" ::: "memory");
    } else {
        const int wg = w >> 2, g = lane >> 2;
        float acc[128];
        const int tok0 = 32 * (4 * mt + (w >> 1)) + 8 * (g >> 1) + 4 * (w & 1) + (g & 1);
        const float g0 = g_gate[tok0], g1 = g_gate[tok0 + 2];
        int st = 0, ph = 0, pst = 0;
        #pragma unroll 1
        for (int kb = 0; kb < 32; kb++) {
            mbar_wait(full + st * 8, ph);
            const uint64_t da = mkdesc(SB + st * STG + wg * 8192, 128, 1024, 0), db = mkdesc(SB + st * STG + 16384, 8192, 1024, 1);
            wg_fence();
            #pragma unroll
            for (int ks = 0; ks < 4; ks++) wgmma_n256_ss_tt(acc, da + ks * 16, db + ks * 128, (kb | ks) != 0);
            wg_commit();
            wg_wait<1>();
            if (kb > 0 && lane == 0) mbar_arrive(empty + pst * 8);
            pst = st;
            if (++st == STAGES) { st = 0; ph ^= 1; }
        }
        wg_wait<0>();
        TLX(12);
        asm volatile("barrier.cluster.arrive.aligned; barrier.cluster.wait.aligned;" ::: "memory");
        uint32_t peer;
        asm volatile("mapa.shared::cluster.u32 %0, %1, %2;" : "=r"(peer) : "r"(SB + 65536 + tid * 16), "r"(rank ^ 1));
        #define SND(e) pack2(rank ? acc[8 * i + (e)] : acc[64 + 8 * i + (e)], rank ? acc[8 * i + (e) + 1] : acc[65 + 8 * i + (e)])
        #pragma unroll
        for (int i = 0; i < 8; i++)
            asm volatile("st.shared::cluster.v4.b32 [%0], {%1,%2,%3,%4};" :: "r"(peer + i * 4096), "r"(SND(0)), "r"(SND(2)), "r"(SND(4)), "r"(SND(6)) : "memory");
        #undef SND
        asm volatile("barrier.cluster.arrive.aligned; barrier.cluster.wait.aligned;" ::: "memory");
        mbar_wait(afull, 0);
        const float h0 = 1.f - g0, h1 = 1.f - g1;
        const uint32_t la = AT + wg * 16384 + ((lane >> 4) * 8 + (lane & 7)) * 128 + ((((w & 3) * 2 + ((lane >> 3) & 1)) ^ (lane & 7)) << 4);
        const uint32_t ra = SB + (w * 16 + (lane & 15)) * 128;
        #pragma unroll
        for (int i = 0; i < 8; i++) {
            const uint32_t a = ra + (i >> 2) * 16384 + ((((i & 3) * 2 + (lane >> 4)) ^ (lane & 7)) << 4);
            uint32_t r0, r1, r2, r3, x0, x1, x2, x3;
            ldsm4t(r0, r1, r2, r3, la + i * 2048);
            ldsm4(x0, x1, x2, x3, a);
            const uint4 u = lds128(SB + 65536 + tid * 16 + i * 4096);
            float p[8];
            #pragma unroll
            for (int e = 0; e < 8; e++) { const uint32_t x = ((const uint32_t*)&u)[e >> 1]; p[e] = (rank ? acc[64 + 8 * i + e] : acc[8 * i + e]) + ((e & 1) ? bfhi(x) : bflo(x)); }
            #define MIX(g, h, r, x, e) pack2(fmaf(g * bflo(x), bflo(r), h * p[e]), fmaf(g * bfhi(x), bfhi(r), h * p[e + 1]))
            stsm4(a, MIX(g0, h0, r0, x0, 0), MIX(g1, h1, r1, x1, 2), MIX(g0, h0, r2, x2, 4), MIX(g1, h1, r3, x3, 6));
        }
        asm volatile("fence.proxy.async.shared::cta;" ::: "memory");
        bsync<1, 256>();
        if (tid == 0) {
            for (int hf = 0; hf < 2; hf++)
                asm volatile("cp.async.bulk.tensor.5d.global.shared::cta.bulk_group [%0, {%2, %3, %3, %3, %4}], [%1];"
                    :: "l"(&tmOut), "r"(SB + hf * 16384), "r"(nt * 256 + rank * 128 + hf * 64), "r"(0), "r"(mt * 4) : "memory");
            asm volatile("cp.async.bulk.commit_group;" ::: "memory");
            asm volatile("cp.async.bulk.wait_group 0;" ::: "memory");
        }
        TL(5);
    }
}

typedef CUresult (*EncodeFn)(CUtensorMap*, CUtensorMapDataType, cuuint32_t, void*, const cuuint64_t*, const cuuint64_t*, const cuuint32_t*,
                             const cuuint32_t*, CUtensorMapInterleave, CUtensorMapSwizzle, CUtensorMapL2promotion, CUtensorMapFloatOOBfill);
static void enc(EncodeFn fn, CUtensorMap* m, void* base, int rank, const cuuint64_t* dims, const cuuint64_t* strides, const cuuint32_t* box, CUtensorMapSwizzle sw) {
    cuuint32_t es[5] = {1, 1, 1, 1, 1};
    fn(m, CU_TENSOR_MAP_DATA_TYPE_BFLOAT16, rank, base, dims, strides, box, es, CU_TENSOR_MAP_INTERLEAVE_NONE, sw,
       CU_TENSOR_MAP_L2_PROMOTION_L2_128B, CU_TENSOR_MAP_FLOAT_OOB_FILL_NONE);
}
static MainParams h_prm = {{768, 576, 512, 0, 0, 0, 0, 0, 0, 0, 0, 0}, 0, 1, nullptr, nullptr};

extern "C" void kernel_launch(void* const* d_in, const int* in_sizes, int n_in, void* d_out, int out_size) {
    const bf16* q = (const bf16*)d_in[0];
    const bf16* shift_k = (const bf16*)d_in[3];
    const bf16* ssm_k = (const bf16*)d_in[4];
    const bf16* ssm_D = (const bf16*)d_in[5];
    const bf16* mem0 = (const bf16*)d_in[7];
    const bf16* gate_w = (const bf16*)d_in[13];

    static EncodeFn fn = nullptr;
    static void* pO = nullptr;
    static void* pA = nullptr;
    if (!fn) {
        cudaDriverEntryPointQueryResult qr;
        cudaGetDriverEntryPoint("cuTensorMapEncodeTiled", (void**)&fn, cudaEnableDefault, &qr);
        cudaGetSymbolAddress(&pO, g_O);
        cudaGetSymbolAddress(&pA, g_Y);
        void* pRB; cudaGetSymbolAddress(&pRB, g_RB);
        h_prm.rb = (char*)(((uintptr_t)pRB + (4u << 20) - 1) & ~(uintptr_t)((4u << 20) - 1));
        int dev, sms; cudaGetDevice(&dev); cudaDeviceGetAttribute(&sms, cudaDevAttrMultiProcessorCount, dev);
        h_prm.by_sm = sms == NCTA;
        cudaFuncSetAttribute(main_kernel, cudaFuncAttributeMaxDynamicSharedMemorySize, mk::TOTAL);
        cudaFuncSetAttribute(out_kernel, cudaFuncAttributeMaxDynamicSharedMemorySize, ok::TOTAL);
    }
    CUtensorMap mWq, mWk, mWv, mWo, mX, mO, mWo2, mA, mOut, mQ;
    {
        cuuint64_t d[2] = {4096, 1024}, s[1] = {8192}; cuuint32_t b[2] = {64, 256};
        enc(fn, &mWq, d_in[8], 2, d, s, b, CU_TENSOR_MAP_SWIZZLE_128B);
        enc(fn, &mWk, d_in[9], 2, d, s, b, CU_TENSOR_MAP_SWIZZLE_128B);
        enc(fn, &mWv, d_in[10], 2, d, s, b, CU_TENSOR_MAP_SWIZZLE_128B);
    }
    {
        cuuint64_t d[2] = {1024, 4096}, s[1] = {2048}; cuuint32_t b[2] = {64, 128};
        enc(fn, &mWo, d_in[11], 2, d, s, b, CU_TENSOR_MAP_SWIZZLE_128B);
        cuuint64_t d2[3] = {64, 4096, 16}, s2[2] = {2048, 128}; cuuint32_t b2[3] = {64, 64, 4};
        enc(fn, &mWo2, d_in[11], 3, d2, s2, b2, CU_TENSOR_MAP_SWIZZLE_128B);
    }
    {
        cuuint64_t d[3] = {64, 2048, 16}, s[2] = {2048, 128}; cuuint32_t b[3] = {64, 32, 8};
        enc(fn, &mX, d_in[0], 3, d, s, b, CU_TENSOR_MAP_SWIZZLE_128B);
    }
    {
        cuuint64_t d[3] = {256, 128, 256}, s[2] = {512, 65536}; cuuint32_t b[3] = {256, 2, 16};
        enc(fn, &mO, pO, 3, d, s, b, CU_TENSOR_MAP_SWIZZLE_NONE);
    }
    {
        cuuint64_t d[5] = {1024, 2, 4, 4, 64}, s[4] = {2048, 16384, 4096, 65536}; cuuint32_t b[5] = {64, 2, 4, 4, 4};
        cuuint64_t da[3] = {64, 1024, 32}, sa[2] = {4096, 128}; cuuint32_t ba[3] = {64, 128, 2};
        enc(fn, &mA, pA, 3, da, sa, ba, CU_TENSOR_MAP_SWIZZLE_128B);
        enc(fn, &mQ, d_in[0], 5, d, s, b, CU_TENSOR_MAP_SWIZZLE_128B);
        enc(fn, &mOut, d_out, 5, d, s, b, CU_TENSOR_MAP_SWIZZLE_128B);
    }
    KVMaps mK;
    {
        cuuint64_t d[3] = {1024, 256, 8}, s[2] = {16384, 2048}; cuuint32_t b[3] = {8, 256, 1};
        for (int i = 0; i < 2; i++) enc(fn, &mK.m[i], d_in[1 + i], 3, d, s, b, CU_TENSOR_MAP_SWIZZLE_NONE);
    }
    cudaStream_t st = cudaStreamPerThread;
    cudaLaunchAttribute at[1];
    at[0].id = cudaLaunchAttributeProgrammaticStreamSerialization;
    at[0].val.programmaticStreamSerializationAllowed = 1;
    cudaLaunchConfig_t cfg = {};
    cfg.stream = st; cfg.attrs = at;
    cfg.gridDim = dim3(NCTA); cfg.blockDim = dim3(256); cfg.dynamicSmemBytes = mk::TOTAL;
    h_prm.x = (const char*)q;
    const ConvIn cin = {q, shift_k, ssm_k, ssm_D, gate_w};
    cudaLaunchKernelEx(&cfg, main_kernel, mWq, mWk, mWv, mWo, mX, mK, mem0, cin, h_prm);
    cfg.numAttrs = PDL;
    cfg.gridDim = dim3(128); cfg.blockDim = dim3(288); cfg.dynamicSmemBytes = ok::TOTAL;
    cudaLaunchKernelEx(&cfg, out_kernel, mO, mWo2, mA, mOut, mQ);
}
```

```cpp
#include <cuda_runtime.h>
#include <cuda_bf16.h>
#include <cuda.h>
#include <stdint.h>

typedef __nv_bfloat16 bf16;

constexpr int SEQ = 2048, DM = 1024, NH = 32, DH = 128, NSEG = 64;
constexpr int SPIN_LIMIT = 1 << 13, NCTA = 132;
#define NPR 2
#define RF 0
#define CC 0
#define XDL 10
#define NSP 128
#define XPF 2
#define FRONT __forceinline__
#define PDL 1
#define TPF 1

constexpr uint32_t HOME_BITS = 0xB3000;
constexpr uint32_t RB_R = 0;
constexpr uint32_t RB_B = 0x80000;
constexpr uint32_t RB_T = RB_B + 0x4000;
constexpr uint32_t RB_P = RB_B + 0x20000;
constexpr uint32_t RB_X = 2u << 20;
__device__ uint4 g_RB[(8 << 20) / 16];
__device__ uint32_t g_cls[160];
__device__ uint4 g_T[2 * NH * 3072];
__device__ uint4 g_O[NSEG * 4 * 4096];
__device__ uint4 g_Y[SEQ * DM / 8];
__device__ float g_gate[SEQ];
__device__ uint32_t g_err;
#define TL(i) do {} while (0)
#define TLX(i)

__device__ __forceinline__ uint32_t smem_u32(const void* p) { return (uint32_t)__cvta_generic_to_shared(p); }
__device__ __forceinline__ uint32_t clk() { uint32_t c; asm volatile("mov.u32 %0, %%clock;" : "=r"(c) :: "memory"); return c; }
__device__ __forceinline__ void ldsm4(uint32_t& r0, uint32_t& r1, uint32_t& r2, uint32_t& r3, uint32_t a) {
    asm volatile("ldmatrix.sync.aligned.m8n8.x4.shared.b16 {%0,%1,%2,%3}, [%4];" : "=r"(r0), "=r"(r1), "=r"(r2), "=r"(r3) : "r"(a) : "memory");
}
__device__ __forceinline__ void ldsm4t(uint32_t& r0, uint32_t& r1, uint32_t& r2, uint32_t& r3, uint32_t a) {
    asm volatile("ldmatrix.sync.aligned.m8n8.x4.trans.shared.b16 {%0,%1,%2,%3}, [%4];" : "=r"(r0), "=r"(r1), "=r"(r2), "=r"(r3) : "r"(a) : "memory");
}
__device__ __forceinline__ void ldsm2(uint32_t& r0, uint32_t& r1, uint32_t a) {
    asm volatile("ldmatrix.sync.aligned.m8n8.x2.shared.b16 {%0,%1}, [%2];" : "=r"(r0), "=r"(r1) : "r"(a) : "memory");
}
__device__ __forceinline__ void stsm4t(uint32_t a, uint32_t r0, uint32_t r1, uint32_t r2, uint32_t r3) {
    asm volatile("stmatrix.sync.aligned.m8n8.x4.trans.shared.b16 [%0], {%1,%2,%3,%4};" :: "r"(a), "r"(r0), "r"(r1), "r"(r2), "r"(r3) : "memory");
}
__device__ __forceinline__ void mma16(float* c, uint32_t a0, uint32_t a1, uint32_t a2, uint32_t a3, uint32_t b0, uint32_t b1) {
    asm volatile("mma.sync.aligned.m16n8k16.row.col.f32.bf16.bf16.f32 {%0,%1,%2,%3}, {%4,%5,%6,%7}, {%8,%9}, {%0,%1,%2,%3};"
        : "+f"(c[0]), "+f"(c[1]), "+f"(c[2]), "+f"(c[3]) : "r"(a0), "r"(a1), "r"(a2), "r"(a3), "r"(b0), "r"(b1));
}
__device__ __forceinline__ void mma8(float* c, uint32_t a0, uint32_t a1, uint32_t b0) {
    asm volatile("mma.sync.aligned.m16n8k8.row.col.f32.bf16.bf16.f32 {%0,%1,%2,%3}, {%4,%5}, {%6}, {%0,%1,%2,%3};"
        : "+f"(c[0]), "+f"(c[1]), "+f"(c[2]), "+f"(c[3]) : "r"(a0), "r"(a1), "r"(b0));
}
__device__ __forceinline__ uint32_t pack2(float lo, float hi) {
    uint32_t r; asm("cvt.rn.bf16x2.f32 %0, %1, %2;" : "=r"(r) : "f"(hi), "f"(lo)); return r;
}
__device__ __forceinline__ uint32_t hadd2(uint32_t a, uint32_t b) {
    uint32_t r; asm("add.rn.bf16x2 %0, %1, %2;" : "=r"(r) : "r"(a), "r"(b)); return r;
}
__device__ __forceinline__ float bflo(uint32_t w) { return __uint_as_float(w << 16); }
__device__ __forceinline__ float bfhi(uint32_t w) { return __uint_as_float(w & 0xFFFF0000u); }
__device__ __forceinline__ void st_g32(void* p, uint32_t v) { asm volatile("st.relaxed.gpu.global.u32 [%0], %1;" :: "l"(p), "r"(v) : "memory"); }
__device__ __forceinline__ void st_g128(void* p, uint32_t a, uint32_t b, uint32_t c, uint32_t d) {
    asm volatile("st.relaxed.gpu.global.v4.u32 [%0], {%1,%2,%3,%4};" :: "l"(p), "r"(a), "r"(b), "r"(c), "r"(d) : "memory");
}
__device__ __forceinline__ uint4 lds128(uint32_t a) { uint4 v; asm volatile("ld.shared.v4.u32 {%0,%1,%2,%3}, [%4];" : "=r"(v.x), "=r"(v.y), "=r"(v.z), "=r"(v.w) : "r"(a) : "memory"); return v; }
__device__ __forceinline__ void sts128(uint32_t a, uint4 v) { asm volatile("st.shared.v4.u32 [%0], {%1,%2,%3,%4};" :: "r"(a), "r"(v.x), "r"(v.y), "r"(v.z), "r"(v.w) : "memory"); }
__device__ __forceinline__ float2 lds64f(uint32_t a) { float2 v; asm volatile("ld.shared.v2.f32 {%0,%1}, [%2];" : "=f"(v.x), "=f"(v.y) : "r"(a) : "memory"); return v; }
__device__ __forceinline__ void sts64f(uint32_t a, float x, float y) { asm volatile("st.shared.v2.f32 [%0], {%1,%2};" :: "r"(a), "f"(x), "f"(y) : "memory"); }
__device__ __forceinline__ void sts32f(uint32_t a, float x) { asm volatile("st.shared.f32 [%0], %1;" :: "r"(a), "f"(x) : "memory"); }
__device__ __forceinline__ void sts32(uint32_t a, uint32_t x) { asm volatile("st.shared.u32 [%0], %1;" :: "r"(a), "r"(x) : "memory"); }
__device__ __forceinline__ uint32_t lds32(uint32_t a) { uint32_t v; asm volatile("ld.shared.u32 %0, [%1];" : "=r"(v) : "r"(a) : "memory"); return v; }
__device__ __forceinline__ void cpa16(uint32_t dst, const void* src) { asm volatile("cp.async.cg.shared.global [%0], [%1], 16;" :: "r"(dst), "l"(src) : "memory"); }
__device__ __forceinline__ void cpa_commit() { asm volatile("cp.async.commit_group;" ::: "memory"); }
__device__ __forceinline__ void cpa_wait() { asm volatile("cp.async.wait_all;" ::: "memory"); }
template <int ID, int N> __device__ __forceinline__ void bsync() { asm volatile("bar.sync %0, %1;" :: "n"(ID), "n"(N) : "memory"); }
template <int ID, int N> __device__ __forceinline__ void barrive() { asm volatile("bar.arrive %0, %1;" :: "n"(ID), "n"(N) : "memory"); }
template <int ID, int N> __device__ __forceinline__ void bsync_if(bool on) { asm volatile("{ .reg .pred p; setp.ne.b32 p, %2, 0; @p bar.sync %0, %1; }" :: "n"(ID), "n"(N), "r"((int)on) : "memory"); }
template <int ID, int N> __device__ __forceinline__ void barrive_if(bool on) { asm volatile("{ .reg .pred p; setp.ne.b32 p, %2, 0; @p bar.arrive %0, %1; }" :: "n"(ID), "n"(N), "r"((int)on) : "memory"); }
template <int ID> __device__ __forceinline__ uint32_t any128(uint32_t x) {
    uint32_t r; asm volatile("{ .reg .pred p; setp.ne.b32 p, %1, 0; bar.red.or.pred p, %2, 128, p; selp.u32 %0, 1, 0, p; }" : "=r"(r) : "r"(x), "n"(ID) : "memory"); return r;
}
__device__ __forceinline__ bool elect() {
    uint32_t p; asm volatile("{ .reg .pred p; elect.sync _|p, 0xFFFFFFFF; selp.u32 %0, 1, 0, p; }" : "=r"(p)); return p;
}
__device__ __forceinline__ void mbar_init(uint32_t mb, uint32_t n) { asm volatile("mbarrier.init.shared::cta.b64 [%0], %1;" :: "r"(mb), "r"(n) : "memory"); }
__device__ __forceinline__ void mbar_expect(uint32_t mb, uint32_t bytes) { asm volatile("mbarrier.arrive.expect_tx.shared::cta.b64 _, [%0], %1;" :: "r"(mb), "r"(bytes) : "memory"); }
__device__ __forceinline__ void mbar_arrive(uint32_t mb) { asm volatile("mbarrier.arrive.shared::cta.b64 _, [%0];" :: "r"(mb) : "memory"); }
__device__ __forceinline__ void mbar_wait(uint32_t mb, uint32_t ph) {
    asm volatile("{ .reg .pred p; .reg .u32 n; mov.u32 n, 0;\n"
                 "MW_%=: mbarrier.try_wait.parity.shared::cta.b64 p, [%0], %1; add.u32 n, n, 1; setp.lt.and.u32 p, n, %2, !p; @p bra.uni MW_%=; }"
                 :: "r"(mb), "r"(ph), "n"(SPIN_LIMIT) : "memory");
}
__device__ __forceinline__ void tma2d(uint32_t dst, const CUtensorMap* m, int c0, int c1, uint32_t mb) {
    asm volatile("cp.async.bulk.tensor.2d.shared::cluster.global.mbarrier::complete_tx::bytes [%0], [%1, {%3, %4}], [%2];"
        :: "r"(dst), "l"(m), "r"(mb), "r"(c0), "r"(c1) : "memory");
}
__device__ __forceinline__ void tma3d(uint32_t dst, const CUtensorMap* m, int c0, int c1, int c2, uint32_t mb) {
    asm volatile("cp.async.bulk.tensor.3d.shared::cluster.global.mbarrier::complete_tx::bytes [%0], [%1, {%3, %4, %5}], [%2];"
        :: "r"(dst), "l"(m), "r"(mb), "r"(c0), "r"(c1), "r"(c2) : "memory");
}
__device__ __forceinline__ void bulk_ld(uint32_t dst, const void* src, uint32_t bytes, uint32_t mb) {
    asm volatile("cp.async.bulk.shared::cluster.global.mbarrier::complete_tx::bytes [%0], [%1], %2, [%3];" :: "r"(dst), "l"(src), "r"(bytes), "r"(mb) : "memory");
}
__device__ __forceinline__ uint64_t mkdesc(uint32_t addr, uint32_t lbo, uint32_t sbo, uint32_t swz) {
    return (uint64_t)((addr & 0x3FFFF) >> 4) | ((uint64_t)(lbo >> 4) << 16) | ((uint64_t)(sbo >> 4) << 32) | ((uint64_t)swz << 62);
}
__device__ __forceinline__ void wg_fence() { asm volatile("wgmma.fence.sync.aligned;" ::: "memory"); }
__device__ __forceinline__ void wg_commit() { asm volatile("wgmma.commit_group.sync.aligned;" ::: "memory"); }
template <int N> __device__ __forceinline__ void wg_wait() { asm volatile("wgmma.wait_group.sync.aligned %0;" :: "n"(N) : "memory"); }
#define F4(d, o) "+f"(d[o]), "+f"(d[o + 1]), "+f"(d[o + 2]), "+f"(d[o + 3])
__device__ __forceinline__ void wgmma_n32_rs(float* d, const uint32_t* a, uint64_t db, int accum) {
    asm volatile("{.reg .pred p; setp.ne.b32 p, %21, 0;\n"
        "wgmma.mma_async.sync.aligned.m64n32k16.f32.bf16.bf16 {%0,%1,%2,%3,%4,%5,%6,%7,%8,%9,%10,%11,%12,%13,%14,%15}, {%16,%17,%18,%19}, %20, p, 1, 1, 0;}"
        : F4(d, 0), F4(d, 4), F4(d, 8), F4(d, 12) : "r"(a[0]), "r"(a[1]), "r"(a[2]), "r"(a[3]), "l"(db), "r"(accum));
}
__device__ __forceinline__ void wait_until(uint32_t tgt, uint32_t any) {
    asm volatile("{ .reg .pred p, q; .reg .u32 t; .reg .s32 d; mov.u32 t, %0; setp.ne.u32 q, %1, 0xFFFFFFFF;\n"
                 "WU_%=: @q mov.u32 t, %%clock; sub.s32 d, t, %0; setp.lt.s32 p, d, 0; @p bra.uni WU_%=; }" :: "r"(tgt), "r"(any) : "memory");
}

namespace mk {
constexpr uint32_t SB = 1024;
constexpr uint32_t WV = SB, WO = SB + 65536, XT = SB + 131072, TK = SB + 163840  , TQ = TK + 32768, MEM = TQ + 4096,
                   SC = MEM + 8192  , PT = SC + 6144,
                   OB = SC + 8192, SUM = OB + 2048, BAR = SUM + 512, GRP = BAR + 128, PROFB = BAR + 192,
                   TOTAL = PROFB - SB;
static_assert(TOTAL <= 232448, "shared memory");
constexpr uint32_t MB_WQ = BAR, MB_WK = BAR + 8, MB_WV = BAR + 16, MB_WO = BAR + 24, MB_X = BAR + 32, MB_KV = BAR + 40, MB_R = BAR + 48, MB_B = BAR + 56, MB_C = BAR + 64;
constexpr uint32_t XT2 = WV, RS = WV + 32768, VE = RS + 4096;
enum { B_START = 1, B_H0, B_H2, B_H3, B_S1, B_SC, B_SC2, B_S0, B_O, B_O2, B_PT, B_GO, B_VX, B_RD, B_BT };
constexpr uint64_t XD0 = (uint64_t)(XT >> 4) | ((uint64_t)1 << 16) | ((uint64_t)64 << 32) | ((uint64_t)1 << 62);
constexpr uint32_t TSLOT = NH * 49152;
}
struct MainParams { int d[12]; uint32_t zero; int by_sm; char* rb; const char* x; };
#define XD(i) (mk::XD0 - (((i) >> 5) & 1) * ((mk::XT - mk::XT2) >> 4) + ((i) >> 6) * ((mk::TK - mk::XT) >> 4) + (((i) & 31) >> 2) * 256 + ((i) & 3) * 2)
#define XD4(i) XD(i), XD(i + 1), XD(i + 2), XD(i + 3)
#define XD16(i) XD4(i), XD4(i + 4), XD4(i + 8), XD4(i + 12)
__constant__ __align__(256) uint64_t c_xd[96] = {XD16(0), XD16(16), XD16(32), XD16(48), XD16(64), XD16(80)};
#define CUT(r) asm volatile("{ .reg .pred q; setp.eq.u32 q, %1, 0xFFFFFFFF; @q mov.u32 %0, %%clock; }" : "+r"(r) : "r"(t16) : "memory")
__device__ __forceinline__ uint32_t opq(uint32_t x) { asm volatile("" : "+r"(x)); return x; }
__device__ __forceinline__ float opqf(float x) { asm volatile("" : "+f"(x)); return x; }
#define PROF(i)
#define PROFW(i, w)
#define TRC(i, v)
#define RETRY(i, on)
#define P(i) prm.d[i]
#define DELAY(n) do { if (n) { _Pragma("unroll") for (int i_ = 0; i_ < n; i_++) asm volatile("mad.lo.u32 %0, %0, %1, %0;" : "+r"(pb) : "r"(prm.zero)); CUT(pa); } } while (0)

__device__ __forceinline__ uint32_t tagw(uint32_t w, uint32_t tau) { return (w & ~1u) | tau; }
__device__ __forceinline__ uint32_t ld_g32(const void* p) { uint32_t v; asm volatile("ld.relaxed.gpu.global.u32 %0, [%1];" : "=r"(v) : "l"(p) : "memory"); return v; }
__device__ __forceinline__ void ld_g64(uint32_t* v, const void* p) { asm volatile("ld.relaxed.gpu.global.v2.u32 {%0,%1}, [%2];" : "=r"(v[0]), "=r"(v[1]) : "l"(p) : "memory"); }
__device__ __forceinline__ void ld_g128(uint32_t* v, const void* p) {
    asm volatile("ld.relaxed.gpu.global.v4.u32 {%0,%1,%2,%3}, [%4];" : "=r"(v[0]), "=r"(v[1]), "=r"(v[2]), "=r"(v[3]) : "l"(p) : "memory");
}
__device__ __forceinline__ void st_g64(void* p, uint32_t a, uint32_t b) { asm volatile("st.relaxed.gpu.global.v2.u32 [%0], {%1,%2};" :: "l"(p), "r"(a), "r"(b) : "memory"); }
__device__ __forceinline__ void lds128f(float* v, uint32_t a) { asm volatile("ld.shared.v4.f32 {%0,%1,%2,%3}, [%4];" : "=f"(v[0]), "=f"(v[1]), "=f"(v[2]), "=f"(v[3]) : "r"(a) : "memory"); }
__device__ __forceinline__ void sts128f(uint32_t a, float x, float y, float z, float w) { asm volatile("st.shared.v4.f32 [%0], {%1,%2,%3,%4};" :: "r"(a), "f"(x), "f"(y), "f"(z), "f"(w) : "memory"); }
__device__ __forceinline__ void stsm4(uint32_t a, uint32_t r0, uint32_t r1, uint32_t r2, uint32_t r3) {
    asm volatile("stmatrix.sync.aligned.m8n8.x4.shared.b16 [%0], {%1,%2,%3,%4};" :: "r"(a), "r"(r0), "r"(r1), "r"(r2), "r"(r3) : "memory");
}
__device__ __forceinline__ void mmaq(float* c, const uint32_t* a, uint32_t b0, uint32_t b1) { mma16(c, a[0], a[1], a[2], a[3], b0, b1); }
template <int LUT> __device__ __forceinline__ uint32_t lop3(uint32_t a, uint32_t b, uint32_t c) { uint32_t r; asm("lop3.b32 %0, %1, %2, %3, %4;" : "=r"(r) : "r"(a), "r"(b), "r"(c), "n"(LUT)); return r; }
template <int N, int S> __device__ __forceinline__ uint32_t stale(const uint32_t* x, uint32_t tau) {
    if constexpr (N == 2) return lop3<0x7E>(x[0], tau, x[S]);
    else if constexpr (N == 3) return lop3<0xF6>(stale<2, S>(x, tau), x[2 * S], tau);
    else if constexpr (N == 4 || N == 16) return lop3<0xFC>(stale<N / 2, S>(x, tau), stale<N / 2, S>(x + N / 2 * S, tau), 0);
    else return lop3<0xFE>(stale<3, S>(x, tau), stale<3, S>(x + 3 * S, tau), stale<2, S>(x + 6 * S, tau));
}
__device__ __forceinline__ uint32_t late(uint32_t a, uint32_t b, uint32_t mask) {
    uint32_t r;
    asm volatile("{ .reg .pred p; .reg .b32 t; lop3.b32 t, %1, %2, %3, 0xA8; setp.ne.b32 p, t, 0; vote.sync.any.pred p, p, 0xFFFFFFFF; selp.u32 %0, 1, 0, p; }" : "=r"(r) : "r"(a), "r"(b), "r"(mask));
    return r;
}
#define AGAIN(id, reload, ...) _Pragma("unroll 1") for (int n_ = 0; __builtin_expect(__VA_ARGS__, 0) && n_ < SPIN_LIMIT; n_++) { RETRY(id, 1); reload; }
__device__ __forceinline__ uint32_t tile_off(int lane, int chunk0) {
    return ((lane >> 4) * 8 + (lane & 7)) * 128 + (((chunk0 + ((lane >> 3) & 1)) ^ (lane & 7)) << 4);
}
template <int K0, int K1>
__device__ __forceinline__ void load_tile(uint32_t a, uint32_t* T) {
    #pragma unroll
    for (int ks = K0; ks < K1; ks++) ldsm4t(T[4 * ks], T[4 * ks + 1], T[4 * ks + 2], T[4 * ks + 3], a + ks * 2048);
}
__device__ __forceinline__ void lds128u(uint32_t* v, uint32_t a) { asm volatile("ld.shared.v4.u32 {%0,%1,%2,%3}, [%4];" : "=r"(v[0]), "=r"(v[1]), "=r"(v[2]), "=r"(v[3]) : "r"(a) : "memory"); }
template <int K0, int K1, int STRIDE = 4096>
__device__ __forceinline__ void load_frag(uint32_t a, uint32_t* T) {
    #pragma unroll
    for (int ks = K0; ks < K1; ks++) lds128u(&T[4 * ks], a + ks * STRIDE);
}
template <int L0, int L1, bool INIT = false>
__device__ __forceinline__ void wg_run(float* acc, const uint32_t* A, const uint64_t* d) {
    if (L1 > L0) {
        wg_fence();
        #pragma unroll
        for (int l = L0; l < L1; l++) wgmma_n32_rs(acc, &A[4 * l], d[l], INIT || l != 0);
        wg_commit();
    }
}
__device__ __forceinline__ void load_x(const CUtensorMap* tmX, int c, int seg, uint32_t dst) {
    asm volatile("{ .reg .pred p; elect.sync _|p, 0xFFFFFFFF;\n"
        "@p cp.async.bulk.tensor.3d.shared::cluster.global.mbarrier::complete_tx::bytes [%4], [%0, {%5, %1, %2}], [%3]; }"
        :: "l"(tmX), "r"(seg * 32), "r"((c & 1) * 8), "r"(mk::MB_X), "r"(dst), "r"(0) : "memory");
    __syncwarp();
}
__device__ __forceinline__ void bulk_expect(uint32_t mb, uint32_t bytes) {
    asm volatile("{ .reg .pred p; elect.sync _|p, 0xFFFFFFFF; @p mbarrier.arrive.expect_tx.shared::cta.b64 _, [%0], %1; }" :: "r"(mb), "r"(bytes) : "memory");
}
__device__ __forceinline__ void bulk_copy(uint32_t dst, const void* src, uint32_t bytes, uint32_t mb) {
    asm volatile("{ .reg .pred p; elect.sync _|p, 0xFFFFFFFF; @p cp.async.bulk.shared::cluster.global.mbarrier::complete_tx::bytes [%0], [%1], %2, [%3]; }"
        :: "r"(dst), "l"(src), "r"(bytes), "r"(mb) : "memory");
    __syncwarp();
}
__device__ __forceinline__ void bulk_copy_if(bool on, uint32_t dst, const void* src, uint32_t bytes, uint32_t mb) {
    asm volatile("{ .reg .pred p; elect.sync _|p, 0xFFFFFFFF; setp.ne.and.b32 p, %4, 0, p; @p cp.async.bulk.shared::cluster.global.mbarrier::complete_tx::bytes [%0], [%1], %2, [%3]; }"
        :: "r"(dst), "l"(src), "r"(bytes), "r"(mb), "r"((int)on) : "memory");
    __syncwarp();
}
__device__ __forceinline__ void kv_expect(uint32_t bytes) { bulk_expect(mk::MB_KV, bytes); }
__device__ __forceinline__ void kv_copy(uint32_t dst, const void* src, uint32_t bytes) { bulk_copy(dst, src, bytes, mk::MB_KV); }
__device__ __forceinline__ uint32_t gtime() { uint32_t c; asm volatile("mov.u32 %0, %%globaltimer_lo;" : "=r"(c) :: "memory"); return c; }
__device__ __forceinline__ void wait_g(uint32_t tgt, uint32_t any) {
    asm volatile("{ .reg .pred p, q; .reg .u32 t; mov.u32 t, %0; setp.ne.u32 q, %1, 0xFFFFFFFF;\n"
                 "WG_%=: @q mov.u32 t, %%globaltimer_lo; sub.u32 t, t, %0; setp.gt.u32 p, t, 0xFFFF0000; @p bra.uni WG_%=; }" :: "r"(tgt), "r"(any) : "memory");
    __syncwarp();
}
__device__ __forceinline__ uint32_t clkv(uint32_t any) {
    uint32_t c; asm volatile("{ .reg .pred q; setp.ne.u32 q, %1, 0xFFFFFFFF; mov.u32 %0, 0; @q mov.u32 %0, %%clock; }" : "=r"(c) : "r"(any) : "memory"); return c;
}
__device__ __forceinline__ char* kv_src(int c, int seg) { return (char*)g_T + ((seg & 1) * mk::TSLOT + (c >> 2) * 49152); }
__device__ __forceinline__ void prefetch_l2(const void* p, uint32_t bytes) {
    asm volatile("{ .reg .pred p; elect.sync _|p, 0xFFFFFFFF; @p cp.async.bulk.prefetch.L2.global [%0], %1; }" :: "l"(p), "r"(bytes) : "memory");
}
__device__ __forceinline__ uint32_t phase(int i) { return (~i >> 1) & 1; }
__device__ __forceinline__ void qk_pack(const float* acc, uint32_t* p) {
    #pragma unroll
    for (int i = 0; i < 4; i++) { p[i] = pack2(acc[4 * i], acc[4 * i + 1]); p[4 + i] = pack2(acc[4 * i + 2], acc[4 * i + 3]); }
}
__device__ __forceinline__ void sts128_if(bool on, uint32_t a, const uint32_t* p) {
    asm volatile("{ .reg .pred p; setp.ne.b32 p, %5, 0; @p st.shared.v4.u32 [%0], {%1,%2,%3,%4}; }" :: "r"(a), "r"(p[0]), "r"(p[1]), "r"(p[2]), "r"(p[3]), "r"((int)on) : "memory");
}
__device__ __forceinline__ void st_if(bool on, char* a, const uint32_t* p) {
    asm volatile("{ .reg .pred p; setp.ne.b32 p, %5, 0; @p st.relaxed.gpu.global.v4.u32 [%0], {%1,%2,%3,%4}; }" :: "l"(a), "r"(p[0]), "r"(p[1]), "r"(p[2]), "r"(p[3]), "r"((int)on) : "memory");
}
__device__ __forceinline__ char* tok_dst(int c, int seg, int wg) { return kv_src(c, seg) + (wg ? (c & 1) * 8192 + (c & 2) * 2048 : 32768 + (c & 1) * 2048 + (c & 2) * 512); }
#define HI8 (wg ? 0x220 : 0xC0)
#define TAGM() uint32_t tm[4]; tag_masks(tm, (t16 >> (wg ? 4 : 6)) & 24)
__device__ __forceinline__ void acc_init(float* acc, const uint32_t* p) {
    #pragma unroll
    for (int i = 0; i < 4; i++) { acc[4 * i] = bflo(p[i]); acc[4 * i + 1] = bfhi(p[i]); acc[4 * i + 2] = bflo(p[4 + i]); acc[4 * i + 3] = bfhi(p[4 + i]); }
}
__device__ __forceinline__ void acc_add(float* acc, const uint32_t* p) {
    #pragma unroll
    for (int i = 0; i < 4; i++) { acc[4 * i] += bflo(p[i]); acc[4 * i + 1] += bfhi(p[i]); acc[4 * i + 2] += bflo(p[4 + i]); acc[4 * i + 3] += bfhi(p[4 + i]); }
}
__device__ __forceinline__ void tag_masks(uint32_t* m, uint32_t j8) {
    const uint32_t x = 1u << j8;
    #pragma unroll
    for (int i = 0; i < 4; i++) m[i] = opq(__byte_perm(x, 0, 0x4440 + i));
}
__device__ __forceinline__ void pack_tag(const float* acc, uint32_t* p, uint32_t tau, const uint32_t* m) {
    qk_pack(acc, p);
    #pragma unroll
    for (int i = 0; i < 8; i++) p[i] = lop3<0xB8>(p[i], m[i & 3], tau);
}
__device__ __forceinline__ uint32_t kv_stale(uint32_t w, uint32_t l16, uint32_t tau) {
    uint32_t x[12];
    const uint32_t a = opq(l16 * 2 + ((l16 >> 4) & 0x1C) + w * 12288), aq = w == 2 ? opq(l16 * 2 + ((l16 >> 2) & 0x10) + ((l16 >> 5) & 0xC) + 24576) : a;
    #pragma unroll
    for (int i = 0; i < 12; i++) x[i] = lds32(mk::TK + i * 1024 + (i < 8 ? a : aq));
    return late(stale<8, 1>(x, tau), stale<4, 1>(x + 8, tau), 1);
}
__device__ __forceinline__ void refetch_kv(int c, int seg, int w, uint32_t l16) {
    #pragma unroll 1
    for (int i = w * 24; i < w * 24 + 24; i++) {
        uint32_t v[4];
        ld_g128(v, kv_src(c, seg) + (i * 512 + (i >> 6) * (c & 3) * 4096) + l16);
        sts128(mk::TK + i * 512 + l16, make_uint4(v[0], v[1], v[2], v[3]));
    }
    __syncwarp();
}
__device__ __forceinline__ void get_kv(int c, int seg) {
    kv_expect(36864); kv_copy(mk::TK, kv_src(c, seg), 32768); kv_copy(mk::TQ, kv_src(c, seg) + (32768 + (c & 3) * 4096), 4096);
}
constexpr uint32_t ONES = 0x3F803F80u;
__device__ __forceinline__ float rcpf(float x) { float r; asm("rcp.approx.ftz.f32 %0, %1;" : "=f"(r) : "f"(x)); return r; }

#define ANN 2
#define POL 8
#define PRE0 4
#define PRE1 4
#define HC 2
#define HR 4
#define BL 1
#define NA 2
#define QF 0
#define DEEP 6
#define AHEAD(n) (PRE0 + 2 * (n) < (n) + DEEP ? PRE0 + 2 * (n) : (n) + DEEP < 16 ? (n) + DEEP : 16)
#define CO 1
#define HS 2
#define VP 0
#define KM 1
#define NLDS 2
#define AL 2
#define RP 26
#define RQ 2
#define RL 29
#define R4 1
#define KVP 12
#define LD7 8
#define XP 3
#define G2 0
#define NB 26
#define BD 8
#define NP 22
#define TA 4
#define TA0 2
#define NT 19
#define VH 1
#define TRIES 200
#define NPW 3
#define EV0 5
#define EV1 8
#define WA1 6
#define WA2 9
#define H2 10
#define QV 1
#define QD 0
#define KD 0
#define VD 0
#define WA0 4
#define ONE 0
#define PP 12
#define OBA 3
#define WA3 1
#define WB1 0
#define WB2 12
#define WB3 13
#define H0 6
#define H3 10
__device__ __forceinline__ uint32_t tagm(uint32_t w, uint32_t mask, uint32_t tau) { return lop3<0xB8>(w, mask, tau); }
__device__ __forceinline__ char* at(uint32_t lo, uint32_t hi) { char* p; asm("mov.b64 %0, {%1,%2};" : "=l"(p) : "r"(lo), "r"(hi)); return p; }
__device__ __forceinline__ float ex2(float x) { float r; asm("ex2.approx.ftz.f32 %0, %1;" : "=f"(r) : "f"(x)); return r; }
__device__ __forceinline__ float max8(const float* x) { return fmaxf(fmaxf(fmaxf(x[0], x[1]), fmaxf(x[2], x[3])), fmaxf(fmaxf(x[4], x[5]), fmaxf(x[6], x[7]))); }
__device__ __forceinline__ float max4lanes(float m) { return fmaxf(fmaxf(m, __shfl_xor_sync(~0u, m, 1)), fmaxf(__shfl_xor_sync(~0u, m, 2), __shfl_xor_sync(~0u, m, 3))); }
constexpr float SCL = 0.08838834764831845f * 1.4426950408889634f;
__device__ __forceinline__ void tok_scores(float* x, uint32_t sa) {
    float y[8];
    lds128f(x, sa); lds128f(y, sa + 1024); lds128f(x + 4, sa + 512); lds128f(y + 4, sa + 1536);
    #pragma unroll
    for (int i = 0; i < 8; i++) x[i] += y[i];
}
__device__ __forceinline__ void mem_scores(float* x, uint32_t sa) {
    float z[8];
    lds128f(z, sa + 2048); lds128f(z + 4, sa + 2560);
    x[8] = (z[0] + z[2]) + (z[4] + z[6]); x[9] = (z[1] + z[3]) + (z[5] + z[7]);
}

struct Ctx { uint32_t u_rs, u_rl, u_bs, u_bl, rblo, rbhi; int w8, c; };
template <int wg>
__device__ __forceinline__ void steps(uint32_t* W, uint32_t* T, uint32_t t16, uint32_t pa, uint32_t pb, const Ctx& cx, const CUtensorMap* tmX, const MainParams& prm) {
    using namespace mk;
    const int c = cx.c, kap = c & 1, w8 = cx.w8;
    const uint32_t rbhi = cx.rbhi;
    uint32_t u_rs = cx.u_rs, u_rl = cx.u_rl, u_bs = cx.u_bs, u_bl = cx.u_bl ^ ((c & 2) << 14);
    uint32_t u_x = cx.rblo + RB_X + (c >> 2) * 16384, u_xs = u_x + kap * 2048 + (c & 2) * 512;
    uint32_t u_ta = ((cx.u_bl & ~0x10000u) ^ (kap << 12)) + (RB_T - RB_B) + 1024;
    uint32_t u_rp = cx.rblo + RB_T + 1024 + c * 4;
    uint32_t u_og = (c & 3) * 65536 + (c >> 2) * 2048 + (w8 & 3) * 256;
    const uint32_t u_sa = (w8 & 2) * 256 + (w8 & 1) * 8;
    #define TOK_DST() tok_dst(c, seg, wg)
    constexpr int EV = wg ? EV1 : EV0;
    constexpr uint32_t VEB = VE + (wg ? EV0 * 2048 - 2048 : 0) - (16 - EV) * 2048;
    static_assert((EV0 + EV1) * 2048 <= 28672, "");
    __syncthreads();
    #pragma unroll
    for (int i = 16 - EV; i < 16; i++) sts128(VEB + i * 2048 + t16, make_uint4(T[4 * i], T[4 * i + 1], T[4 * i + 2], T[4 * i + 3]));
    asm volatile("fence.proxy.async.shared::cta;" ::: "memory");
    #pragma unroll 1
    for (uint32_t sb = 0, redo = 0, uz = prm.zero;;) {
        sb = opq(sb + 256);
        const int s = sb & 255, bc = sb >> 8;
        t16 |= uz;
        uz &= sb;
        const int seg = s + 2;
        const uint32_t tau = phase(s);
        const uint32_t l16 = opq(t16 & 0x1F0);
        uint32_t F[64];
        float ot[3][2][4];
        uint32_t an[4];
        #define LDB(i) ldsm4t(b[i][0], b[i][1], b[i][2], b[i][3], MEM + l16 + (i) * 512)
        #define ST_X() do { char* xs = at(u_xs + (pb >> 16), rbhi) + wg * 4096; \
            st_g32(xs, tagm(pack2((a[0][0] + a[1][0]) + (a[2][0] + a[3][0]), (a[0][2] + a[1][2]) + (a[2][2] + a[3][2])), mG, tau * 0x10001u)); \
            st_g32(xs + 32, tagm(pack2((a[0][1] + a[1][1]) + (a[2][1] + a[3][1]), (a[0][3] + a[1][3]) + (a[2][3] + a[3][3])), mG, tau * 0x10001u)); } while (0)
        #define ST_V() st_g64(at(u_xs + (t16 >> 1), rbhi) + (8192 + wg * 3072), \
            tagm(pack2((v[0][0] + v[1][0]) + (v[2][0] + v[3][0]), (v[0][1] + v[1][1]) + (v[2][1] + v[3][1])), mT, tau), \
            pack2((v[0][2] + v[1][2]) + (v[2][2] + v[3][2]), (v[0][3] + v[1][3]) + (v[2][3] + v[3][3])))
        #define V_MMA(i, o) do { mmaq(v[2 * ((i) & 1)], &T[8 * (i)], b[(o) + (i)][0], b[(o) + (i)][1]); mmaq(v[2 * ((i) & 1) + 1], &T[8 * (i) + 4], b[(o) + (i)][2], b[(o) + (i)][3]); } while (0)
        #define ST_R(i) do { \
                const uint32_t r0 = pack2((r[i][0][0] + r[i][1][0]) * i0, (r[i][0][1] + r[i][1][1]) * i1); \
                const uint32_t r1 = pack2((r[i][0][2] + r[i][1][2]) * i0, (r[i][0][3] + r[i][1][3]) * i1); \
                st_g64(at(ra ^ (i * 0x3000), rbhi), tagm(r0, mT, tau), r1); } while (0)
        #define LD_OB(i) ldsm4t(ob[4 * (i)], ob[4 * (i) + 1], ob[4 * (i) + 2], ob[4 * (i) + 3], OB + l16 + (i) * 512)
        #define WO_MMA(have, more, mid, tail) uint32_t ob[16], ra; float r[2][2][4] = {}; \
            LD_OB(0); __syncwarp(); LD_OB(1); __syncwarp(); if (OBA > 2) { LD_OB(2); __syncwarp(); } \
            _Pragma("unroll") for (int i = have; i < have + more; i++) { lds128u(&F[4 * i], WO + t16 + i * 4096); __syncwarp(); } \
            _Pragma("unroll") for (int i = 0; i < 16; i++) { \
                if (!(i & 1) || (i > 4 && i < 8)) CUT(pb); \
                if (i == 4) LD_OB(OBA); \
                if (i == 5 && OBA == 2) LD_OB(3); \
                { const int n = have + more + i - 8 + OBA; if (i >= 8 - OBA && n < 16) lds128u(&F[4 * n], WO + t16 + n * 4096); } \
                if (wg == 0 && i == 4) { const float2 su = lds64f(SUM + (l16 >> 1)); i0 = su.x; i1 = su.y; } \
                mmaq(r[(i >> 1) & 1][i & 1], &F[4 * i], ob[(i >> 2) * 4 + 2 * (i & 1)], ob[(i >> 2) * 4 + 2 * (i & 1) + 1]); \
                if (wg && i == 2) { i0 = opqf(rcpf(i0)); i1 = opqf(rcpf(i1)); } \
                if (i == PP) { mid; } \
                if (wg && i == POL) POLL(); \
                if (!wg && i == KVP) bulk_copy(TK + 16384 + w8 * 4096, kv_src(c, s + 1) + (16384 + w8 * 4096), 4096, MB_KV); \
                if (i == 11) { ra = (l16 >> 1) * 33 & 0x1078; CUT(ra); } \
                if (i == 13) ra = opq(ra ^ u_rs); } \
            CUT(pb); tail; \
            if (!wg) { i0 = rcpf(i0); i1 = rcpf(i1); } \
            ST_R(0); ST_R(1)
        #define LD_X(r, o) do { ld_g64(r, xa + (o)); ld_g64(r + 2, xa + ((o) + 2048)); ld_g64(r + 4, xa + ((o) + 1024)); ld_g64(r + 6, xa + ((o) + 3072)); } while (0)
        #define REPORT(w, add) asm volatile("{ .reg .pred p; .reg .u32 t; setp.lt.u32 p, %1, 32; mov.u32 t, %1; @p mov.u32 t, %%globaltimer_lo; add.u32 t, t, %3; lop3.b32 t, t, 31, %2, 0xB8; @p st.relaxed.gpu.global.u32 [%0], t; }" \
            :: "l"(at(u_rp + (l16 << 8), rbhi)), "r"(t16 - (w) * 512), "r"(s), "r"(add) : "memory")
        #define POLL() asm volatile("{ .reg .pred p; setp.ge.u32 p, %5, 3584; mov.u32 %0, 0; mov.u32 %1, 0; mov.u32 %2, 0; mov.u32 %3, 0; @p ld.relaxed.gpu.global.v4.u32 {%0,%1,%2,%3}, [%4]; }" \
            : "=&r"(an[0]), "=&r"(an[1]), "=&r"(an[2]), "=&r"(an[3]) : "l"(at(u_ta + l16, rbhi)), "r"(t16) : "memory")
        #define GET_B(sl) do { const uint32_t a_ = u_bl ^ (sl); bulk_copy(MEM, at(a_, rbhi), 4096, MB_B); bulk_copy(MEM + 4096, at(a_ ^ 0x3000, rbhi), 4096, MB_B); } while (0)
        if constexpr (wg == 0) {
            float a[4][4], v[4][4] = {};
            uint32_t b[16][4];
            if (__builtin_expect(redo, 0)) {
                RETRY(6, 1);
                bsync<B_RD, 256>();
                if (w8 == 3) { bulk_expect(MB_B, 8192); GET_B(1 << 20); }
                __syncwarp();
            }
            const uint32_t ck = opq(t16 * 2 + ((l16 >> 4) & 0x1C)), tp = opq(phase(s - 1)), cm = opq((2 * bc + (s > 0 && bc < SPIN_LIMIT)) | (t16 >> 19));
            CUT(pa);
            mbar_wait(MB_B, ~bc & 1);
            #define ORD(n) (n)
            LDB(ORD(0)); __syncwarp(); LDB(ORD(1)); __syncwarp();
            const uint32_t c0 = lds32(MEM + ck), c1 = lds32(MEM + 4096 + ck);
            __syncwarp();
            #pragma unroll
            for (int n = 2; n < PRE0; n++) { LDB(ORD(n)); __syncwarp(); }
            PROF(0);
            uint32_t vw[2];
            #pragma unroll
            for (int n = 0; n < 16; n++) {
                const int i = ORD(n);
                CUT(pa);
                #pragma unroll
                for (int m = AHEAD(n); m < AHEAD(n + 1); m++) { LDB(ORD(m)); __syncwarp(); }
                if (n == HC) redo = opq(lop3<0x7E>(c0, tp, c1) & cm);
                if (n == HC + 1) asm volatile("{ .reg .pred p; setp.ne.u32 p, %2, 0; @p st.shared.u32 [%0], %1; }" :: "r"(SUM + 256), "r"(cm), "r"(redo & 1) : "memory");
                if (n == H0) barrive<B_H0, 256>();
                if (n == HR + 1) { redo = lds32(SUM + 256 + opq(t16 >> 20)); __syncwarp(); }
                if (n == HR) bsync<B_START, 128>();
                if (n == 12) redo = !late(redo ^ (2 * bc + 1), 0, ~0u);
                const int e = n < 8 ? 0 : 2 * (~n & 1);
                if (!(n & 7)) a[e][0] = a[e][1] = a[e][2] = a[e][3] = a[e + 1][0] = a[e + 1][1] = a[e + 1][2] = a[e + 1][3] = 0.f;
                mmaq(a[e], &W[8 * i], b[i][0], b[i][1]);
                if (n < 8) { mmaq(v[0], &T[8 * i], b[i][0], b[i][1]); CUT(pa); }
                mmaq(a[e + 1], &W[8 * i + 4], b[i][2], b[i][3]);
                if (n < 8) mmaq(v[1], &T[8 * i + 4], b[i][2], b[i][3]);
                if (n == 10) { vw[0] = opq(pack2(v[0][0] + v[1][0], v[0][1] + v[1][1])); vw[1] = opq(pack2(v[0][2] + v[1][2], v[0][3] + v[1][3])); }
            }
            CUT(pa);
            if (__builtin_expect(redo, 0)) { __syncwarp(); continue; }
            CUT(pa); CUT(pb);
            const uint32_t mG = (l16 & 0x1C0) ? 0 : 0x10001u, mT = (l16 & 0x30) ? 0 : 1;
            ST_X();
            CUT(pa);
            PROF(1);
            const char* const xa = at(u_x + (t16 >> 1), rbhi);
            float sc[4][4];
            uint32_t k[8], A[16], q[16], kf[16];
            #define LD_Q(xb) do { LD_X(q, 0); { const char* const xa = xb; LD_X(q + 8, 0); } } while (0)
            #define XB() at((u_x + (opq(t16) >> 1)) ^ 256, rbhi)
            #define LD_A(i) ldsm4t(A[4 * i], A[4 * i + 1], A[4 * i + 2], A[4 * i + 3], TQ + (i & 1) * 1024 + ((i & 2) ? qb : qa))
            uint32_t k1[16];
            #define LD_K(i) do { ldsm4t(kf[4 * i], kf[4 * i + 1], kf[4 * i + 2], kf[4 * i + 3], TK + ka[i]); ldsm4t(k1[4 * i], k1[4 * i + 1], k1[4 * i + 2], k1[4 * i + 3], TK + 8192 + ka[i]); __syncwarp(); } while (0)
            const char* const xb = XB();
            const uint32_t ka[4] = {opq(pa & 0xFFFF), opq((pa & 0xFFFF) ^ 0x400), opq((pa & 0xFFFF) ^ 0x10), opq((pa & 0xFFFF) ^ 0x410)}, qa = opq(pa >> 16), qb = opq(qa ^ 0x100);
            st_g64(at(u_xs + (t16 >> 1), rbhi) + 8192, tagm(vw[0], mT, tau), vw[1]);
            CUT(pb);
            bsync<B_H2, 256>();
            if (QF) { LD_Q(xb); __syncwarp(); }
            #pragma unroll
            for (int i = 0; i < NA; i++) LD_K(i);
            CUT(pb);
            #pragma unroll
            for (int i = 0; i < 4 * NA; i++) kf[i] = opq(hadd2(kf[i], k1[i]));
            CUT(pb);
            if (!QF) { DELAY(QD); LD_Q(xb); CUT(pb); }
            bsync<B_H3, 256>();
            #pragma unroll
            for (int i = NA; i < 4; i++) LD_K(i);
            LD_A(0); LD_A(1); LD_A(2); LD_A(3);
            CUT(pb);
            if (KM == 1) {
                #pragma unroll
                for (int i = 4 * NA; i < 16; i++) kf[i] = opq(hadd2(kf[i], k1[i]));
                CUT(pb);
            }
            DELAY(KD);
            LD_X(k, 4096);
            barrive<B_VX, 256>();
            CUT(pb);
            PROF(3);
            if (KM == 2) {
                #pragma unroll
                for (int i = 4 * NA; i < 16; i++) kf[i] = opq(hadd2(kf[i], k1[i]));
            }
            #pragma unroll
            for (int i = 0; i < 8; i++) A[2 * i + 1] = opq(hadd2(A[2 * i], A[2 * i + 1]));
            CUT(pb);
            AGAIN(1, LD_Q(XB()); LD_X(k, 4096); sts32(SUM + 268, s + 1), late(stale<4, 2>(q, tau), stale<4, 2>(q + 8, tau), mT))
            #pragma unroll
            for (int i = 0; i < 4; i++) {
                A[4 * i] = hadd2(q[4 * i], q[4 * i + 2]); A[4 * i + 2] = hadd2(q[4 * i + 1], q[4 * i + 3]);
                if (i < 2) { sc[i][0] = sc[i][1] = sc[i][2] = sc[i][3] = sc[2 + i][0] = sc[2 + i][1] = sc[2 + i][2] = sc[2 + i][3] = 0.f; }
                mmaq(sc[i & 1], A + 4 * i, kf[2 * i], kf[2 * i + 1]); mmaq(sc[2 + (i & 1)], A + 4 * i, kf[8 + 2 * i], kf[9 + 2 * i]);
            }
            sts128f(SC + t16, sc[0][0] + sc[1][0], sc[0][1] + sc[1][1], sc[2][0] + sc[3][0], sc[2][1] + sc[3][1]);
            barrive<B_S1, 256>();
            sts128f(SC + 3072 + t16, sc[0][2] + sc[1][2], sc[0][3] + sc[1][3], sc[2][2] + sc[3][2], sc[2][3] + sc[3][3]);
            load_frag<0, WB1>(WO + t16, F);
            const uint32_t sa = opq(l16 + u_sa);
            CUT(pb);
            PROF(4);
            float d[16];
            #pragma unroll 1
            for (int n_ = 0;; n_++) {
                #pragma unroll
                for (int i = 0; i < 4; i++) { d[4 * i] = d[4 * i + 1] = d[4 * i + 2] = d[4 * i + 3] = 0.f; mmaq(d + 4 * i, A + 4 * (i >> 1), k[2 * i], k[2 * i + 1]); }
                if (__builtin_expect(!late(stale<2, 2>(k, tau), stale<2, 2>(k + 4, tau), mT), 1) || n_ >= SPIN_LIMIT) break;
                RETRY(2, 1);
                LD_X(k, 4096);
            }
            sts64f(SC + 2048 + sa, (d[0] + d[4]) + (d[8] + d[12]), (d[1] + d[5]) + (d[9] + d[13]));
            barrive<B_SC, 256>();
            CUT(pb);
            sts64f(SC + 5120 + sa, (d[2] + d[6]) + (d[10] + d[14]), (d[3] + d[7]) + (d[11] + d[15]));
            PROF(5);
            if (w8 == 0) {
                float x[10];
                bsync<B_S0, 128>();
                tok_scores(x, SC + 3072 + l16); mem_scores(x, SC + 3072 + l16);
                __syncwarp();
                load_frag<WB1, WB2>(WO + t16, F);
                const int g = l16 >> 6, lim = 8 * (g >> 1) + 2 * (c & 3) + (g & 1) - ((l16 >> 1) & 0x18);
                #pragma unroll
                for (int i = 0; i < 8; i++) if (i > lim) x[i] = -INFINITY;
                const float ms = opqf(-SCL * max4lanes(fmaxf(max8(x), fmaxf(x[8], x[9]))));
                CUT(pb);
                #pragma unroll
                for (int i = 0; i < 10; i++) x[i] = ex2(fmaf(x[i], SCL, ms));
                load_frag<WB2, WB3>(WO + t16, F);
                sts128(PT + l16, make_uint4(pack2(x[0], x[1]), pack2(x[2], x[3]), pack2(x[4], x[5]), pack2(x[6], x[7])));
                sts32(PT + 512 + (l16 >> 2), pack2(x[8], x[9]));
                if (!ONE) barrive<B_PT, 160>();
            } else {
                if (ANN == 2) { bsync<B_S0, 128>(); const uint32_t f = lds32(SUM + 268 + opq(t16 >> 16)); REPORT(3, f == s + 1 ? P(2) : 0); } else barrive<B_S0, 128>();
                if (w8 == 1) {
                    mbar_wait(MB_X, ~seg & 1); bulk_expect(MB_X, 32768);
                    if (XPF) prefetch_l2(prm.x + (((seg + XPF) & 63) * 65536 + c * 512), 512);
                    __syncwarp();
                    if (XDL == 300) load_x(tmX, c, seg + 1, (s & 1) ? XT : XT2);
                }
                else if (w8 == 2) {
                    bulk_expect(MB_KV, 36864);
                    bulk_copy(TK, kv_src(c, s + 1), 16384, MB_KV); bulk_copy(TQ, kv_src(c, s + 1) + (32768 + (c & 3) * 4096), 4096, MB_KV);
                    bulk_expect(MB_B, 8192); bulk_expect(MB_R, 4096);
                    __syncwarp();
                }
                bsync<B_SC2, 224>();
                load_frag<WB1, WB3>(WO + t16, F);
                __syncwarp();
                CUT(pb);
            }
            bsync<B_O2, 256>();
            PROF(6);
            float i0, i1;
            WO_MMA(WB3, 0, , );
        } else {
            float a[4][4], v[4][4] = {};
            uint32_t b[16][4];
            barrive_if<B_RD, 256>(redo);
            CUT(pa);
            bsync<B_H0, 256>();
            #pragma unroll
            for (int n = 0; n < PRE1; n++) { LDB(n); __syncwarp(); }
            redo = lds32(SUM + 256 + opq(t16 >> 20));
            PROF(0);
            #pragma unroll
            for (int i = 0; i < 16; i++) {
                if (!(i & 1)) {
                    CUT(pa);
                    if (PRE1 < 8 && i + PRE1 < 16) { LDB(i + PRE1); __syncwarp(); LDB(i + PRE1 + 1); __syncwarp(); }
                    if (PRE1 == 8 && i >= 2 && i < 10) { LDB(i + 6); __syncwarp(); LDB(i + 7); __syncwarp(); }
                    if (i == 6) redo = !late(redo ^ (2 * bc + 1), 0, ~0u);
                    if (i == H2) { barrive_if<B_H2, 256>(!redo); CUT(pa); }
                }
                else if (CO) CUT(pa);
                if (i < 2) { a[2 * i][0] = a[2 * i][1] = a[2 * i][2] = a[2 * i][3] = a[2 * i + 1][0] = a[2 * i + 1][1] = a[2 * i + 1][2] = a[2 * i + 1][3] = 0.f; }
                mmaq(a[2 * (i & 1)], &W[8 * i], b[i][0], b[i][1]); mmaq(a[2 * (i & 1) + 1], &W[8 * i + 4], b[i][2], b[i][3]);
            }
            if (__builtin_expect(redo, 0)) { __syncwarp(); continue; }
            CUT(pa); CUT(pb);
            const uint32_t mG = (l16 & 0x1C0) ? 0 : 0x10001u, mT = (l16 & 0x30) ? 0 : 1;
            ST_X();
            barrive<B_H3, 256>();
            CUT(pa);
            PROF(1);
            #pragma unroll
            for (int i = 7; i >= 0; i--) V_MMA(i, 8);
            ST_V();
            CUT(pb);
            bsync<B_VX, 256>();
            PROF(2);
            uint32_t vf[16], vm[16];
            const uint32_t va = opq(pa), vb = opq(va ^ 0x20);
            #define LD_V() do { _Pragma("unroll") for (int i = 0; i < 4; i++) { const uint32_t a_ = TK + 16384 + ((i & 1) ? vb : va) + (i >> 1) * 4096; \
                ldsm4(vf[4 * i], vf[4 * i + 1], vf[4 * i + 2], vf[4 * i + 3], a_); ldsm4(vm[4 * i], vm[4 * i + 1], vm[4 * i + 2], vm[4 * i + 3], a_ + 8192); } } while (0)
            LD_V();
            __syncwarp();
            load_frag<0, WA0>(WO + t16, F);
            #pragma unroll
            for (int i = 0; i < 16; i++) vf[i] = opq(hadd2(vf[i], vm[i]));
            const char* const xa = at(u_x + (t16 >> 1), rbhi) + (8192 - 1024);
            if (VP) CUT(pb);
            DELAY(VD);
            LD_X(vm, 0); LD_X(vm + 8, 4096);
            __syncwarp();
            load_frag<WA0, WA1>(WO + t16, F);
            CUT(pb);
            float x[10];
            bsync<B_S1, 256>();
            tok_scores(x, SC + l16);
            const float mt = opqf(max8(x));
            if (ANN == 3) REPORT(7, 0);
            CUT(pb);
            PROF(3);
            bsync<B_SC, 256>();
            mem_scores(x, SC + l16);
            const float m1 = fmaxf(mt, fmaxf(x[8], x[9]));
            const float m2 = __shfl_xor_sync(~0u, m1, 1), m3 = __shfl_xor_sync(~0u, m1, 2), m4 = __shfl_xor_sync(~0u, m1, 3);
            CUT(pb);
            load_frag<WA1, WA2>(WO + t16, F);
            barrive<B_SC2, 224>();
            uint32_t p[5], vs[4];
            #define SUM_V() do { _Pragma("unroll") for (int i = 0; i < 4; i++) { const int e = (i >> 1) * 4 + (i & 1); vs[i] = hadd2(hadd2(vm[e], vm[e + 8]), hadd2(vm[e + 2], vm[e + 10])); } } while (0)
            CUT(pb);
            const float ms = -SCL * fmaxf(fmaxf(m1, m2), fmaxf(m3, m4));
            PROF(5);
            #pragma unroll
            for (int i = 0; i < 10; i++) x[i] = fmaf(x[i], SCL, ms);
            x[8] = opqf(ex2(x[8])); x[9] = opqf(ex2(x[9]));
            CUT(pb);
            uint32_t badv = late(stale<4, 2>(vm, tau), stale<4, 2>(vm + 8, tau), mT);
            SUM_V();
            #pragma unroll
            for (int i = 0; i < 4; i++) { x[i] = opqf(ex2(x[i])); vs[i] = opq(vs[i]); }
            const uint32_t z0 = t16 >> 16;
            uint32_t one[4] = {opq(ONES | z0), opq(ONES ^ z0), opq(ONES + z0), opq(ONES - z0)};
            CUT(pb);
            #pragma unroll
            for (int i = 4; i < 8; i++) x[i] = ex2(x[i]);
            #pragma unroll
            for (int i = 0; i < 5; i++) p[i] = pack2(x[2 * i], x[2 * i + 1]);
            float sm[4] = {};
            #define PV(also) do { float o[8] = {}; \
                mma8(o, vs[0], vs[1], p[4]); mma8(o + 4, vs[2], vs[3], p[4]); if (also) mma8(sm, one[0], one[1], p[4]); \
                mmaq(o, vf, p[0], p[1]); mmaq(o + 4, vf + 8, p[0], p[1]); if (also) mmaq(sm, one, p[0], p[1]); \
                mmaq(o, vf + 4, p[2], p[3]); mmaq(o + 4, vf + 12, p[2], p[3]); if (also) mmaq(sm, one, p[2], p[3]); \
                stsm4(OB - 2048 + opq(t16), pack2(o[0], o[1]), pack2(o[2], o[3]), pack2(o[4], o[5]), pack2(o[6], o[7])); } while (0)
            PV(true);
            if (w8 == 4) sts64f(SUM + (l16 >> 1), sm[0], sm[1]);
            if (__builtin_expect(badv, 0)) {
                int n_ = 0;
                uint32_t vm[16];
                const char* const xa = at(u_x + (8192 - 1024) + (opq(t16) >> 1), rbhi);
                do { RETRY(3, 1); LD_X(vm, 0); LD_X(vm + 8, 4096); } while (late(stale<4, 2>(vm, tau), stale<4, 2>(vm + 8, tau), mT) && ++n_ < SPIN_LIMIT);
                SUM_V();
                PV(false);
            }
            if (ONE) bsync<B_O2, 256>(); else { barrive<B_O2, 256>(); bsync<B_O, 128>(); }
            PROF(6);
            float i0 = sm[0], i1 = sm[1];
            #define GET_P() if (!ONE) bsync<B_PT, 160>(); lds128u(p, PT + l16); p[4] = lds32(PT + 512 + (l16 >> 2))
            #define TOK_PV() { const uint32_t z = t16 >> 17; one[0] = ONES | z; one[1] = ONES ^ z; one[2] = ONES + z; one[3] = ONES - z; } \
                _Pragma("unroll") for (int i = 0; i < 12; i++) ot[i >> 2][0][i & 3] = ot[i >> 2][1][i & 3] = 0.f; \
                mma8(ot[0][0], vs[0], vs[1], p[4]); mma8(ot[1][0], vs[2], vs[3], p[4]); mma8(ot[2][0], one[0], one[1], p[4]); \
                mmaq(ot[0][1], vf + 4, p[2], p[3]); mmaq(ot[1][1], vf + 12, p[2], p[3]); mmaq(ot[2][1], one, p[2], p[3]); CUT(pa)
            WO_MMA(WA2, WA3, GET_P(), TOK_PV());
            CUT(pa);
            mmaq(ot[0][0], vf, p[0], p[1]); mmaq(ot[1][0], vf + 8, p[0], p[1]); mmaq(ot[2][0], one, p[0], p[1]);
            CUT(pb);
            barrive<B_GO, 256>();
        }
        CUT(pb);
        PROF(7);
        #define PK_O() const float j0 = rcpf(ot[2][0][0] + ot[2][1][0]), j1 = rcpf(ot[2][0][1] + ot[2][1][1]); uint32_t ow[4]; \
            _Pragma("unroll") for (int i = 0; i < 4; i++) \
                ow[i] = opq(pack2((ot[i >> 1][0][2 * (i & 1)] + ot[i >> 1][1][2 * (i & 1)]) * j0, (ot[i >> 1][0][2 * (i & 1) + 1] + ot[i >> 1][1][2 * (i & 1) + 1]) * j1))
        #define ST_O() do { uint32_t* og = (uint32_t*)((char*)g_O + (u_og + (l16 >> 2))); \
            _Pragma("unroll") for (int i = 0; i < 4; i++) og[(i >> 1) * 256 + (i & 1) * 32] = ow[i]; } while (0)
        #define BSO() ((u_bs) ^ ((l16 & 0x10) + ((l16 >> 3) & 0xC) + (l16 & 0x80) * 0x20 + (l16 & 0x100) * 0x80))
        const uint32_t taus = phase(seg);
        const uint64_t* const dq = c_xd + (s & 1) * 32; const uint64_t* const dv = dq + (wg * 16 | uz);
        float acc[16], acv[16];
        uint32_t u[8];
        if constexpr (wg == 0) {
            if (s == NSEG - 1) { bsync<B_GO, 256>(); st_g32(at(BSO(), rbhi), 0); mbar_wait(MB_KV, 1); if (XDL == 300) mbar_wait(MB_X, 1); break; }
            load_frag<16 - EV, 16, 2048>(VEB + t16, T);
            bsync<B_GO, 256>();
            PROF(8);
            wg_run<0, 16 - EV>(acv, T, dv);
            wg_run<16 - EV, 16>(acv, T, dv);
            wg_run<0, 5>(acc, W, dq); wg_wait<1>();
            qk_pack(acv, u);
            #pragma unroll
            for (int i = 0; i < 8; i++) u[i] = opq(u[i]);
            CUT(pa);
            wg_run<5, 8>(acc, W, dq);
            __syncwarp();
            sts128(SC + opq(t16), make_uint4(u[0], u[1], u[2], u[3])); sts128(SC + 2048 + opq(t16), make_uint4(u[4], u[5], u[6], u[7]));
            barrive<B_VX, 256>();
            __syncwarp();
            PROF(9);
            wg_run<8, 12>(acc, W, dq);
            CUT(pa);
            char* const bs = at(opq(BSO()), opq(rbhi));
            CUT(pa);
            wg_run<12, 15>(acc, W, dq);
            CUT(pa);
            const uint32_t ro = opq(l16 * 8 + ((l16 & 0x70) ^ ((w8 & 3) << 5))), ro2 = opq(ro ^ 0x10);
            const uint32_t mG = opq((l16 & 0x1C0) ? 0 : 0x10001u), mB = opq((((l16 >> 2) & 4) + ((l16 >> 5) & 3)) == ((u_bs >> 7) & 7) ? 1 : 0), zz = t16 >> 18;
            CUT(pa);
            wg_run<15, 18>(acc, W, dq);
            CUT(pa);
            const uint32_t one[4] = {opq(ONES | zz), opq(ONES ^ zz), opq(ONES + zz), opq(ONES - zz)};
            const uint32_t par = s & 1, tt = tau * 0x10001u;
            CUT(pa);
            wg_run<18, RP>(acc, W, dq);
            CUT(pa);
            PROF(10);
            mbar_wait(MB_R, par);
            PROF(14);
            uint32_t x[8], bad;
            float d[4][4];
            #define SUM_R() do { ldsm4t(x[0], x[1], x[2], x[3], RS + ro); ldsm4t(x[4], x[5], x[6], x[7], RS + ro2); \
                _Pragma("unroll") for (int i = 0; i < 4; i++) { d[i][0] = d[i][1] = d[i][2] = d[i][3] = 0.f; mmaq(d[i], one, x[2 * i], x[2 * i + 1]); } } while (0)
            #define PUT_B() do { bad = late(stale<2, 1>(x, tt), stale<2, 1>(x + 2, tt), mG); \
                const uint32_t w0 = pack2(d[0][0] + d[1][0], d[0][1] + d[1][1]), w1 = pack2(d[2][0] + d[3][0], d[2][1] + d[3][1]); \
                asm volatile("{ .reg .pred p; setp.eq.b32 p, %2, 0; @p st.relaxed.gpu.global.u32 [%0], %1; }" :: "l"(bs), "r"(tagm((l16 & 0x40) ? w1 : w0, mB, tt)), "r"(bad) : "memory"); } while (0)
            SUM_R();
            CUT(pa);
            wg_run<RP, (RP + RQ < 32 ? RP + RQ : 32)>(acc, W, dq);
            if (RP + RQ >= RL) barrive<B_BT, 256>();
            CUT(pa);
            PUT_B();
            const uint32_t tb = lds32(SUM + 272 + 28 + zz);
            CUT(pa);
            PROF(11);
            if (RP + RQ < RL) { wg_run<RP + RQ, RL>(acc, W, dq); __syncwarp(); barrive<B_BT, 256>(); __syncwarp(); }
            wg_run<(RP + RQ < RL ? RL : RP + RQ), 32>(acc, W, dq);
            CUT(pa);
            AGAIN(5, ld_g128(x, at(u_rl + opq(ro), rbhi)); ld_g128(x + 4, at(u_rl + opq(ro2), rbhi)); sts128(RS + ro, make_uint4(x[0], x[1], x[2], x[3])); sts128(RS + ro2, make_uint4(x[4], x[5], x[6], x[7]));
                     CUT(pa); __syncwarp(); SUM_R(); PUT_B(), bad)
            #define REQ_B() if (w8 == 3) { TRC(13, gtime() - tb); wait_g(tb, t16); GET_B(0); PROFW(13, 3); }
            if (!BL) REQ_B();
            const uint32_t ps = opq(pb & 0xFFFF), ps2 = opq(ps ^ HI8);
            char* const qd0 = TOK_DST() + ps; char* const qd1 = TOK_DST() + ps2;
            TAGM();
            wg_wait<0>();
            pack_tag(acc, u, taus, tm);
            #pragma unroll
            for (int i = 0; i < 8; i++) u[i] = opq(u[i]);
            CUT(pa);
            if (BL) REQ_B();
            bsync<B_S0, 128>();
            st_if(seg < NSEG, qd0, u); st_if(seg < NSEG, qd1, u + 4);
            if (XDL >= 200 && XDL < 300 && w8 == 1) { CUT(pb); DELAY(XDL - 200); load_x(tmX, c, seg + 1, (s & 1) ? XT : XT2); }
            PROF(12);
        } else {
            #define LAST() __reduce_max_sync(~0u, max(max(an[0], an[1]), max(an[2], an[3])))
            PK_O();
            CUT(pa);
            if (s == NSEG - 1) { ST_O(); break; }
            PROF(8);
            if (w8 != 7) {
                load_frag<16 - EV, 16 - EV + TA0, 2048>(VEB + t16, T);
                mbar_wait(MB_KV, s & 1);
                AGAIN(0, refetch_kv(c, s + 1, w8 - 4, l16), kv_stale(w8 - 4, l16, phase(s + 1)))
            } else {
                uint32_t tr = LAST();
                AGAIN(8, ld_g128(an, at(u_ta + l16, rbhi)); tr = LAST(), late(stale<2, 1>(an, s), stale<2, 1>(an + 2, s), 31))
                tr = (tr & ~31u) + P(0);
                TRC(14, gtime() - tr);
                wait_g(tr, t16);
                if (R4) { for (int i = 0; i < 4; i++) bulk_copy(RS + i * 1024, at(u_rl + i * 1024, rbhi), 1024, MB_R); }
                else bulk_copy(RS, at(u_rl, rbhi), 4096, MB_R);
                PROFW(14, 3);
                sts32(SUM + 272 + 28, tr + P(1));
                load_frag<16 - EV, 16 - EV + TA0, 2048>(VEB + t16, T);
                if (XDL < 100) { CUT(pb); DELAY(XDL); load_x(tmX, c, seg + 1, (s & 1) ? XT : XT2); }
            }
            CUT(pa);
            bsync<B_VX, 256>();
            lds128u(u, SC - 2048 + opq(t16)); lds128u(u + 4, SC + opq(t16));
            CUT(pa);
            ST_O();
            CUT(pa);
            load_frag<16 - EV + TA0, 16 - EV + TA, 2048>(VEB + t16, T);
            acc_init(acv, u);
            #pragma unroll
            for (int i = 0; i < 16; i++) acv[i] = opqf(acv[i]);
            const uint32_t ps = opq(pb & 0xFFFF), ps2 = opq(ps ^ HI8);
            CUT(pa);
            PROF(9);
            if (XDL == 100 && w8 == 7) load_x(tmX, c, seg + 1, (s & 1) ? XT : XT2);
            bsync<B_BT, 256>();
            CUT(pa);
            wg_run<0, 3>(acc, W, dq);
            PROF(11);
            wg_run<3, NT, true>(acc, W, dq);
            __syncwarp();
            load_frag<16 - EV + TA, 16, 2048>(VEB + t16, T);
            __syncwarp();
            wg_run<NT, NB>(acc, W, dq);
            char* const qd0 = TOK_DST() + ps; char* const qd1 = TOK_DST() + ps2;
            TAGM();
            wg_run<NB, 32>(acc, W, dq);
            wg_run<0, 5, true>(acv, T, dv);
            wg_wait<1>();
            PROF(12);
            pack_tag(acc, u, taus, tm);
            #pragma unroll
            for (int i = 0; i < 8; i++) u[i] = opq(u[i]);
            CUT(pa);
            wg_run<5, 16 - EV>(acv, T, dv);
            __syncwarp();
            st_if(seg < NSEG, qd0, u); st_if(seg < NSEG, qd1, u + 4);
            __syncwarp();
            wg_run<16 - EV, 16>(acv, T, dv);
            CUT(pa);
            PROF(10);
            wg_wait<0>();
            PROF(13);
            pack_tag(acv, u, taus, tm);
            st_if(seg < NSEG, qd0 + 16384, u); st_if(seg < NSEG, qd1 + 16384, u + 4);
        }
        sb++;
        u_rs ^= 1 << 20; u_rl ^= 1 << 20; u_bs ^= 1 << 20; u_bl ^= 1 << 20; u_x ^= 1 << 20; u_xs ^= 1 << 20; u_ta ^= 1 << 20; u_rp ^= 1 << 20; u_og += 262144;
    }
}

namespace ck {
constexpr uint32_t UPL = 144 * 16 + 64, UCH = 2 * UPL;
constexpr uint32_t FCP = 4160, FCH = 2 * FCP;
template <int NW> struct At { static constexpr uint32_t K = NW == 2 ? mk::XT : mk::SB, V = K + 32768, F = NW == 2 ? V : V + 32768, U = F + 8 / NW * FCH; };
static_assert(At<2>::U + 4 * UCH <= mk::OB && At<1>::U + 8 * UCH <= mk::OB, "");
}
struct ConvIn { const bf16 *shift_k, *ssm_k, *ssm_D; };
template <int NW> struct ConvRaw { uint4 f[8 / NW], sk[4 / NW]; uint32_t fn, d; };
template <int NW> __device__ __forceinline__ void strip_request(const CUtensorMap* tmK, int grp) {
    mbar_expect(mk::MB_C, 65536);
    #pragma unroll 1
    for (int i = 0; i < 16; i++) tma3d(ck::At<NW>::K + i * 4096, tmK + (i >> 3), grp * 8, 0, i & 7, mk::MB_C);
}
template <int NW> __device__ __forceinline__ void conv_load(ConvRaw<NW>& r, const ConvIn& in, int ch0) {
    const int tid = threadIdx.x, w = tid >> 5, ch = ch0 + w / NW, e = w % NW;
    const bf16* fp = in.ssm_k + (size_t)ch * SEQ + e * 1024;
    #pragma unroll
    for (int i = 0; i < 8 / NW; i++) r.f[i] = __ldg((const uint4*)fp + (tid & 31) + 32 * i);
    r.fn = e == NW - 1 ? 0 : __ldg((const uint32_t*)(fp + 1024));
    r.d = __ldg((const unsigned short*)in.ssm_D + ch);
    #pragma unroll
    for (int i = 0; i < 4 / NW; i++) r.sk[i] = __ldg((const uint4*)(in.shift_k + ch0 * 4) + i);
}
template <int NW> __device__ __forceinline__ void kv_build(const ConvRaw<NW>& r, int ch0) {
    using namespace ck;
    const int tid = threadIdx.x;
    if (tid < 32 * 8 / NW) sts128(At<NW>::U + (tid >> 4) * UPL + (tid & 15) * 16, make_uint4(0, 0, 0, 0));
    #pragma unroll
    for (int hf = 0; hf < 2 / NW; hf++) {
        const uint32_t a = tid * 16 + (ch0 & 4) * 2 + hf * 8;
        float2 kr[11], vr[8];
        #pragma unroll
        for (int i = 0; i < 11; i++) { kr[i] = lds64f(At<NW>::K + ((i + 5) & 7) * 4096 - (i < 3) * 16 + a); if (i < 3 && !tid) kr[i] = make_float2(0.f, 0.f); }
        #pragma unroll
        for (int i = 0; i < 8; i++) vr[i] = lds64f(At<NW>::V + i * 4096 + a);
        #pragma unroll
        for (int ch = 0; ch < 4; ch++) {
            const uint32_t s01 = ((const uint32_t*)r.sk)[8 * hf + 2 * ch], s23 = ((const uint32_t*)r.sk)[8 * hf + 2 * ch + 1];
            const float sk[4] = {bflo(s01), bfhi(s01), bflo(s23), bfhi(s23)};
            float kf[11], kv[8];
            #pragma unroll
            for (int i = 0; i < 11; i++) { const uint32_t wd = __float_as_uint((ch & 2) ? kr[i].y : kr[i].x); kf[i] = (ch & 1) ? bfhi(wd) : bflo(wd); }
            #pragma unroll
            for (int i = 0; i < 8; i++) {
                const uint32_t wv = __float_as_uint((ch & 2) ? vr[i].y : vr[i].x);
                kv[i] = fmaf(kf[i + 3], sk[0], fmaf(kf[i + 2], sk[1], fmaf(kf[i + 1], sk[2], kf[i] * sk[3]))) * ((ch & 1) ? bfhi(wv) : bflo(wv));
            }
            sts128(At<NW>::U + (hf * 4 + ch) * UCH + (tid & 1) * UPL + (16 + (tid >> 1)) * 16,
                   make_uint4(pack2(kv[0], kv[1]), pack2(kv[2], kv[3]), pack2(kv[4], kv[5]), pack2(kv[6], kv[7])));
        }
    }
}
template <int NW> __device__ __forceinline__ void conv_filter(const ConvRaw<NW>& r) {
    using namespace ck;
    constexpr int N = 8 / NW;
    const int w = threadIdx.x >> 5, lane = threadIdx.x & 31, e = w % NW;
    const uint32_t fb = At<NW>::F + w / NW * FCH;
    if (!e && lane < 8) { sts32(fb + 4128 + lane * 4, 0); sts32(fb + FCP + 4128 + lane * 4, lane ? 0 : r.f[0].x & 0xFFFFu); }
    #pragma unroll
    for (int i = 0; i < N; i++) {
        const int vi = e * 128 + lane + 32 * i;
        const uint4 x = r.f[i];
        const uint32_t a = __shfl_down_sync(~0u, x.x, 1), b = i < N - 1 ? __shfl_sync(~0u, r.f[i < N - 1 ? i + 1 : i].x, 0) : r.fn;
        const uint32_t nxt = lane == 31 ? b : a;
        const uint32_t ea = fb + (2056 - 8 * vi) * 2;
        sts128(ea, make_uint4(__byte_perm(x.w, 0, 0x1032), __byte_perm(x.z, 0, 0x1032), __byte_perm(x.y, 0, 0x1032), __byte_perm(x.x, 0, 0x1032)));
        sts128(ea + FCP, make_uint4(__byte_perm(nxt, x.w, 0x7610), __byte_perm(x.w, x.z, 0x7610), __byte_perm(x.z, x.y, 0x7610), __byte_perm(x.y, x.x, 0x7610)));
    }
}
template <int NW> __device__ __forceinline__ void conv_mma(int ch0, uint32_t d, uint32_t zero) {
    using namespace ck;
    constexpr int N = 16 / NW;
    const int w = threadIdx.x >> 5, lane = threadIdx.x & 31, ch = w / NW, e = w % NW, g = lane >> 2, t = lane & 3;
    float acc[N][4] = {};
    uint32_t fa = At<NW>::F + ch * FCH + ((g & 1) ? (2063 - g + 2 * t) * 2 : FCP + (2064 - g + 2 * t) * 2);
    uint32_t ua = At<NW>::U + ch * UCH + ((lane >> 3) & 1) * UPL + (24 + (e - NW) * 8 + (lane >> 4) * 8 + (lane & 7)) * 16;
    uint32_t Fr[32], A[2][8], yo = (ch0 + ch) * 512 + e * 32 + t * 8 + g;
    const uint32_t t16 = CC ? lane | zero : lane;
    #define LD_U(m0, m1) _Pragma("unroll") for (int m = m0; m < m1; m++) ldsm4(Fr[4 * m], Fr[4 * m + 1], Fr[4 * m + 2], Fr[4 * m + 3], ua + m * 256)
    #define LD_F(b, o, p) _Pragma("unroll") for (int i = 0; i < 2; i++) { const uint32_t x_ = fa - (o) * 32 - (i ? 15 - (p) : (p)) * 256; \
        A[b][4 * i] = lds32(x_); A[b][4 * i + 1] = lds32(x_ - 16); A[b][4 * i + 2] = lds32(x_ + 16); }
    #define ROW(a, q, j0, j1) _Pragma("unroll") for (int j = j0; j < j1; j++) mmaq(acc[j], a, Fr[2 * (NW * j + NW - 1 - (q))], Fr[2 * (NW * j + NW - 1 - (q)) + 1])
    LD_U(0, 8);
    LD_F(0, 0, 0);
    {
        const uint32_t da = (g >> 1) == t ? d << ((g & 1) * 16) : 0, D[4] = {da, zero, zero >> 1, da ^ zero};
        ROW(D, 0, 0, N);
    }
    #pragma unroll 1
    for (int r = 0; r < 8; r++) {
        ua -= 16;
        #pragma unroll
        for (int p = 0; p < 8; p++) {
            uint32_t* const a = A[p & 1];
            a[3] = a[0] ^ zero; a[7] = a[4] ^ zero;
            LD_F(~p & 1, p == 7, (p + 1) & 7);
            if (p >= 2 && !(p & 1)) { LD_U(8 - p / 2, 9 - p / 2); }
            ROW(a, p, p / NW, 3);
            CUT(yo);
            ROW(a + 4, 15 - p, (15 - p) / NW, N);
            CUT(yo);
            ROW(a, p, (p / NW > 3 ? p / NW : 3), N);
            CUT(yo);
        }
        LD_U(0, 5);
        fa -= 32;
    }
    uint2* y = (uint2*)g_Y + yo;
    #pragma unroll
    for (int j = 0; j < N; j++) {
        const uint32_t p0 = pack2(acc[j][0], acc[j][2]), p1 = pack2(acc[j][1], acc[j][3]), x = __shfl_xor_sync(~0u, (g & 1) ? p0 : p1, 4);
        const uint32_t lo = (g & 1) ? x : p0, hi = (g & 1) ? p1 : x;
        y[j * 32 * NW] = make_uint2(__byte_perm(lo, hi, 0x5410), __byte_perm(lo, hi, 0x7632));
    }
}
__device__ __noinline__ void spare(const CUtensorMap* tmK, const ConvIn in, int i, uint32_t zero) {
    const int w = __shfl_sync(~0u, threadIdx.x >> 5, 0);
    ConvRaw<1> raw;
    #pragma unroll 1
    for (int grp = NCTA / 2 - 4 + i, n = 0; grp < NSP; grp += 4, n++) {
        if (n) { mbar_wait(mk::MB_C, n & 1); kv_build<1>(raw, grp * 8); conv_filter<1>(raw); }
        const uint32_t d = raw.d;
        if (w == 0 && elect()) mbar_expect(mk::MB_C, 65536);
        asm volatile("fence.proxy.async.shared::cta;" ::: "memory");
        __syncthreads();
        if (grp + 4 < NSP) {
            if (elect()) for (int j = 0; j < 2; j++) tma3d(ck::At<1>::K + j * 32768 + w * 4096, tmK + j, grp * 8 + 32, 0, w, mk::MB_C);
            __syncwarp();
            conv_load<1>(raw, in, grp * 8 + 32);
        }
        if (n) conv_mma<1>(grp * 8, d, zero);
        __syncthreads();
    }
}

__device__ __forceinline__ uint32_t round_trip(char* a, int n) {
    uint32_t best = 0x7FFFu;
    #pragma unroll 1
    for (int i = 0; i < n; i++) {
        uint32_t v; const uint32_t t0 = clk();
        asm volatile("atom.relaxed.gpu.global.exch.b32 %0, [%1], %2;" : "=r"(v) : "l"(a), "r"(i) : "memory");
        if (v == 0x7FC1A5A5u) g_err = 2;
        best = min(best, clk() - t0);
    }
    return (__popc((uint32_t)(uintptr_t)a & HOME_BITS) & 1) ? best << 16 | 0x7FFFu : best | 0x7FFF0000u;
}
__device__ __forceinline__ int place(int by_sm) {
    uint32_t sm = blockIdx.x;
    if (by_sm) asm volatile("mov.u32 %0, %%smid;" : "=r"(sm));
    const uint32_t g = sm < 64 ? (sm & 15) >> 1 : 1 + (sm - 64) % 14 / 2, j = sm < 64 ? sm >> 4 : 4 + (sm - 64) / 14;
    return sm < 120 ? (g ? g * 16 - 8 : 0) + j * 2 + (sm & 1) : sm;
}
__device__ __forceinline__ void publish(char* rb, int p) {
    const int t = threadIdx.x, i = p * 4 + (t >> 6);
    char* line = rb + RB_P + (i & 31) * 128 + (i >> 5) * 8192 + (t & 32) * 128;
    if ((t & 31) < 2) st_g128(line + (t & 1) * 16, 0, 0, 0, 0);
    __syncwarp();
    if (!(t & 31)) sts32(mk::SUM + (t >> 3), round_trip(line, NPR));
    __syncthreads();
    if (t == 32) {
        const uint4 x = lds128(mk::SUM), y = lds128(mk::SUM + 16);
        st_g32(g_cls + p, 0x80000000u | __vminu2(__vminu2(__vminu2(x.x, x.y), __vminu2(x.z, x.w)), __vminu2(__vminu2(y.x, y.y), __vminu2(y.z, y.w))));
    }
}
__device__ __forceinline__ uint32_t survey(uint32_t& x) {
    const int lane = threadIdx.x & 31;
    uint32_t a[4], b[2];
    int n = 0;
    do { ld_g128(a, g_cls + lane * 4); ld_g64(b, g_cls + 120 + lane % 6 * 2); } while (__any_sync(~0u, !((a[0] & a[1] & a[2] & a[3] & b[0] & b[1]) >> 31)) && ++n < SPIN_LIMIT);
    const uint32_t m = __vminu2(__vminu2(a[0], a[1]), __vminu2(a[2], a[3])), e = __vminu2(b[0], b[1]);
    const uint32_t M = __ballot_sync(~0u, (m >> 16 & 0x7FFF) < (m & 0xFFFF)) & 0x3FFFFFFF, E = __ballot_sync(~0u, (e >> 16 & 0x7FFF) < (e & 0xFFFF)) & 63;
    const int x0 = min(max(max(__popc(M) - 14, 2 - __popc(E) / 2), 0), min(2, (6 - __popc(E)) / 2));
    x = E | x0 << 8;
    return M | (x0 < 1) << 30 | (x0 < 2) << 31;
}
__device__ __forceinline__ int role(int p, uint32_t x) {
    const int i = (p - 120) >> 1, x0 = x >> 8, side = x >> i & 1, r = __popc((side ? x : ~x) & ((1 << i) - 1)), e0 = 6 - __popc(x & 63);
    const int pair = !side ? (r < 2 * x0 ? r : 4 + r - 2 * x0) : (r < 4 - 2 * x0 ? 2 * x0 + r : e0 + r);
    return 120 + 2 * pair + (p & 1);
}
__device__ __forceinline__ void tma_prefetch(const CUtensorMap* m, int c0, int c1) {
    asm volatile("cp.async.bulk.prefetch.tensor.2d.L2.global [%0, {%1, %2}];" :: "l"(m), "r"(c0), "r"(c1) : "memory");
}

struct KVMaps { CUtensorMap m[2]; };
__global__ void __launch_bounds__(256, 1)
main_kernel(const __grid_constant__ CUtensorMap tmWq, const __grid_constant__ CUtensorMap tmWk, const __grid_constant__ CUtensorMap tmWv,
            const __grid_constant__ CUtensorMap tmWo, const __grid_constant__ CUtensorMap tmX,
            const __grid_constant__ KVMaps tmK, const bf16* __restrict__ mem0,
            const __grid_constant__ ConvIn in, const __grid_constant__ MainParams prm) {
    using namespace mk;
    extern __shared__ __align__(1024) uint8_t smem_raw[];
    if (smem_u32(smem_raw) != SB) __trap();
    TL(0); TL(2);
    const int tid0 = threadIdx.x, w8 = __shfl_sync(~0u, tid0 >> 5, 0), wg = w8 >> 2;
    const int p = __shfl_sync(~0u, place(prm.by_sm), 0);
    if (w8 == 0 && elect()) {
        for (int i = 0; i < 9; i++) mbar_init(BAR + i * 8, 1);
        asm volatile("fence.mbarrier_init.release.cluster;" ::: "memory");
        asm volatile("fence.proxy.async.shared::cta;" ::: "memory");
        sts32(SUM + 256, 0); sts32(SUM + 268, 0); mbar_arrive(MB_B);
    }
    if (tid0 >= 252) asm volatile("prefetch.tensormap [%0];" :: "l"(tid0 == 252 ? &tmWq : tid0 == 253 ? &tmWk : tmK.m + (tid0 & 1)) : "memory");
    __syncwarp();
    publish(prm.rb, p);
    TLX(16);
    int c = p;
    if (p >= 120) { uint32_t x; survey(x); c = role(p, x); }
    TLX(17);
    if (w8 == 0 && elect()) {
        strip_request<2>(tmK.m, p >> 1);
        if (c < 128) {
            mbar_expect(MB_WQ, 65536); mbar_expect(MB_WK, 65536);
            for (int i = 0; i < 2; i++) { tma2d(WO + i * 32768, &tmWq, (c >> 1) * 64, (c & 1) * 512 + i * 256, MB_WQ); tma2d(WV + i * 32768, &tmWk, (c >> 1) * 64, (c & 1) * 512 + i * 256, MB_WK); }
        }
    }
    __syncwarp();
    uint32_t m0[8];
    {
        ConvRaw<2> raw;
        conv_load<2>(raw, in, p * 4);
        #pragma unroll
        for (int i = 0; i < 8; i++) m0[i] = __ldg((const uint32_t*)(mem0 + i * DM + (c & 1) * 512) + tid0);
        if (tid0 < 16 && p < 128) g_gate[p * 16 + tid0] = -1.f;
        if (!c_xd[w8 * 12 + (tid0 & 8)]) __trap();
        asm volatile("griddepcontrol.launch_dependents;" ::: "memory");
        mbar_wait(MB_C, 0);
        TLX(22);
        kv_build<2>(raw, p * 4);
        __syncthreads();
        TLX(14);
        if (w8 == 0 && c < 128 && elect()) {
            mbar_expect(MB_X, 32768); tma3d(XT, &tmX, 0, 32, (c & 1) * 8, MB_X);
            for (int i = 0; i < 4; i++) tma_prefetch(&tmWo, (c & 3) * 256 + i * 64, (c >> 2) * DH);
            for (int i = 0; i < 2; i++) tma_prefetch(&tmWv, (c >> 1) * 64, (c & 1) * 512 + i * 256);
        }
        __syncwarp();
        conv_filter<2>(raw);
        __syncthreads();
        TL(9);
        conv_mma<2>(p * 4, raw.d, prm.zero);
    }
    if (c >= 128) { spare(tmK.m, in, c - 128, prm.zero); TLX(18); return; }
    const int kap = c & 1;
    TL(1);
    asm volatile("fence.proxy.async.shared::cta;" ::: "memory");
    __syncthreads();
    if (w8 == 0 && elect()) { mbar_expect(MB_KV, 32768); tma3d(TK, &tmX, 0, 0, kap * 8, MB_KV); }
    #pragma unroll
    for (int i = 0; i < 2; i++) {
        const uint32_t e = i ? 0x7632 : 0x5410;
        sts128(MEM + tid0 * 32 + i * 16, make_uint4(__byte_perm(m0[0], m0[1], e), __byte_perm(m0[2], m0[3], e), __byte_perm(m0[4], m0[5], e), __byte_perm(m0[6], m0[7], e)));
    }
    uint32_t W[128], T[64];
    mbar_wait(wg ? MB_WK : MB_WQ, 0);
    TLX(19);
    load_tile<0, 32>(tile_off(tid0 & 31, 2 * (w8 & 3)) + (wg ? WV : WO), W);
    __syncthreads();
    if (w8 == 0 && elect()) {
        mbar_expect(MB_WO, 65536);
        for (int i = 0; i < 4; i++) tma2d(WO + i * 16384, &tmWo, (c & 3) * 256 + i * 64, (c >> 2) * DH, MB_WO);
        mbar_expect(MB_WV, 65536); tma2d(WV, &tmWv, (c >> 1) * 64, kap * 512, MB_WV); tma2d(WV + 32768, &tmWv, (c >> 1) * 64, kap * 512 + 256, MB_WV);
    }
    uint32_t t16 = tid0 * 16, pa, pb;
    {
        const int lane = tid0 & 31, w = w8 & 3, g = lane >> 2, t = lane & 3;
        auto vec = [](int hf, int gg, int ch) { return hf * 512 + (gg >> 1) * 128 + (gg & 1) * 64 + ((ch ^ (gg >> 1) ^ (hf << 1)) << 4); };
        const int kg = ((lane >> 3) & 1) * 4 + ((lane & 7) >> 1);
        pa = wg ? w * 1024 + vec((lane >> 3) & 1, lane & 7, lane >> 4)
                : ((lane >> 4) * 4096 + w * 1024 + vec(lane & 1, kg, 2 * (w & 1))) | ((lane & 8) * 256 + w * 256 + (lane & 1) * 128 + ((((lane >> 4) ^ (lane & 1)) * 4 + ((lane & 7) >> 1)) << 4)) << 16;
        pb = (wg ? w * 1024 + vec(0, g, t) : t * 4096 + w * 256 + g * 16) | (w * 256 + t * 64 + (g & 3) * 8 + (g >> 2) * 4) << 16;
    }
    int budget = SPIN_LIMIT;
    const uint32_t ps = pb & 0xFFFF;
    #define ST_TOK(o) do { TAGM(); pack_tag(acc, u, 1, tm); st_if(true, tok_dst(c, seg, wg) + ((o) + ps), u); st_if(true, tok_dst(c, seg, wg) + ((o) + (ps ^ HI8)), u + 4); } while (0)
    #pragma unroll 1
    for (int seg = 1; seg >= 0; seg--) {
        float acc[16];
        uint32_t u[8];
        mbar_wait(seg ? MB_X : MB_KV, 0);
        wg_run<0, 32>(acc, W, c_xd + (seg ? 0 : 64));
        wg_wait<0>();
        ST_TOK(0);
    }
    {
        mbar_wait(MB_WO, 0);
        TLX(20);
        const int lane = tid0 & 31;
        const uint32_t a = (tid0 >> 6) * 16384 + tile_off(lane, (w8 & 1) * 4) + WO;
        #pragma unroll
        for (int i = 0; i < 16; i++) ldsm4t(T[4 * i], T[4 * i + 1], T[4 * i + 2], T[4 * i + 3], ((i & 2) ? a ^ 32 : a) + ((i >> 2) + 4 * (i & 1)) * 2048);
        __syncthreads();
        const uint32_t d = WO + w8 * 512 + ((lane >> 3) * 4 + (lane & 3)) * 16 + ((lane >> 2) & 1) * 4;
        #pragma unroll
        for (int i = 0; i < 64; i++) sts32(d + (i >> 2) * 4096 + (i & 1) * 256 + (i & 2) * 4, T[i]);
    }
    mbar_wait(MB_WV, 0);
    TLX(21);
    load_tile<0, 16>(tile_off(tid0 & 31, 2 * (w8 & 3)) + wg * 32768 + WV, T);
    #pragma unroll 1
    for (int seg = 0; seg < 2; seg++) {
        float acc[16];
        uint32_t u[8];
        wg_run<0, 16>(acc, T, c_xd + (seg ? 0 : 64) + wg * 16);
        wg_wait<0>();
        const uint32_t x = SC + seg * 4096 + (t16 & 2047);
        if (!wg) { qk_pack(acc, u); sts128(x, make_uint4(u[0], u[1], u[2], u[3])); sts128(x + 2048, make_uint4(u[4], u[5], u[6], u[7])); }
        __syncthreads();
        if (wg) { lds128u(u, x); lds128u(u + 4, x + 2048); acc_add(acc, u); ST_TOK(16384); }
    }
    if (w8 == 1) { bulk_expect(MB_X, 32768); load_x(&tmX, c, 2, XT); }
    uint32_t u_rs, u_rl, u_bs, u_bl;
    const uint32_t rbhi = (uint32_t)((uintptr_t)prm.rb >> 32);
    {
        const int lane = tid0 & 31, h = c >> 2, j = c & 3;
        uint32_t cl;
        const uint32_t M = survey(cl), below = (1u << h) - 1;
        const int pos = ((M >> h) & 1) ? 32 - __popc(M) + __popc(M & below) : __popc(~M & below), G = pos >> 4, rk = pos & 15;
        auto half = [&](uint32_t off) { return (uint32_t)(uintptr_t)prm.rb + off + ((__popc(off & HOME_BITS) ^ G) & 1) * 4096; };
        auto rpair = [&](int m) { return RB_R + (j << 16) + ((m & 1) << 13) + (((m >> 1) & 3) << 14) + ((m >> 3) << 18); };
        u_rs = (half(rpair(2 * w8)) ^ (G << 12)) + h * 128 + (h & 7) * 16;
        u_rl = half(rpair(rk));
        u_bs = (uint32_t)(uintptr_t)prm.rb + RB_B + ((j & 1) << 13) + ((j >> 1) << 16) + rk * 256 + G * 128 + (w8 & 3) * 32;
        u_bl = half(RB_B + (kap << 16));
        if (w8 == 0) {
            const char* v0 = kv_src(c, 0) + 16384 + lane * 128 + (lane & 3) * 4;
            do cl = ld_g32(v0) & ld_g32(v0 + 4096) & ld_g32(v0 + 8192) & ld_g32(v0 + 12288); while (__any_sync(~0u, !(cl & 1)) && --budget > 0);
            get_kv(c, 0);
        }
    }
    mbar_wait(MB_KV, 1);
    if (w8 < 3) while (kv_stale(w8, t16 & 0x1F0, 1) && --budget > 0) refetch_kv(c, 0, w8, t16 & 0x1F0);
    asm volatile("fence.proxy.async.shared::cta;" ::: "memory");
    TLX(7);
    __syncwarp();
    const Ctx cx = {u_rs, u_rl, u_bs, u_bl, (uint32_t)(uintptr_t)prm.rb, rbhi, w8, c};
    if (wg) steps<1>(W, T, t16, pa, pb, cx, &tmX, prm); else steps<0>(W, T, t16, pa, pb, cx, &tmX, prm);
    TLX(3);
}

namespace ok {
constexpr int STAGES = 4;
constexpr uint32_t STG = 49152, TOTAL = STAGES * STG + 32768 + 256;
}
#define R8(o) F4(d, o), F4(d, o + 4)
__device__ __forceinline__ void wgmma_n256_ss_tt(float* d, uint64_t da, uint64_t db, int accum) {
    asm volatile("{.reg .pred p; setp.ne.b32 p, %130, 0;\n"
        "wgmma.mma_async.sync.aligned.m64n256k16.f32.bf16.bf16 {%0,%1,%2,%3,%4,%5,%6,%7,%8,%9,%10,%11,%12,%13,%14,%15,"
        "%16,%17,%18,%19,%20,%21,%22,%23,%24,%25,%26,%27,%28,%29,%30,%31,%32,%33,%34,%35,%36,%37,%38,%39,%40,%41,%42,%43,%44,%45,%46,%47,"
        "%48,%49,%50,%51,%52,%53,%54,%55,%56,%57,%58,%59,%60,%61,%62,%63,%64,%65,%66,%67,%68,%69,%70,%71,%72,%73,%74,%75,%76,%77,%78,%79,"
        "%80,%81,%82,%83,%84,%85,%86,%87,%88,%89,%90,%91,%92,%93,%94,%95,%96,%97,%98,%99,%100,%101,%102,%103,%104,%105,%106,%107,%108,%109,%110,%111,"
        "%112,%113,%114,%115,%116,%117,%118,%119,%120,%121,%122,%123,%124,%125,%126,%127}, %128, %129, p, 1, 1, 1, 1;}"
        : R8(0), R8(8), R8(16), R8(24), R8(32), R8(40), R8(48), R8(56), R8(64), R8(72), R8(80), R8(88), R8(96), R8(104), R8(112), R8(120)
        : "l"(da), "l"(db), "r"(accum));
}
#undef R8
__global__ void __cluster_dims__(2, 1, 1) __launch_bounds__(320, 1)
out_kernel(const __grid_constant__ CUtensorMap tmO, const __grid_constant__ CUtensorMap tmWo, const __grid_constant__ CUtensorMap tmA,
           const __grid_constant__ CUtensorMap tmOut, const __grid_constant__ CUtensorMap tmQ, const bf16* __restrict__ q, const bf16* __restrict__ gate_w) {
    using namespace ok;
    extern __shared__ __align__(1024) uint8_t smem_raw[];
    const uint32_t SB = smem_u32(smem_raw), AT = SB + STAGES * STG, BAR = AT + 32768;
    if (SB & 1023) __trap();
    const int tid = threadIdx.x, w = tid >> 5, lane = tid & 31;
    const int rank = blockIdx.x & 1, mt = blockIdx.x >> 3, nt = (blockIdx.x >> 1) & 3;
    const uint32_t full = BAR, empty = BAR + 64, afull = BAR + 128;
    if (tid == 0) {
        for (int i = 0; i < STAGES; i++) { mbar_init(full + i * 8, 1); mbar_init(empty + i * 8, 8); }
        mbar_init(afull, 2);
        asm volatile("fence.mbarrier_init.release.cluster;" ::: "memory");
    }
    __syncthreads();
    asm volatile("griddepcontrol.wait;" ::: "memory");
    if (blockIdx.x == 0 && tid < 160) g_cls[tid] = 0;
    TL(4);
    if (w >= 8) {
        if (w == 9) {
            uint4 gw[4];
            #pragma unroll
            for (int i = 0; i < 4; i++) gw[i] = __ldg((const uint4*)gate_w + lane + 32 * i);
            #pragma unroll 2
            for (int row = blockIdx.x * 16; row < blockIdx.x * 16 + 16; row++) {
                float a = 0.f;
                #pragma unroll
                for (int i = 0; i < 4; i++) {
                    const uint4 x = __ldg((const uint4*)(q + (size_t)row * DM) + lane + 32 * i);
                    #pragma unroll
                    for (int j = 0; j < 4; j++) { const uint32_t gg = ((const uint32_t*)&gw[i])[j], u = ((const uint32_t*)&x)[j]; a = fmaf(bflo(u), bflo(gg), fmaf(bfhi(u), bfhi(gg), a)); }
                }
                #pragma unroll
                for (int o = 16; o; o >>= 1) a += __shfl_xor_sync(~0u, a, o);
                if (lane == 0) st_g32(g_gate + row, __float_as_uint(1.f / (1.f + __expf(-a))));
            }
        } else if (lane == 0) {
            int st = 0, ph = 1;
            for (int kb = 0; kb < 32; kb++) {
                if (kb >= STAGES) mbar_wait(empty + st * 8, ph);
                mbar_expect(full + st * 8, STG);
                tma3d(SB + st * STG, &tmO, 0, (rank * 32 + kb) * 2, mt * 16, full + st * 8);
                tma3d(SB + st * STG + 16384, &tmWo, 0, (rank * 32 + kb) * 64, nt * 4, full + st * 8);
                if (kb == STAGES - 1) { mbar_expect(afull, 32768); tma3d(AT, &tmA, 0, (nt * 2 + rank) * 128, mt * 2, afull); }
                if (++st == STAGES) { st = 0; ph ^= 1; }
            }
            mbar_wait(empty, ph);
            mbar_expect(afull, 32768);
            for (int hf = 0; hf < 2; hf++)
                asm volatile("cp.async.bulk.tensor.5d.shared::cluster.global.mbarrier::complete_tx::bytes [%0], [%1, {%3, %4, %4, %4, %5}], [%2];"
                    :: "r"(SB + hf * 16384), "l"(&tmQ), "r"(afull), "r"(nt * 256 + rank * 128 + hf * 64), "r"(0), "r"(mt * 4) : "memory");
        }
        __syncwarp();
        asm volatile("barrier.cluster.arrive.aligned; barrier.cluster.wait.aligned;" ::: "memory");
        asm volatile("barrier.cluster.arrive.aligned; barrier.cluster.wait.aligned;" ::: "memory");
    } else {
        const int wg = w >> 2, g = lane >> 2;
        float acc[128];
        const int tok0 = 32 * (4 * mt + (w >> 1)) + 8 * (g >> 1) + 4 * (w & 1) + (g & 1);
        int st = 0, ph = 0, pst = 0;
        #pragma unroll 1
        for (int kb = 0; kb < 32; kb++) {
            mbar_wait(full + st * 8, ph);
            const uint64_t da = mkdesc(SB + st * STG + wg * 8192, 128, 1024, 0), db = mkdesc(SB + st * STG + 16384, 8192, 1024, 1);
            wg_fence();
            #pragma unroll
            for (int ks = 0; ks < 4; ks++) wgmma_n256_ss_tt(acc, da + ks * 16, db + ks * 128, (kb | ks) != 0);
            wg_commit();
            wg_wait<1>();
            if (kb > 0 && lane == 0) mbar_arrive(empty + pst * 8);
            pst = st;
            if (++st == STAGES) { st = 0; ph ^= 1; }
        }
        float g0, g1;
        int n = 0;
        do { g0 = __uint_as_float(ld_g32(g_gate + tok0)); g1 = __uint_as_float(ld_g32(g_gate + tok0 + 2)); } while ((g0 < 0.f || g1 < 0.f) && ++n < SPIN_LIMIT);
        __syncwarp();
        wg_wait<0>();
        TLX(12);
        asm volatile("barrier.cluster.arrive.aligned; barrier.cluster.wait.aligned;" ::: "memory");
        uint32_t peer;
        asm volatile("mapa.shared::cluster.u32 %0, %1, %2;" : "=r"(peer) : "r"(SB + 65536 + tid * 16), "r"(rank ^ 1));
        #define SND(e) pack2(rank ? acc[8 * i + (e)] : acc[64 + 8 * i + (e)], rank ? acc[8 * i + (e) + 1] : acc[65 + 8 * i + (e)])
        #pragma unroll
        for (int i = 0; i < 8; i++)
            asm volatile("st.shared::cluster.v4.b32 [%0], {%1,%2,%3,%4};" :: "r"(peer + i * 4096), "r"(SND(0)), "r"(SND(2)), "r"(SND(4)), "r"(SND(6)) : "memory");
        #undef SND
        asm volatile("barrier.cluster.arrive.aligned; barrier.cluster.wait.aligned;" ::: "memory");
        mbar_wait(afull, 0);
        const float h0 = 1.f - g0, h1 = 1.f - g1;
        const uint32_t la = AT + wg * 16384 + ((lane >> 4) * 8 + (lane & 7)) * 128 + ((((w & 3) * 2 + ((lane >> 3) & 1)) ^ (lane & 7)) << 4);
        const uint32_t ra = SB + (w * 16 + (lane & 15)) * 128;
        #pragma unroll
        for (int i = 0; i < 8; i++) {
            const uint32_t a = ra + (i >> 2) * 16384 + ((((i & 3) * 2 + (lane >> 4)) ^ (lane & 7)) << 4);
            uint32_t r0, r1, r2, r3, x0, x1, x2, x3;
            ldsm4t(r0, r1, r2, r3, la + i * 2048);
            ldsm4(x0, x1, x2, x3, a);
            const uint4 u = lds128(SB + 65536 + tid * 16 + i * 4096);
            float p[8];
            #pragma unroll
            for (int e = 0; e < 8; e++) { const uint32_t x = ((const uint32_t*)&u)[e >> 1]; p[e] = (rank ? acc[64 + 8 * i + e] : acc[8 * i + e]) + ((e & 1) ? bfhi(x) : bflo(x)); }
            #define MIX(g, h, r, x, e) pack2(fmaf(g * bflo(x), bflo(r), h * p[e]), fmaf(g * bfhi(x), bfhi(r), h * p[e + 1]))
            stsm4(a, MIX(g0, h0, r0, x0, 0), MIX(g1, h1, r1, x1, 2), MIX(g0, h0, r2, x2, 4), MIX(g1, h1, r3, x3, 6));
        }
        asm volatile("fence.proxy.async.shared::cta;" ::: "memory");
        bsync<1, 256>();
        if (tid == 0) {
            for (int hf = 0; hf < 2; hf++)
                asm volatile("cp.async.bulk.tensor.5d.global.shared::cta.bulk_group [%0, {%2, %3, %3, %3, %4}], [%1];"
                    :: "l"(&tmOut), "r"(SB + hf * 16384), "r"(nt * 256 + rank * 128 + hf * 64), "r"(0), "r"(mt * 4) : "memory");
            asm volatile("cp.async.bulk.commit_group;" ::: "memory");
            asm volatile("cp.async.bulk.wait_group 0;" ::: "memory");
        }
        TL(5);
    }
}

typedef CUresult (*EncodeFn)(CUtensorMap*, CUtensorMapDataType, cuuint32_t, void*, const cuuint64_t*, const cuuint64_t*, const cuuint32_t*,
                             const cuuint32_t*, CUtensorMapInterleave, CUtensorMapSwizzle, CUtensorMapL2promotion, CUtensorMapFloatOOBfill);
static void enc(EncodeFn fn, CUtensorMap* m, void* base, int rank, const cuuint64_t* dims, const cuuint64_t* strides, const cuuint32_t* box, CUtensorMapSwizzle sw) {
    cuuint32_t es[5] = {1, 1, 1, 1, 1};
    fn(m, CU_TENSOR_MAP_DATA_TYPE_BFLOAT16, rank, base, dims, strides, box, es, CU_TENSOR_MAP_INTERLEAVE_NONE, sw,
       CU_TENSOR_MAP_L2_PROMOTION_L2_128B, CU_TENSOR_MAP_FLOAT_OOB_FILL_NONE);
}
static MainParams h_prm = {{768, 576, 512, 0, 0, 0, 0, 0, 0, 0, 0, 0}, 0, 1, nullptr, nullptr};

extern "C" void kernel_launch(void* const* d_in, const int* in_sizes, int n_in, void* d_out, int out_size) {
    const bf16* q = (const bf16*)d_in[0];
    const bf16* shift_k = (const bf16*)d_in[3];
    const bf16* ssm_k = (const bf16*)d_in[4];
    const bf16* ssm_D = (const bf16*)d_in[5];
    const bf16* mem0 = (const bf16*)d_in[7];
    const bf16* gate_w = (const bf16*)d_in[13];

    static EncodeFn fn = nullptr;
    static void* pO = nullptr;
    static void* pA = nullptr;
    if (!fn) {
        cudaDriverEntryPointQueryResult qr;
        cudaGetDriverEntryPoint("cuTensorMapEncodeTiled", (void**)&fn, cudaEnableDefault, &qr);
        cudaGetSymbolAddress(&pO, g_O);
        cudaGetSymbolAddress(&pA, g_Y);
        void* pRB; cudaGetSymbolAddress(&pRB, g_RB);
        h_prm.rb = (char*)(((uintptr_t)pRB + (4u << 20) - 1) & ~(uintptr_t)((4u << 20) - 1));
        int dev, sms; cudaGetDevice(&dev); cudaDeviceGetAttribute(&sms, cudaDevAttrMultiProcessorCount, dev);
        h_prm.by_sm = sms == NCTA;
        cudaFuncSetAttribute(main_kernel, cudaFuncAttributeMaxDynamicSharedMemorySize, mk::TOTAL);
        cudaFuncSetAttribute(out_kernel, cudaFuncAttributeMaxDynamicSharedMemorySize, ok::TOTAL);
    }
    CUtensorMap mWq, mWk, mWv, mWo, mX, mO, mWo2, mA, mOut, mQ;
    {
        cuuint64_t d[2] = {4096, 1024}, s[1] = {8192}; cuuint32_t b[2] = {64, 256};
        enc(fn, &mWq, d_in[8], 2, d, s, b, CU_TENSOR_MAP_SWIZZLE_128B);
        enc(fn, &mWk, d_in[9], 2, d, s, b, CU_TENSOR_MAP_SWIZZLE_128B);
        enc(fn, &mWv, d_in[10], 2, d, s, b, CU_TENSOR_MAP_SWIZZLE_128B);
    }
    {
        cuuint64_t d[2] = {1024, 4096}, s[1] = {2048}; cuuint32_t b[2] = {64, 128};
        enc(fn, &mWo, d_in[11], 2, d, s, b, CU_TENSOR_MAP_SWIZZLE_128B);
        cuuint64_t d2[3] = {64, 4096, 16}, s2[2] = {2048, 128}; cuuint32_t b2[3] = {64, 64, 4};
        enc(fn, &mWo2, d_in[11], 3, d2, s2, b2, CU_TENSOR_MAP_SWIZZLE_128B);
    }
    {
        cuuint64_t d[3] = {64, 2048, 16}, s[2] = {2048, 128}; cuuint32_t b[3] = {64, 32, 8};
        enc(fn, &mX, d_in[0], 3, d, s, b, CU_TENSOR_MAP_SWIZZLE_128B);
    }
    {
        cuuint64_t d[3] = {256, 128, 256}, s[2] = {512, 65536}; cuuint32_t b[3] = {256, 2, 16};
        enc(fn, &mO, pO, 3, d, s, b, CU_TENSOR_MAP_SWIZZLE_NONE);
    }
    {
        cuuint64_t d[5] = {1024, 2, 4, 4, 64}, s[4] = {2048, 16384, 4096, 65536}; cuuint32_t b[5] = {64, 2, 4, 4, 4};
        cuuint64_t da[3] = {64, 1024, 32}, sa[2] = {4096, 128}; cuuint32_t ba[3] = {64, 128, 2};
        enc(fn, &mA, pA, 3, da, sa, ba, CU_TENSOR_MAP_SWIZZLE_128B);
        enc(fn, &mQ, d_in[0], 5, d, s, b, CU_TENSOR_MAP_SWIZZLE_128B);
        enc(fn, &mOut, d_out, 5, d, s, b, CU_TENSOR_MAP_SWIZZLE_128B);
    }
    KVMaps mK;
    {
        cuuint64_t d[3] = {1024, 256, 8}, s[2] = {16384, 2048}; cuuint32_t b[3] = {8, 256, 1};
        for (int i = 0; i < 2; i++) enc(fn, &mK.m[i], d_in[1 + i], 3, d, s, b, CU_TENSOR_MAP_SWIZZLE_NONE);
    }
    cudaStream_t st = cudaStreamPerThread;
    cudaLaunchAttribute at[1];
    at[0].id = cudaLaunchAttributeProgrammaticStreamSerialization;
    at[0].val.programmaticStreamSerializationAllowed = 1;
    cudaLaunchConfig_t cfg = {};
    cfg.stream = st; cfg.attrs = at;
    cfg.gridDim = dim3(NCTA); cfg.blockDim = dim3(256); cfg.dynamicSmemBytes = mk::TOTAL;
    h_prm.x = (const char*)q;
    const ConvIn cin = {shift_k, ssm_k, ssm_D};
    cudaLaunchKernelEx(&cfg, main_kernel, mWq, mWk, mWv, mWo, mX, mK, mem0, cin, h_prm);
    cfg.numAttrs = PDL;
    cfg.gridDim = dim3(128); cfg.blockDim = dim3(320); cfg.dynamicSmemBytes = ok::TOTAL;
    cudaLaunchKernelEx(&cfg, out_kernel, mO, mWo2, mA, mOut, mQ, q, gate_w);
}
```

```cpp
#include <cuda_runtime.h>
#include <cuda_bf16.h>
#include <cuda.h>
#include <stdint.h>

typedef __nv_bfloat16 bf16;

constexpr int SEQ = 2048, DM = 1024, NH = 32, DH = 128, NSEG = 64;
constexpr int SPIN_LIMIT = 1 << 13, NCTA = 132;
#define NPR 2
#define RF 0
#define CC 1
#define XDL 10
#define NSP 128
#define XPF 2
#define FRONT __forceinline__
#define PDL 1
#define TPF 1

constexpr uint32_t HOME_BITS = 0xB3000;
constexpr uint32_t RB_R = 0;
constexpr uint32_t RB_B = 0x80000;
constexpr uint32_t RB_T = RB_B + 0x4000;
constexpr uint32_t RB_P = RB_B + 0x20000;
constexpr uint32_t RB_X = 2u << 20;
__device__ uint4 g_RB[(8 << 20) / 16];
__device__ uint32_t g_cls[160];
__device__ uint4 g_T[2 * NH * 3072];
__device__ uint4 g_O[NSEG * 4 * 4096];
__device__ uint4 g_Y[SEQ * DM / 8];
__device__ float g_gate[SEQ];
__device__ uint32_t g_err;
#define TL(i) do {} while (0)
#define TLX(i)

__device__ __forceinline__ uint32_t smem_u32(const void* p) { return (uint32_t)__cvta_generic_to_shared(p); }
__device__ __forceinline__ uint32_t clk() { uint32_t c; asm volatile("mov.u32 %0, %%clock;" : "=r"(c) :: "memory"); return c; }
__device__ __forceinline__ void ldsm4(uint32_t& r0, uint32_t& r1, uint32_t& r2, uint32_t& r3, uint32_t a) {
    asm volatile("ldmatrix.sync.aligned.m8n8.x4.shared.b16 {%0,%1,%2,%3}, [%4];" : "=r"(r0), "=r"(r1), "=r"(r2), "=r"(r3) : "r"(a) : "memory");
}
__device__ __forceinline__ void ldsm4t(uint32_t& r0, uint32_t& r1, uint32_t& r2, uint32_t& r3, uint32_t a) {
    asm volatile("ldmatrix.sync.aligned.m8n8.x4.trans.shared.b16 {%0,%1,%2,%3}, [%4];" : "=r"(r0), "=r"(r1), "=r"(r2), "=r"(r3) : "r"(a) : "memory");
}
__device__ __forceinline__ void ldsm2(uint32_t& r0, uint32_t& r1, uint32_t a) {
    asm volatile("ldmatrix.sync.aligned.m8n8.x2.shared.b16 {%0,%1}, [%2];" : "=r"(r0), "=r"(r1) : "r"(a) : "memory");
}
__device__ __forceinline__ void stsm4t(uint32_t a, uint32_t r0, uint32_t r1, uint32_t r2, uint32_t r3) {
    asm volatile("stmatrix.sync.aligned.m8n8.x4.trans.shared.b16 [%0], {%1,%2,%3,%4};" :: "r"(a), "r"(r0), "r"(r1), "r"(r2), "r"(r3) : "memory");
}
__device__ __forceinline__ void mma16(float* c, uint32_t a0, uint32_t a1, uint32_t a2, uint32_t a3, uint32_t b0, uint32_t b1) {
    asm volatile("mma.sync.aligned.m16n8k16.row.col.f32.bf16.bf16.f32 {%0,%1,%2,%3}, {%4,%5,%6,%7}, {%8,%9}, {%0,%1,%2,%3};"
        : "+f"(c[0]), "+f"(c[1]), "+f"(c[2]), "+f"(c[3]) : "r"(a0), "r"(a1), "r"(a2), "r"(a3), "r"(b0), "r"(b1));
}
__device__ __forceinline__ void mma8(float* c, uint32_t a0, uint32_t a1, uint32_t b0) {
    asm volatile("mma.sync.aligned.m16n8k8.row.col.f32.bf16.bf16.f32 {%0,%1,%2,%3}, {%4,%5}, {%6}, {%0,%1,%2,%3};"
        : "+f"(c[0]), "+f"(c[1]), "+f"(c[2]), "+f"(c[3]) : "r"(a0), "r"(a1), "r"(b0));
}
__device__ __forceinline__ uint32_t pack2(float lo, float hi) {
    uint32_t r; asm("cvt.rn.bf16x2.f32 %0, %1, %2;" : "=r"(r) : "f"(hi), "f"(lo)); return r;
}
__device__ __forceinline__ uint32_t hadd2(uint32_t a, uint32_t b) {
    uint32_t r; asm("add.rn.bf16x2 %0, %1, %2;" : "=r"(r) : "r"(a), "r"(b)); return r;
}
__device__ __forceinline__ float bflo(uint32_t w) { return __uint_as_float(w << 16); }
__device__ __forceinline__ float bfhi(uint32_t w) { return __uint_as_float(w & 0xFFFF0000u); }
__device__ __forceinline__ void st_g32(void* p, uint32_t v) { asm volatile("st.relaxed.gpu.global.u32 [%0], %1;" :: "l"(p), "r"(v) : "memory"); }
__device__ __forceinline__ void st_g128(void* p, uint32_t a, uint32_t b, uint32_t c, uint32_t d) {
    asm volatile("st.relaxed.gpu.global.v4.u32 [%0], {%1,%2,%3,%4};" :: "l"(p), "r"(a), "r"(b), "r"(c), "r"(d) : "memory");
}
__device__ __forceinline__ uint4 lds128(uint32_t a) { uint4 v; asm volatile("ld.shared.v4.u32 {%0,%1,%2,%3}, [%4];" : "=r"(v.x), "=r"(v.y), "=r"(v.z), "=r"(v.w) : "r"(a) : "memory"); return v; }
__device__ __forceinline__ void sts128(uint32_t a, uint4 v) { asm volatile("st.shared.v4.u32 [%0], {%1,%2,%3,%4};" :: "r"(a), "r"(v.x), "r"(v.y), "r"(v.z), "r"(v.w) : "memory"); }
__device__ __forceinline__ float2 lds64f(uint32_t a) { float2 v; asm volatile("ld.shared.v2.f32 {%0,%1}, [%2];" : "=f"(v.x), "=f"(v.y) : "r"(a) : "memory"); return v; }
__device__ __forceinline__ void sts64f(uint32_t a, float x, float y) { asm volatile("st.shared.v2.f32 [%0], {%1,%2};" :: "r"(a), "f"(x), "f"(y) : "memory"); }
__device__ __forceinline__ void sts32f(uint32_t a, float x) { asm volatile("st.shared.f32 [%0], %1;" :: "r"(a), "f"(x) : "memory"); }
__device__ __forceinline__ void sts32(uint32_t a, uint32_t x) { asm volatile("st.shared.u32 [%0], %1;" :: "r"(a), "r"(x) : "memory"); }
__device__ __forceinline__ uint32_t lds32(uint32_t a) { uint32_t v; asm volatile("ld.shared.u32 %0, [%1];" : "=r"(v) : "r"(a) : "memory"); return v; }
__device__ __forceinline__ void cpa16(uint32_t dst, const void* src) { asm volatile("cp.async.cg.shared.global [%0], [%1], 16;" :: "r"(dst), "l"(src) : "memory"); }
__device__ __forceinline__ void cpa_commit() { asm volatile("cp.async.commit_group;" ::: "memory"); }
__device__ __forceinline__ void cpa_wait() { asm volatile("cp.async.wait_all;" ::: "memory"); }
template <int ID, int N> __device__ __forceinline__ void bsync() { asm volatile("bar.sync %0, %1;" :: "n"(ID), "n"(N) : "memory"); }
template <int ID, int N> __device__ __forceinline__ void barrive() { asm volatile("bar.arrive %0, %1;" :: "n"(ID), "n"(N) : "memory"); }
template <int ID, int N> __device__ __forceinline__ void bsync_if(bool on) { asm volatile("{ .reg .pred p; setp.ne.b32 p, %2, 0; @p bar.sync %0, %1; }" :: "n"(ID), "n"(N), "r"((int)on) : "memory"); }
template <int ID, int N> __device__ __forceinline__ void barrive_if(bool on) { asm volatile("{ .reg .pred p; setp.ne.b32 p, %2, 0; @p bar.arrive %0, %1; }" :: "n"(ID), "n"(N), "r"((int)on) : "memory"); }
template <int ID> __device__ __forceinline__ uint32_t any128(uint32_t x) {
    uint32_t r; asm volatile("{ .reg .pred p; setp.ne.b32 p, %1, 0; bar.red.or.pred p, %2, 128, p; selp.u32 %0, 1, 0, p; }" : "=r"(r) : "r"(x), "n"(ID) : "memory"); return r;
}
__device__ __forceinline__ bool elect() {
    uint32_t p; asm volatile("{ .reg .pred p; elect.sync _|p, 0xFFFFFFFF; selp.u32 %0, 1, 0, p; }" : "=r"(p)); return p;
}
__device__ __forceinline__ void mbar_init(uint32_t mb, uint32_t n) { asm volatile("mbarrier.init.shared::cta.b64 [%0], %1;" :: "r"(mb), "r"(n) : "memory"); }
__device__ __forceinline__ void mbar_expect(uint32_t mb, uint32_t bytes) { asm volatile("mbarrier.arrive.expect_tx.shared::cta.b64 _, [%0], %1;" :: "r"(mb), "r"(bytes) : "memory"); }
__device__ __forceinline__ void mbar_arrive(uint32_t mb) { asm volatile("mbarrier.arrive.shared::cta.b64 _, [%0];" :: "r"(mb) : "memory"); }
__device__ __forceinline__ void mbar_wait(uint32_t mb, uint32_t ph) {
    asm volatile("{ .reg .pred p; .reg .u32 n; mov.u32 n, 0;\n"
                 "MW_%=: mbarrier.try_wait.parity.shared::cta.b64 p, [%0], %1; add.u32 n, n, 1; setp.lt.and.u32 p, n, %2, !p; @p bra.uni MW_%=; }"
                 :: "r"(mb), "r"(ph), "n"(SPIN_LIMIT) : "memory");
}
__device__ __forceinline__ void tma2d(uint32_t dst, const CUtensorMap* m, int c0, int c1, uint32_t mb) {
    asm volatile("cp.async.bulk.tensor.2d.shared::cluster.global.mbarrier::complete_tx::bytes [%0], [%1, {%3, %4}], [%2];"
        :: "r"(dst), "l"(m), "r"(mb), "r"(c0), "r"(c1) : "memory");
}
__device__ __forceinline__ void tma3d(uint32_t dst, const CUtensorMap* m, int c0, int c1, int c2, uint32_t mb) {
    asm volatile("cp.async.bulk.tensor.3d.shared::cluster.global.mbarrier::complete_tx::bytes [%0], [%1, {%3, %4, %5}], [%2];"
        :: "r"(dst), "l"(m), "r"(mb), "r"(c0), "r"(c1), "r"(c2) : "memory");
}
__device__ __forceinline__ void bulk_ld(uint32_t dst, const void* src, uint32_t bytes, uint32_t mb) {
    asm volatile("cp.async.bulk.shared::cluster.global.mbarrier::complete_tx::bytes [%0], [%1], %2, [%3];" :: "r"(dst), "l"(src), "r"(bytes), "r"(mb) : "memory");
}
__device__ __forceinline__ uint64_t mkdesc(uint32_t addr, uint32_t lbo, uint32_t sbo, uint32_t swz) {
    return (uint64_t)((addr & 0x3FFFF) >> 4) | ((uint64_t)(lbo >> 4) << 16) | ((uint64_t)(sbo >> 4) << 32) | ((uint64_t)swz << 62);
}
__device__ __forceinline__ void wg_fence() { asm volatile("wgmma.fence.sync.aligned;" ::: "memory"); }
__device__ __forceinline__ void wg_commit() { asm volatile("wgmma.commit_group.sync.aligned;" ::: "memory"); }
template <int N> __device__ __forceinline__ void wg_wait() { asm volatile("wgmma.wait_group.sync.aligned %0;" :: "n"(N) : "memory"); }
#define F4(d, o) "+f"(d[o]), "+f"(d[o + 1]), "+f"(d[o + 2]), "+f"(d[o + 3])
__device__ __forceinline__ void wgmma_n32_rs(float* d, const uint32_t* a, uint64_t db, int accum) {
    asm volatile("{.reg .pred p; setp.ne.b32 p, %21, 0;\n"
        "wgmma.mma_async.sync.aligned.m64n32k16.f32.bf16.bf16 {%0,%1,%2,%3,%4,%5,%6,%7,%8,%9,%10,%11,%12,%13,%14,%15}, {%16,%17,%18,%19}, %20, p, 1, 1, 0;}"
        : F4(d, 0), F4(d, 4), F4(d, 8), F4(d, 12) : "r"(a[0]), "r"(a[1]), "r"(a[2]), "r"(a[3]), "l"(db), "r"(accum));
}
__device__ __forceinline__ void wait_until(uint32_t tgt, uint32_t any) {
    asm volatile("{ .reg .pred p, q; .reg .u32 t; .reg .s32 d; mov.u32 t, %0; setp.ne.u32 q, %1, 0xFFFFFFFF;\n"
                 "WU_%=: @q mov.u32 t, %%clock; sub.s32 d, t, %0; setp.lt.s32 p, d, 0; @p bra.uni WU_%=; }" :: "r"(tgt), "r"(any) : "memory");
}

namespace mk {
constexpr uint32_t SB = 1024;
constexpr uint32_t WV = SB, WO = SB + 65536, XT = SB + 131072, TK = SB + 163840  , TQ = TK + 32768, MEM = TQ + 4096,
                   SC = MEM + 8192  , PT = SC + 6144,
                   OB = SC + 8192, SUM = OB + 2048, BAR = SUM + 512, GRP = BAR + 128, PROFB = BAR + 192,
                   TOTAL = PROFB - SB;
static_assert(TOTAL <= 232448, "shared memory");
constexpr uint32_t MB_WQ = BAR, MB_WK = BAR + 8, MB_WV = BAR + 16, MB_WO = BAR + 24, MB_X = BAR + 32, MB_KV = BAR + 40, MB_R = BAR + 48, MB_B = BAR + 56, MB_C = BAR + 64;
constexpr uint32_t XT2 = WV, RS = WV + 32768, VE = RS + 4096;
enum { B_START = 1, B_H0, B_H2, B_H3, B_S1, B_SC, B_SC2, B_S0, B_O, B_O2, B_PT, B_GO, B_VX, B_RD, B_BT };
constexpr uint64_t XD0 = (uint64_t)(XT >> 4) | ((uint64_t)1 << 16) | ((uint64_t)64 << 32) | ((uint64_t)1 << 62);
constexpr uint32_t TSLOT = NH * 49152;
}
struct MainParams { int d[12]; uint32_t zero; int by_sm; char* rb; const char* x; };
#define XD(i) (mk::XD0 - (((i) >> 5) & 1) * ((mk::XT - mk::XT2) >> 4) + ((i) >> 6) * ((mk::TK - mk::XT) >> 4) + (((i) & 31) >> 2) * 256 + ((i) & 3) * 2)
#define XD4(i) XD(i), XD(i + 1), XD(i + 2), XD(i + 3)
#define XD16(i) XD4(i), XD4(i + 4), XD4(i + 8), XD4(i + 12)
__constant__ __align__(256) uint64_t c_xd[96] = {XD16(0), XD16(16), XD16(32), XD16(48), XD16(64), XD16(80)};
#define CUT(r) asm volatile("{ .reg .pred q; setp.eq.u32 q, %1, 0xFFFFFFFF; @q mov.u32 %0, %%clock; }" : "+r"(r) : "r"(t16) : "memory")
__device__ __forceinline__ uint32_t opq(uint32_t x) { asm volatile("" : "+r"(x)); return x; }
__device__ __forceinline__ float opqf(float x) { asm volatile("" : "+f"(x)); return x; }
#define PROF(i)
#define PROFW(i, w)
#define TRC(i, v)
#define RETRY(i, on)
#define P(i) prm.d[i]
#define DELAY(n) do { if (n) { _Pragma("unroll") for (int i_ = 0; i_ < n; i_++) asm volatile("mad.lo.u32 %0, %0, %1, %0;" : "+r"(pb) : "r"(prm.zero)); CUT(pa); } } while (0)

__device__ __forceinline__ uint32_t tagw(uint32_t w, uint32_t tau) { return (w & ~1u) | tau; }
__device__ __forceinline__ uint32_t ld_g32(const void* p) { uint32_t v; asm volatile("ld.relaxed.gpu.global.u32 %0, [%1];" : "=r"(v) : "l"(p) : "memory"); return v; }
__device__ __forceinline__ void ld_g64(uint32_t* v, const void* p) { asm volatile("ld.relaxed.gpu.global.v2.u32 {%0,%1}, [%2];" : "=r"(v[0]), "=r"(v[1]) : "l"(p) : "memory"); }
__device__ __forceinline__ void ld_g128(uint32_t* v, const void* p) {
    asm volatile("ld.relaxed.gpu.global.v4.u32 {%0,%1,%2,%3}, [%4];" : "=r"(v[0]), "=r"(v[1]), "=r"(v[2]), "=r"(v[3]) : "l"(p) : "memory");
}
__device__ __forceinline__ void st_g64(void* p, uint32_t a, uint32_t b) { asm volatile("st.relaxed.gpu.global.v2.u32 [%0], {%1,%2};" :: "l"(p), "r"(a), "r"(b) : "memory"); }
__device__ __forceinline__ void lds128f(float* v, uint32_t a) { asm volatile("ld.shared.v4.f32 {%0,%1,%2,%3}, [%4];" : "=f"(v[0]), "=f"(v[1]), "=f"(v[2]), "=f"(v[3]) : "r"(a) : "memory"); }
__device__ __forceinline__ void sts128f(uint32_t a, float x, float y, float z, float w) { asm volatile("st.shared.v4.f32 [%0], {%1,%2,%3,%4};" :: "r"(a), "f"(x), "f"(y), "f"(z), "f"(w) : "memory"); }
__device__ __forceinline__ void stsm4(uint32_t a, uint32_t r0, uint32_t r1, uint32_t r2, uint32_t r3) {
    asm volatile("stmatrix.sync.aligned.m8n8.x4.shared.b16 [%0], {%1,%2,%3,%4};" :: "r"(a), "r"(r0), "r"(r1), "r"(r2), "r"(r3) : "memory");
}
__device__ __forceinline__ void mmaq(float* c, const uint32_t* a, uint32_t b0, uint32_t b1) { mma16(c, a[0], a[1], a[2], a[3], b0, b1); }
template <int LUT> __device__ __forceinline__ uint32_t lop3(uint32_t a, uint32_t b, uint32_t c) { uint32_t r; asm("lop3.b32 %0, %1, %2, %3, %4;" : "=r"(r) : "r"(a), "r"(b), "r"(c), "n"(LUT)); return r; }
template <int N, int S> __device__ __forceinline__ uint32_t stale(const uint32_t* x, uint32_t tau) {
    if constexpr (N == 2) return lop3<0x7E>(x[0], tau, x[S]);
    else if constexpr (N == 3) return lop3<0xF6>(stale<2, S>(x, tau), x[2 * S], tau);
    else if constexpr (N == 4 || N == 16) return lop3<0xFC>(stale<N / 2, S>(x, tau), stale<N / 2, S>(x + N / 2 * S, tau), 0);
    else return lop3<0xFE>(stale<3, S>(x, tau), stale<3, S>(x + 3 * S, tau), stale<2, S>(x + 6 * S, tau));
}
__device__ __forceinline__ uint32_t late(uint32_t a, uint32_t b, uint32_t mask) {
    uint32_t r;
    asm volatile("{ .reg .pred p; .reg .b32 t; lop3.b32 t, %1, %2, %3, 0xA8; setp.ne.b32 p, t, 0; vote.sync.any.pred p, p, 0xFFFFFFFF; selp.u32 %0, 1, 0, p; }" : "=r"(r) : "r"(a), "r"(b), "r"(mask));
    return r;
}
#define AGAIN(id, reload, ...) _Pragma("unroll 1") for (int n_ = 0; __builtin_expect(__VA_ARGS__, 0) && n_ < SPIN_LIMIT; n_++) { RETRY(id, 1); reload; }
__device__ __forceinline__ uint32_t tile_off(int lane, int chunk0) {
    return ((lane >> 4) * 8 + (lane & 7)) * 128 + (((chunk0 + ((lane >> 3) & 1)) ^ (lane & 7)) << 4);
}
template <int K0, int K1>
__device__ __forceinline__ void load_tile(uint32_t a, uint32_t* T) {
    #pragma unroll
    for (int ks = K0; ks < K1; ks++) ldsm4t(T[4 * ks], T[4 * ks + 1], T[4 * ks + 2], T[4 * ks + 3], a + ks * 2048);
}
__device__ __forceinline__ void lds128u(uint32_t* v, uint32_t a) { asm volatile("ld.shared.v4.u32 {%0,%1,%2,%3}, [%4];" : "=r"(v[0]), "=r"(v[1]), "=r"(v[2]), "=r"(v[3]) : "r"(a) : "memory"); }
template <int K0, int K1, int STRIDE = 4096>
__device__ __forceinline__ void load_frag(uint32_t a, uint32_t* T) {
    #pragma unroll
    for (int ks = K0; ks < K1; ks++) lds128u(&T[4 * ks], a + ks * STRIDE);
}
template <int L0, int L1, bool INIT = false>
__device__ __forceinline__ void wg_run(float* acc, const uint32_t* A, const uint64_t* d) {
    if (L1 > L0) {
        wg_fence();
        #pragma unroll
        for (int l = L0; l < L1; l++) wgmma_n32_rs(acc, &A[4 * l], d[l], INIT || l != 0);
        wg_commit();
    }
}
__device__ __forceinline__ void load_x(const CUtensorMap* tmX, int c, int seg, uint32_t dst) {
    asm volatile("{ .reg .pred p; elect.sync _|p, 0xFFFFFFFF;\n"
        "@p cp.async.bulk.tensor.3d.shared::cluster.global.mbarrier::complete_tx::bytes [%4], [%0, {%5, %1, %2}], [%3]; }"
        :: "l"(tmX), "r"(seg * 32), "r"((c & 1) * 8), "r"(mk::MB_X), "r"(dst), "r"(0) : "memory");
    __syncwarp();
}
__device__ __forceinline__ void bulk_expect(uint32_t mb, uint32_t bytes) {
    asm volatile("{ .reg .pred p; elect.sync _|p, 0xFFFFFFFF; @p mbarrier.arrive.expect_tx.shared::cta.b64 _, [%0], %1; }" :: "r"(mb), "r"(bytes) : "memory");
}
__device__ __forceinline__ void bulk_copy(uint32_t dst, const void* src, uint32_t bytes, uint32_t mb) {
    asm volatile("{ .reg .pred p; elect.sync _|p, 0xFFFFFFFF; @p cp.async.bulk.shared::cluster.global.mbarrier::complete_tx::bytes [%0], [%1], %2, [%3]; }"
        :: "r"(dst), "l"(src), "r"(bytes), "r"(mb) : "memory");
    __syncwarp();
}
__device__ __forceinline__ void bulk_copy_if(bool on, uint32_t dst, const void* src, uint32_t bytes, uint32_t mb) {
    asm volatile("{ .reg .pred p; elect.sync _|p, 0xFFFFFFFF; setp.ne.and.b32 p, %4, 0, p; @p cp.async.bulk.shared::cluster.global.mbarrier::complete_tx::bytes [%0], [%1], %2, [%3]; }"
        :: "r"(dst), "l"(src), "r"(bytes), "r"(mb), "r"((int)on) : "memory");
    __syncwarp();
}
__device__ __forceinline__ void kv_expect(uint32_t bytes) { bulk_expect(mk::MB_KV, bytes); }
__device__ __forceinline__ void kv_copy(uint32_t dst, const void* src, uint32_t bytes) { bulk_copy(dst, src, bytes, mk::MB_KV); }
__device__ __forceinline__ uint32_t gtime() { uint32_t c; asm volatile("mov.u32 %0, %%globaltimer_lo;" : "=r"(c) :: "memory"); return c; }
__device__ __forceinline__ void wait_g(uint32_t tgt, uint32_t any) {
    asm volatile("{ .reg .pred p, q; .reg .u32 t; mov.u32 t, %0; setp.ne.u32 q, %1, 0xFFFFFFFF;\n"
                 "WG_%=: @q mov.u32 t, %%globaltimer_lo; sub.u32 t, t, %0; setp.gt.u32 p, t, 0xFFFF0000; @p bra.uni WG_%=; }" :: "r"(tgt), "r"(any) : "memory");
    __syncwarp();
}
__device__ __forceinline__ uint32_t clkv(uint32_t any) {
    uint32_t c; asm volatile("{ .reg .pred q; setp.ne.u32 q, %1, 0xFFFFFFFF; mov.u32 %0, 0; @q mov.u32 %0, %%clock; }" : "=r"(c) : "r"(any) : "memory"); return c;
}
__device__ __forceinline__ char* kv_src(int c, int seg) { return (char*)g_T + ((seg & 1) * mk::TSLOT + (c >> 2) * 49152); }
__device__ __forceinline__ void prefetch_l2(const void* p, uint32_t bytes) {
    asm volatile("{ .reg .pred p; elect.sync _|p, 0xFFFFFFFF; @p cp.async.bulk.prefetch.L2.global [%0], %1; }" :: "l"(p), "r"(bytes) : "memory");
}
__device__ __forceinline__ uint32_t phase(int i) { return (~i >> 1) & 1; }
__device__ __forceinline__ void qk_pack(const float* acc, uint32_t* p) {
    #pragma unroll
    for (int i = 0; i < 4; i++) { p[i] = pack2(acc[4 * i], acc[4 * i + 1]); p[4 + i] = pack2(acc[4 * i + 2], acc[4 * i + 3]); }
}
__device__ __forceinline__ void sts128_if(bool on, uint32_t a, const uint32_t* p) {
    asm volatile("{ .reg .pred p; setp.ne.b32 p, %5, 0; @p st.shared.v4.u32 [%0], {%1,%2,%3,%4}; }" :: "r"(a), "r"(p[0]), "r"(p[1]), "r"(p[2]), "r"(p[3]), "r"((int)on) : "memory");
}
__device__ __forceinline__ void st_if(bool on, char* a, const uint32_t* p) {
    asm volatile("{ .reg .pred p; setp.ne.b32 p, %5, 0; @p st.relaxed.gpu.global.v4.u32 [%0], {%1,%2,%3,%4}; }" :: "l"(a), "r"(p[0]), "r"(p[1]), "r"(p[2]), "r"(p[3]), "r"((int)on) : "memory");
}
__device__ __forceinline__ char* tok_dst(int c, int seg, int wg) { return kv_src(c, seg) + (wg ? (c & 1) * 8192 + (c & 2) * 2048 : 32768 + (c & 1) * 2048 + (c & 2) * 512); }
#define HI8 (wg ? 0x220 : 0xC0)
#define TAGM() uint32_t tm[4]; tag_masks(tm, (t16 >> (wg ? 4 : 6)) & 24)
__device__ __forceinline__ void acc_init(float* acc, const uint32_t* p) {
    #pragma unroll
    for (int i = 0; i < 4; i++) { acc[4 * i] = bflo(p[i]); acc[4 * i + 1] = bfhi(p[i]); acc[4 * i + 2] = bflo(p[4 + i]); acc[4 * i + 3] = bfhi(p[4 + i]); }
}
__device__ __forceinline__ void acc_add(float* acc, const uint32_t* p) {
    #pragma unroll
    for (int i = 0; i < 4; i++) { acc[4 * i] += bflo(p[i]); acc[4 * i + 1] += bfhi(p[i]); acc[4 * i + 2] += bflo(p[4 + i]); acc[4 * i + 3] += bfhi(p[4 + i]); }
}
__device__ __forceinline__ void tag_masks(uint32_t* m, uint32_t j8) {
    const uint32_t x = 1u << j8;
    #pragma unroll
    for (int i = 0; i < 4; i++) m[i] = opq(__byte_perm(x, 0, 0x4440 + i));
}
__device__ __forceinline__ void pack_tag(const float* acc, uint32_t* p, uint32_t tau, const uint32_t* m) {
    qk_pack(acc, p);
    #pragma unroll
    for (int i = 0; i < 8; i++) p[i] = lop3<0xB8>(p[i], m[i & 3], tau);
}
__device__ __forceinline__ uint32_t kv_stale(uint32_t w, uint32_t l16, uint32_t tau) {
    uint32_t x[12];
    const uint32_t a = opq(l16 * 2 + ((l16 >> 4) & 0x1C) + w * 12288), aq = w == 2 ? opq(l16 * 2 + ((l16 >> 2) & 0x10) + ((l16 >> 5) & 0xC) + 24576) : a;
    #pragma unroll
    for (int i = 0; i < 12; i++) x[i] = lds32(mk::TK + i * 1024 + (i < 8 ? a : aq));
    return late(stale<8, 1>(x, tau), stale<4, 1>(x + 8, tau), 1);
}
__device__ __forceinline__ void refetch_kv(int c, int seg, int w, uint32_t l16) {
    #pragma unroll 1
    for (int i = w * 24; i < w * 24 + 24; i++) {
        uint32_t v[4];
        ld_g128(v, kv_src(c, seg) + (i * 512 + (i >> 6) * (c & 3) * 4096) + l16);
        sts128(mk::TK + i * 512 + l16, make_uint4(v[0], v[1], v[2], v[3]));
    }
    __syncwarp();
}
__device__ __forceinline__ void get_kv(int c, int seg) {
    kv_expect(36864); kv_copy(mk::TK, kv_src(c, seg), 32768); kv_copy(mk::TQ, kv_src(c, seg) + (32768 + (c & 3) * 4096), 4096);
}
constexpr uint32_t ONES = 0x3F803F80u;
__device__ __forceinline__ float rcpf(float x) { float r; asm("rcp.approx.ftz.f32 %0, %1;" : "=f"(r) : "f"(x)); return r; }

#define ANN 2
#define POL 8
#define PRE0 4
#define PRE1 4
#define HC 2
#define HR 4
#define BL 1
#define NA 2
#define QF 0
#define DEEP 6
#define AHEAD(n) (PRE0 + 2 * (n) < (n) + DEEP ? PRE0 + 2 * (n) : (n) + DEEP < 16 ? (n) + DEEP : 16)
#define CO 1
#define HS 2
#define VP 0
#define KM 1
#define NLDS 2
#define AL 2
#define RP 26
#define RQ 2
#define RL 29
#define R4 1
#define KVP 12
#define LD7 8
#define XP 3
#define G2 0
#define NB 26
#define BD 8
#define NP 22
#define TA 4
#define TA0 2
#define NT 19
#define VH 1
#define TRIES 200
#define NPW 3
#define EV0 5
#define EV1 8
#define WA1 6
#define WA2 9
#define H2 10
#define QV 1
#define QD 0
#define KD 0
#define VD 0
#define WA0 4
#define ONE 0
#define PP 12
#define OBA 3
#define WA3 1
#define WB1 0
#define WB2 12
#define WB3 13
#define H0 6
#define H3 10
__device__ __forceinline__ uint32_t tagm(uint32_t w, uint32_t mask, uint32_t tau) { return lop3<0xB8>(w, mask, tau); }
__device__ __forceinline__ char* at(uint32_t lo, uint32_t hi) { char* p; asm("mov.b64 %0, {%1,%2};" : "=l"(p) : "r"(lo), "r"(hi)); return p; }
__device__ __forceinline__ float ex2(float x) { float r; asm("ex2.approx.ftz.f32 %0, %1;" : "=f"(r) : "f"(x)); return r; }
__device__ __forceinline__ float max8(const float* x) { return fmaxf(fmaxf(fmaxf(x[0], x[1]), fmaxf(x[2], x[3])), fmaxf(fmaxf(x[4], x[5]), fmaxf(x[6], x[7]))); }
__device__ __forceinline__ float max4lanes(float m) { return fmaxf(fmaxf(m, __shfl_xor_sync(~0u, m, 1)), fmaxf(__shfl_xor_sync(~0u, m, 2), __shfl_xor_sync(~0u, m, 3))); }
constexpr float SCL = 0.08838834764831845f * 1.4426950408889634f;
__device__ __forceinline__ void tok_scores(float* x, uint32_t sa) {
    float y[8];
    lds128f(x, sa); lds128f(y, sa + 1024); lds128f(x + 4, sa + 512); lds128f(y + 4, sa + 1536);
    #pragma unroll
    for (int i = 0; i < 8; i++) x[i] += y[i];
}
__device__ __forceinline__ void mem_scores(float* x, uint32_t sa) {
    float z[8];
    lds128f(z, sa + 2048); lds128f(z + 4, sa + 2560);
    x[8] = (z[0] + z[2]) + (z[4] + z[6]); x[9] = (z[1] + z[3]) + (z[5] + z[7]);
}

struct Ctx { uint32_t u_rs, u_rl, u_bs, u_bl, rblo, rbhi; int w8, c; };
template <int wg>
__device__ __forceinline__ void steps(uint32_t* W, uint32_t* T, uint32_t t16, uint32_t pa, uint32_t pb, const Ctx& cx, const CUtensorMap* tmX, const MainParams& prm) {
    using namespace mk;
    const int c = cx.c, kap = c & 1, w8 = cx.w8;
    const uint32_t rbhi = cx.rbhi;
    uint32_t u_rs = cx.u_rs, u_rl = cx.u_rl, u_bs = cx.u_bs, u_bl = cx.u_bl ^ ((c & 2) << 14);
    uint32_t u_x = cx.rblo + RB_X + (c >> 2) * 16384, u_xs = u_x + kap * 2048 + (c & 2) * 512;
    uint32_t u_ta = ((cx.u_bl & ~0x10000u) ^ (kap << 12)) + (RB_T - RB_B) + 1024;
    uint32_t u_rp = cx.rblo + RB_T + 1024 + c * 4;
    uint32_t u_og = (c & 3) * 65536 + (c >> 2) * 2048 + (w8 & 3) * 256;
    const uint32_t u_sa = (w8 & 2) * 256 + (w8 & 1) * 8;
    #define TOK_DST() tok_dst(c, seg, wg)
    constexpr int EV = wg ? EV1 : EV0;
    constexpr uint32_t VEB = VE + (wg ? EV0 * 2048 - 2048 : 0) - (16 - EV) * 2048;
    static_assert((EV0 + EV1) * 2048 <= 28672, "");
    __syncthreads();
    #pragma unroll
    for (int i = 16 - EV; i < 16; i++) sts128(VEB + i * 2048 + t16, make_uint4(T[4 * i], T[4 * i + 1], T[4 * i + 2], T[4 * i + 3]));
    asm volatile("fence.proxy.async.shared::cta;" ::: "memory");
    #pragma unroll 1
    for (uint32_t sb = 0, redo = 0, uz = prm.zero;;) {
        sb = opq(sb + 256);
        const int s = sb & 255, bc = sb >> 8;
        t16 |= uz;
        uz &= sb;
        const int seg = s + 2;
        const uint32_t tau = phase(s);
        const uint32_t l16 = opq(t16 & 0x1F0);
        uint32_t F[64];
        float ot[3][2][4];
        uint32_t an[4];
        #define LDB(i) ldsm4t(b[i][0], b[i][1], b[i][2], b[i][3], MEM + l16 + (i) * 512)
        #define ST_X() do { char* xs = at(u_xs + (pb >> 16), rbhi) + wg * 4096; \
            st_g32(xs, tagm(pack2((a[0][0] + a[1][0]) + (a[2][0] + a[3][0]), (a[0][2] + a[1][2]) + (a[2][2] + a[3][2])), mG, tau * 0x10001u)); \
            st_g32(xs + 32, tagm(pack2((a[0][1] + a[1][1]) + (a[2][1] + a[3][1]), (a[0][3] + a[1][3]) + (a[2][3] + a[3][3])), mG, tau * 0x10001u)); } while (0)
        #define ST_V() st_g64(at(u_xs + (t16 >> 1), rbhi) + (8192 + wg * 3072), \
            tagm(pack2((v[0][0] + v[1][0]) + (v[2][0] + v[3][0]), (v[0][1] + v[1][1]) + (v[2][1] + v[3][1])), mT, tau), \
            pack2((v[0][2] + v[1][2]) + (v[2][2] + v[3][2]), (v[0][3] + v[1][3]) + (v[2][3] + v[3][3])))
        #define V_MMA(i, o) do { mmaq(v[2 * ((i) & 1)], &T[8 * (i)], b[(o) + (i)][0], b[(o) + (i)][1]); mmaq(v[2 * ((i) & 1) + 1], &T[8 * (i) + 4], b[(o) + (i)][2], b[(o) + (i)][3]); } while (0)
        #define ST_R(i) do { \
                const uint32_t r0 = pack2((r[i][0][0] + r[i][1][0]) * i0, (r[i][0][1] + r[i][1][1]) * i1); \
                const uint32_t r1 = pack2((r[i][0][2] + r[i][1][2]) * i0, (r[i][0][3] + r[i][1][3]) * i1); \
                st_g64(at(ra ^ (i * 0x3000), rbhi), tagm(r0, mT, tau), r1); } while (0)
        #define LD_OB(i) ldsm4t(ob[4 * (i)], ob[4 * (i) + 1], ob[4 * (i) + 2], ob[4 * (i) + 3], OB + l16 + (i) * 512)
        #define WO_MMA(have, more, mid, tail) uint32_t ob[16], ra; float r[2][2][4] = {}; \
            LD_OB(0); __syncwarp(); LD_OB(1); __syncwarp(); if (OBA > 2) { LD_OB(2); __syncwarp(); } \
            _Pragma("unroll") for (int i = have; i < have + more; i++) { lds128u(&F[4 * i], WO + t16 + i * 4096); __syncwarp(); } \
            _Pragma("unroll") for (int i = 0; i < 16; i++) { \
                if (!(i & 1) || (i > 4 && i < 8)) CUT(pb); \
                if (i == 4) LD_OB(OBA); \
                if (i == 5 && OBA == 2) LD_OB(3); \
                { const int n = have + more + i - 8 + OBA; if (i >= 8 - OBA && n < 16) lds128u(&F[4 * n], WO + t16 + n * 4096); } \
                if (wg == 0 && i == 4) { const float2 su = lds64f(SUM + (l16 >> 1)); i0 = su.x; i1 = su.y; } \
                mmaq(r[(i >> 1) & 1][i & 1], &F[4 * i], ob[(i >> 2) * 4 + 2 * (i & 1)], ob[(i >> 2) * 4 + 2 * (i & 1) + 1]); \
                if (wg && i == 2) { i0 = opqf(rcpf(i0)); i1 = opqf(rcpf(i1)); } \
                if (i == PP) { mid; } \
                if (wg && i == POL) POLL(); \
                if (!wg && i == KVP) bulk_copy(TK + 16384 + w8 * 4096, kv_src(c, s + 1) + (16384 + w8 * 4096), 4096, MB_KV); \
                if (i == 11) { ra = (l16 >> 1) * 33 & 0x1078; CUT(ra); } \
                if (i == 13) ra = opq(ra ^ u_rs); } \
            CUT(pb); tail; \
            if (!wg) { i0 = rcpf(i0); i1 = rcpf(i1); } \
            ST_R(0); ST_R(1)
        #define LD_X(r, o) do { ld_g64(r, xa + (o)); ld_g64(r + 2, xa + ((o) + 2048)); ld_g64(r + 4, xa + ((o) + 1024)); ld_g64(r + 6, xa + ((o) + 3072)); } while (0)
        #define REPORT(w, add) asm volatile("{ .reg .pred p; .reg .u32 t; setp.lt.u32 p, %1, 32; mov.u32 t, %1; @p mov.u32 t, %%globaltimer_lo; add.u32 t, t, %3; lop3.b32 t, t, 31, %2, 0xB8; @p st.relaxed.gpu.global.u32 [%0], t; }" \
            :: "l"(at(u_rp + (l16 << 8), rbhi)), "r"(t16 - (w) * 512), "r"(s), "r"(add) : "memory")
        #define POLL() asm volatile("{ .reg .pred p; setp.ge.u32 p, %5, 3584; mov.u32 %0, 0; mov.u32 %1, 0; mov.u32 %2, 0; mov.u32 %3, 0; @p ld.relaxed.gpu.global.v4.u32 {%0,%1,%2,%3}, [%4]; }" \
            : "=&r"(an[0]), "=&r"(an[1]), "=&r"(an[2]), "=&r"(an[3]) : "l"(at(u_ta + l16, rbhi)), "r"(t16) : "memory")
        #define GET_B(sl) do { const uint32_t a_ = u_bl ^ (sl); bulk_copy(MEM, at(a_, rbhi), 4096, MB_B); bulk_copy(MEM + 4096, at(a_ ^ 0x3000, rbhi), 4096, MB_B); } while (0)
        if constexpr (wg == 0) {
            float a[4][4], v[4][4] = {};
            uint32_t b[16][4];
            if (__builtin_expect(redo, 0)) {
                RETRY(6, 1);
                bsync<B_RD, 256>();
                if (w8 == 3) { bulk_expect(MB_B, 8192); GET_B(1 << 20); }
                __syncwarp();
            }
            const uint32_t ck = opq(t16 * 2 + ((l16 >> 4) & 0x1C)), tp = opq(phase(s - 1)), cm = opq((2 * bc + (s > 0 && bc < SPIN_LIMIT)) | (t16 >> 19));
            CUT(pa);
            mbar_wait(MB_B, ~bc & 1);
            #define ORD(n) (n)
            LDB(ORD(0)); __syncwarp(); LDB(ORD(1)); __syncwarp();
            const uint32_t c0 = lds32(MEM + ck), c1 = lds32(MEM + 4096 + ck);
            __syncwarp();
            #pragma unroll
            for (int n = 2; n < PRE0; n++) { LDB(ORD(n)); __syncwarp(); }
            PROF(0);
            uint32_t vw[2];
            #pragma unroll
            for (int n = 0; n < 16; n++) {
                const int i = ORD(n);
                CUT(pa);
                #pragma unroll
                for (int m = AHEAD(n); m < AHEAD(n + 1); m++) { LDB(ORD(m)); __syncwarp(); }
                if (n == HC) redo = opq(lop3<0x7E>(c0, tp, c1) & cm);
                if (n == HC + 1) asm volatile("{ .reg .pred p; setp.ne.u32 p, %2, 0; @p st.shared.u32 [%0], %1; }" :: "r"(SUM + 256), "r"(cm), "r"(redo & 1) : "memory");
                if (n == H0) barrive<B_H0, 256>();
                if (n == HR + 1) { redo = lds32(SUM + 256 + opq(t16 >> 20)); __syncwarp(); }
                if (n == HR) bsync<B_START, 128>();
                if (n == 12) redo = !late(redo ^ (2 * bc + 1), 0, ~0u);
                const int e = n < 8 ? 0 : 2 * (~n & 1);
                if (!(n & 7)) a[e][0] = a[e][1] = a[e][2] = a[e][3] = a[e + 1][0] = a[e + 1][1] = a[e + 1][2] = a[e + 1][3] = 0.f;
                mmaq(a[e], &W[8 * i], b[i][0], b[i][1]);
                if (n < 8) { mmaq(v[0], &T[8 * i], b[i][0], b[i][1]); CUT(pa); }
                mmaq(a[e + 1], &W[8 * i + 4], b[i][2], b[i][3]);
                if (n < 8) mmaq(v[1], &T[8 * i + 4], b[i][2], b[i][3]);
                if (n == 10) { vw[0] = opq(pack2(v[0][0] + v[1][0], v[0][1] + v[1][1])); vw[1] = opq(pack2(v[0][2] + v[1][2], v[0][3] + v[1][3])); }
            }
            CUT(pa);
            if (__builtin_expect(redo, 0)) { __syncwarp(); continue; }
            CUT(pa); CUT(pb);
            const uint32_t mG = (l16 & 0x1C0) ? 0 : 0x10001u, mT = (l16 & 0x30) ? 0 : 1;
            ST_X();
            CUT(pa);
            PROF(1);
            const char* const xa = at(u_x + (t16 >> 1), rbhi);
            float sc[4][4];
            uint32_t k[8], A[16], q[16], kf[16];
            #define LD_Q(xb) do { LD_X(q, 0); { const char* const xa = xb; LD_X(q + 8, 0); } } while (0)
            #define XB() at((u_x + (opq(t16) >> 1)) ^ 256, rbhi)
            #define LD_A(i) ldsm4t(A[4 * i], A[4 * i + 1], A[4 * i + 2], A[4 * i + 3], TQ + (i & 1) * 1024 + ((i & 2) ? qb : qa))
            uint32_t k1[16];
            #define LD_K(i) do { ldsm4t(kf[4 * i], kf[4 * i + 1], kf[4 * i + 2], kf[4 * i + 3], TK + ka[i]); ldsm4t(k1[4 * i], k1[4 * i + 1], k1[4 * i + 2], k1[4 * i + 3], TK + 8192 + ka[i]); __syncwarp(); } while (0)
            const char* const xb = XB();
            const uint32_t ka[4] = {opq(pa & 0xFFFF), opq((pa & 0xFFFF) ^ 0x400), opq((pa & 0xFFFF) ^ 0x10), opq((pa & 0xFFFF) ^ 0x410)}, qa = opq(pa >> 16), qb = opq(qa ^ 0x100);
            st_g64(at(u_xs + (t16 >> 1), rbhi) + 8192, tagm(vw[0], mT, tau), vw[1]);
            CUT(pb);
            bsync<B_H2, 256>();
            if (QF) { LD_Q(xb); __syncwarp(); }
            #pragma unroll
            for (int i = 0; i < NA; i++) LD_K(i);
            CUT(pb);
            #pragma unroll
            for (int i = 0; i < 4 * NA; i++) kf[i] = opq(hadd2(kf[i], k1[i]));
            CUT(pb);
            if (!QF) { DELAY(QD); LD_Q(xb); CUT(pb); }
            bsync<B_H3, 256>();
            #pragma unroll
            for (int i = NA; i < 4; i++) LD_K(i);
            LD_A(0); LD_A(1); LD_A(2); LD_A(3);
            CUT(pb);
            if (KM == 1) {
                #pragma unroll
                for (int i = 4 * NA; i < 16; i++) kf[i] = opq(hadd2(kf[i], k1[i]));
                CUT(pb);
            }
            DELAY(KD);
            LD_X(k, 4096);
            barrive<B_VX, 256>();
            CUT(pb);
            PROF(3);
            if (KM == 2) {
                #pragma unroll
                for (int i = 4 * NA; i < 16; i++) kf[i] = opq(hadd2(kf[i], k1[i]));
            }
            #pragma unroll
            for (int i = 0; i < 8; i++) A[2 * i + 1] = opq(hadd2(A[2 * i], A[2 * i + 1]));
            CUT(pb);
            AGAIN(1, LD_Q(XB()); LD_X(k, 4096); sts32(SUM + 268, s + 1), late(stale<4, 2>(q, tau), stale<4, 2>(q + 8, tau), mT))
            #pragma unroll
            for (int i = 0; i < 4; i++) {
                A[4 * i] = hadd2(q[4 * i], q[4 * i + 2]); A[4 * i + 2] = hadd2(q[4 * i + 1], q[4 * i + 3]);
                if (i < 2) { sc[i][0] = sc[i][1] = sc[i][2] = sc[i][3] = sc[2 + i][0] = sc[2 + i][1] = sc[2 + i][2] = sc[2 + i][3] = 0.f; }
                mmaq(sc[i & 1], A + 4 * i, kf[2 * i], kf[2 * i + 1]); mmaq(sc[2 + (i & 1)], A + 4 * i, kf[8 + 2 * i], kf[9 + 2 * i]);
            }
            sts128f(SC + t16, sc[0][0] + sc[1][0], sc[0][1] + sc[1][1], sc[2][0] + sc[3][0], sc[2][1] + sc[3][1]);
            barrive<B_S1, 256>();
            sts128f(SC + 3072 + t16, sc[0][2] + sc[1][2], sc[0][3] + sc[1][3], sc[2][2] + sc[3][2], sc[2][3] + sc[3][3]);
            load_frag<0, WB1>(WO + t16, F);
            const uint32_t sa = opq(l16 + u_sa);
            CUT(pb);
            PROF(4);
            float d[16];
            #pragma unroll 1
            for (int n_ = 0;; n_++) {
                #pragma unroll
                for (int i = 0; i < 4; i++) { d[4 * i] = d[4 * i + 1] = d[4 * i + 2] = d[4 * i + 3] = 0.f; mmaq(d + 4 * i, A + 4 * (i >> 1), k[2 * i], k[2 * i + 1]); }
                if (__builtin_expect(!late(stale<2, 2>(k, tau), stale<2, 2>(k + 4, tau), mT), 1) || n_ >= SPIN_LIMIT) break;
                RETRY(2, 1);
                LD_X(k, 4096);
            }
            sts64f(SC + 2048 + sa, (d[0] + d[4]) + (d[8] + d[12]), (d[1] + d[5]) + (d[9] + d[13]));
            barrive<B_SC, 256>();
            CUT(pb);
            sts64f(SC + 5120 + sa, (d[2] + d[6]) + (d[10] + d[14]), (d[3] + d[7]) + (d[11] + d[15]));
            PROF(5);
            if (w8 == 0) {
                float x[10];
                bsync<B_S0, 128>();
                tok_scores(x, SC + 3072 + l16); mem_scores(x, SC + 3072 + l16);
                __syncwarp();
                load_frag<WB1, WB2>(WO + t16, F);
                const int g = l16 >> 6, lim = 8 * (g >> 1) + 2 * (c & 3) + (g & 1) - ((l16 >> 1) & 0x18);
                #pragma unroll
                for (int i = 0; i < 8; i++) if (i > lim) x[i] = -INFINITY;
                const float ms = opqf(-SCL * max4lanes(fmaxf(max8(x), fmaxf(x[8], x[9]))));
                CUT(pb);
                #pragma unroll
                for (int i = 0; i < 10; i++) x[i] = ex2(fmaf(x[i], SCL, ms));
                load_frag<WB2, WB3>(WO + t16, F);
                sts128(PT + l16, make_uint4(pack2(x[0], x[1]), pack2(x[2], x[3]), pack2(x[4], x[5]), pack2(x[6], x[7])));
                sts32(PT + 512 + (l16 >> 2), pack2(x[8], x[9]));
                if (!ONE) barrive<B_PT, 160>();
            } else {
                if (ANN == 2) { bsync<B_S0, 128>(); const uint32_t f = lds32(SUM + 268 + opq(t16 >> 16)); REPORT(3, f == s + 1 ? P(2) : 0); } else barrive<B_S0, 128>();
                if (w8 == 1) {
                    mbar_wait(MB_X, ~seg & 1); bulk_expect(MB_X, 32768);
                    if (XPF) prefetch_l2(prm.x + (((seg + XPF) & 63) * 65536 + c * 512), 512);
                    __syncwarp();
                    if (XDL == 300) load_x(tmX, c, seg + 1, (s & 1) ? XT : XT2);
                }
                else if (w8 == 2) {
                    bulk_expect(MB_KV, 36864);
                    bulk_copy(TK, kv_src(c, s + 1), 16384, MB_KV); bulk_copy(TQ, kv_src(c, s + 1) + (32768 + (c & 3) * 4096), 4096, MB_KV);
                    bulk_expect(MB_B, 8192); bulk_expect(MB_R, 4096);
                    __syncwarp();
                }
                bsync<B_SC2, 224>();
                load_frag<WB1, WB3>(WO + t16, F);
                __syncwarp();
                CUT(pb);
            }
            bsync<B_O2, 256>();
            PROF(6);
            float i0, i1;
            WO_MMA(WB3, 0, , );
        } else {
            float a[4][4], v[4][4] = {};
            uint32_t b[16][4];
            barrive_if<B_RD, 256>(redo);
            CUT(pa);
            bsync<B_H0, 256>();
            #pragma unroll
            for (int n = 0; n < PRE1; n++) { LDB(n); __syncwarp(); }
            redo = lds32(SUM + 256 + opq(t16 >> 20));
            PROF(0);
            #pragma unroll
            for (int i = 0; i < 16; i++) {
                if (!(i & 1)) {
                    CUT(pa);
                    if (PRE1 < 8 && i + PRE1 < 16) { LDB(i + PRE1); __syncwarp(); LDB(i + PRE1 + 1); __syncwarp(); }
                    if (PRE1 == 8 && i >= 2 && i < 10) { LDB(i + 6); __syncwarp(); LDB(i + 7); __syncwarp(); }
                    if (i == 6) redo = !late(redo ^ (2 * bc + 1), 0, ~0u);
                    if (i == H2) { barrive_if<B_H2, 256>(!redo); CUT(pa); }
                }
                else if (CO) CUT(pa);
                if (i < 2) { a[2 * i][0] = a[2 * i][1] = a[2 * i][2] = a[2 * i][3] = a[2 * i + 1][0] = a[2 * i + 1][1] = a[2 * i + 1][2] = a[2 * i + 1][3] = 0.f; }
                mmaq(a[2 * (i & 1)], &W[8 * i], b[i][0], b[i][1]); mmaq(a[2 * (i & 1) + 1], &W[8 * i + 4], b[i][2], b[i][3]);
            }
            if (__builtin_expect(redo, 0)) { __syncwarp(); continue; }
            CUT(pa); CUT(pb);
            const uint32_t mG = (l16 & 0x1C0) ? 0 : 0x10001u, mT = (l16 & 0x30) ? 0 : 1;
            ST_X();
            barrive<B_H3, 256>();
            CUT(pa);
            PROF(1);
            #pragma unroll
            for (int i = 7; i >= 0; i--) V_MMA(i, 8);
            ST_V();
            CUT(pb);
            bsync<B_VX, 256>();
            PROF(2);
            uint32_t vf[16], vm[16];
            const uint32_t va = opq(pa), vb = opq(va ^ 0x20);
            #define LD_V() do { _Pragma("unroll") for (int i = 0; i < 4; i++) { const uint32_t a_ = TK + 16384 + ((i & 1) ? vb : va) + (i >> 1) * 4096; \
                ldsm4(vf[4 * i], vf[4 * i + 1], vf[4 * i + 2], vf[4 * i + 3], a_); ldsm4(vm[4 * i], vm[4 * i + 1], vm[4 * i + 2], vm[4 * i + 3], a_ + 8192); } } while (0)
            LD_V();
            __syncwarp();
            load_frag<0, WA0>(WO + t16, F);
            #pragma unroll
            for (int i = 0; i < 16; i++) vf[i] = opq(hadd2(vf[i], vm[i]));
            const char* const xa = at(u_x + (t16 >> 1), rbhi) + (8192 - 1024);
            if (VP) CUT(pb);
            DELAY(VD);
            LD_X(vm, 0); LD_X(vm + 8, 4096);
            __syncwarp();
            load_frag<WA0, WA1>(WO + t16, F);
            CUT(pb);
            float x[10];
            bsync<B_S1, 256>();
            tok_scores(x, SC + l16);
            const float mt = opqf(max8(x));
            if (ANN == 3) REPORT(7, 0);
            CUT(pb);
            PROF(3);
            bsync<B_SC, 256>();
            mem_scores(x, SC + l16);
            const float m1 = fmaxf(mt, fmaxf(x[8], x[9]));
            const float m2 = __shfl_xor_sync(~0u, m1, 1), m3 = __shfl_xor_sync(~0u, m1, 2), m4 = __shfl_xor_sync(~0u, m1, 3);
            CUT(pb);
            load_frag<WA1, WA2>(WO + t16, F);
            barrive<B_SC2, 224>();
            uint32_t p[5], vs[4];
            #define SUM_V() do { _Pragma("unroll") for (int i = 0; i < 4; i++) { const int e = (i >> 1) * 4 + (i & 1); vs[i] = hadd2(hadd2(vm[e], vm[e + 8]), hadd2(vm[e + 2], vm[e + 10])); } } while (0)
            CUT(pb);
            const float ms = -SCL * fmaxf(fmaxf(m1, m2), fmaxf(m3, m4));
            PROF(5);
            #pragma unroll
            for (int i = 0; i < 10; i++) x[i] = fmaf(x[i], SCL, ms);
            x[8] = opqf(ex2(x[8])); x[9] = opqf(ex2(x[9]));
            CUT(pb);
            uint32_t badv = late(stale<4, 2>(vm, tau), stale<4, 2>(vm + 8, tau), mT);
            SUM_V();
            #pragma unroll
            for (int i = 0; i < 4; i++) { x[i] = opqf(ex2(x[i])); vs[i] = opq(vs[i]); }
            const uint32_t z0 = t16 >> 16;
            uint32_t one[4] = {opq(ONES | z0), opq(ONES ^ z0), opq(ONES + z0), opq(ONES - z0)};
            CUT(pb);
            #pragma unroll
            for (int i = 4; i < 8; i++) x[i] = ex2(x[i]);
            #pragma unroll
            for (int i = 0; i < 5; i++) p[i] = pack2(x[2 * i], x[2 * i + 1]);
            float sm[4] = {};
            #define PV(also) do { float o[8] = {}; \
                mma8(o, vs[0], vs[1], p[4]); mma8(o + 4, vs[2], vs[3], p[4]); if (also) mma8(sm, one[0], one[1], p[4]); \
                mmaq(o, vf, p[0], p[1]); mmaq(o + 4, vf + 8, p[0], p[1]); if (also) mmaq(sm, one, p[0], p[1]); \
                mmaq(o, vf + 4, p[2], p[3]); mmaq(o + 4, vf + 12, p[2], p[3]); if (also) mmaq(sm, one, p[2], p[3]); \
                stsm4(OB - 2048 + opq(t16), pack2(o[0], o[1]), pack2(o[2], o[3]), pack2(o[4], o[5]), pack2(o[6], o[7])); } while (0)
            PV(true);
            if (w8 == 4) sts64f(SUM + (l16 >> 1), sm[0], sm[1]);
            if (__builtin_expect(badv, 0)) {
                int n_ = 0;
                uint32_t vm[16];
                const char* const xa = at(u_x + (8192 - 1024) + (opq(t16) >> 1), rbhi);
                do { RETRY(3, 1); LD_X(vm, 0); LD_X(vm + 8, 4096); } while (late(stale<4, 2>(vm, tau), stale<4, 2>(vm + 8, tau), mT) && ++n_ < SPIN_LIMIT);
                SUM_V();
                PV(false);
            }
            if (ONE) bsync<B_O2, 256>(); else { barrive<B_O2, 256>(); bsync<B_O, 128>(); }
            PROF(6);
            float i0 = sm[0], i1 = sm[1];
            #define GET_P() if (!ONE) bsync<B_PT, 160>(); lds128u(p, PT + l16); p[4] = lds32(PT + 512 + (l16 >> 2))
            #define TOK_PV() { const uint32_t z = t16 >> 17; one[0] = ONES | z; one[1] = ONES ^ z; one[2] = ONES + z; one[3] = ONES - z; } \
                _Pragma("unroll") for (int i = 0; i < 12; i++) ot[i >> 2][0][i & 3] = ot[i >> 2][1][i & 3] = 0.f; \
                mma8(ot[0][0], vs[0], vs[1], p[4]); mma8(ot[1][0], vs[2], vs[3], p[4]); mma8(ot[2][0], one[0], one[1], p[4]); \
                mmaq(ot[0][1], vf + 4, p[2], p[3]); mmaq(ot[1][1], vf + 12, p[2], p[3]); mmaq(ot[2][1], one, p[2], p[3]); CUT(pa)
            WO_MMA(WA2, WA3, GET_P(), TOK_PV());
            CUT(pa);
            mmaq(ot[0][0], vf, p[0], p[1]); mmaq(ot[1][0], vf + 8, p[0], p[1]); mmaq(ot[2][0], one, p[0], p[1]);
            CUT(pb);
            barrive<B_GO, 256>();
        }
        CUT(pb);
        PROF(7);
        #define PK_O() const float j0 = rcpf(ot[2][0][0] + ot[2][1][0]), j1 = rcpf(ot[2][0][1] + ot[2][1][1]); uint32_t ow[4]; \
            _Pragma("unroll") for (int i = 0; i < 4; i++) \
                ow[i] = opq(pack2((ot[i >> 1][0][2 * (i & 1)] + ot[i >> 1][1][2 * (i & 1)]) * j0, (ot[i >> 1][0][2 * (i & 1) + 1] + ot[i >> 1][1][2 * (i & 1) + 1]) * j1))
        #define ST_O() do { uint32_t* og = (uint32_t*)((char*)g_O + (u_og + (l16 >> 2))); \
            _Pragma("unroll") for (int i = 0; i < 4; i++) og[(i >> 1) * 256 + (i & 1) * 32] = ow[i]; } while (0)
        #define BSO() ((u_bs) ^ ((l16 & 0x10) + ((l16 >> 3) & 0xC) + (l16 & 0x80) * 0x20 + (l16 & 0x100) * 0x80))
        const uint32_t taus = phase(seg);
        const uint64_t* const dq = c_xd + (s & 1) * 32; const uint64_t* const dv = dq + (wg * 16 | uz);
        float acc[16], acv[16];
        uint32_t u[8];
        if constexpr (wg == 0) {
            if (s == NSEG - 1) { bsync<B_GO, 256>(); st_g32(at(BSO(), rbhi), 0); mbar_wait(MB_KV, 1); if (XDL == 300) mbar_wait(MB_X, 1); break; }
            load_frag<16 - EV, 16, 2048>(VEB + t16, T);
            bsync<B_GO, 256>();
            PROF(8);
            wg_run<0, 16 - EV>(acv, T, dv);
            wg_run<16 - EV, 16>(acv, T, dv);
            wg_run<0, 5>(acc, W, dq); wg_wait<1>();
            qk_pack(acv, u);
            #pragma unroll
            for (int i = 0; i < 8; i++) u[i] = opq(u[i]);
            CUT(pa);
            wg_run<5, 8>(acc, W, dq);
            __syncwarp();
            sts128(SC + opq(t16), make_uint4(u[0], u[1], u[2], u[3])); sts128(SC + 2048 + opq(t16), make_uint4(u[4], u[5], u[6], u[7]));
            barrive<B_VX, 256>();
            __syncwarp();
            PROF(9);
            wg_run<8, 12>(acc, W, dq);
            CUT(pa);
            char* const bs = at(opq(BSO()), opq(rbhi));
            CUT(pa);
            wg_run<12, 15>(acc, W, dq);
            CUT(pa);
            const uint32_t ro = opq(l16 * 8 + ((l16 & 0x70) ^ ((w8 & 3) << 5))), ro2 = opq(ro ^ 0x10);
            const uint32_t mG = opq((l16 & 0x1C0) ? 0 : 0x10001u), mB = opq((((l16 >> 2) & 4) + ((l16 >> 5) & 3)) == ((u_bs >> 7) & 7) ? 1 : 0), zz = t16 >> 18;
            CUT(pa);
            wg_run<15, 18>(acc, W, dq);
            CUT(pa);
            const uint32_t one[4] = {opq(ONES | zz), opq(ONES ^ zz), opq(ONES + zz), opq(ONES - zz)};
            const uint32_t par = s & 1, tt = tau * 0x10001u;
            CUT(pa);
            wg_run<18, RP>(acc, W, dq);
            CUT(pa);
            PROF(10);
            mbar_wait(MB_R, par);
            PROF(14);
            uint32_t x[8], bad;
            float d[4][4];
            #define SUM_R() do { ldsm4t(x[0], x[1], x[2], x[3], RS + ro); ldsm4t(x[4], x[5], x[6], x[7], RS + ro2); \
                _Pragma("unroll") for (int i = 0; i < 4; i++) { d[i][0] = d[i][1] = d[i][2] = d[i][3] = 0.f; mmaq(d[i], one, x[2 * i], x[2 * i + 1]); } } while (0)
            #define PUT_B() do { bad = late(stale<2, 1>(x, tt), stale<2, 1>(x + 2, tt), mG); \
                const uint32_t w0 = pack2(d[0][0] + d[1][0], d[0][1] + d[1][1]), w1 = pack2(d[2][0] + d[3][0], d[2][1] + d[3][1]); \
                asm volatile("{ .reg .pred p; setp.eq.b32 p, %2, 0; @p st.relaxed.gpu.global.u32 [%0], %1; }" :: "l"(bs), "r"(tagm((l16 & 0x40) ? w1 : w0, mB, tt)), "r"(bad) : "memory"); } while (0)
            SUM_R();
            CUT(pa);
            wg_run<RP, (RP + RQ < 32 ? RP + RQ : 32)>(acc, W, dq);
            if (RP + RQ >= RL) barrive<B_BT, 256>();
            CUT(pa);
            PUT_B();
            const uint32_t tb = lds32(SUM + 272 + 28 + zz);
            CUT(pa);
            PROF(11);
            if (RP + RQ < RL) { wg_run<RP + RQ, RL>(acc, W, dq); __syncwarp(); barrive<B_BT, 256>(); __syncwarp(); }
            wg_run<(RP + RQ < RL ? RL : RP + RQ), 32>(acc, W, dq);
            CUT(pa);
            AGAIN(5, ld_g128(x, at(u_rl + opq(ro), rbhi)); ld_g128(x + 4, at(u_rl + opq(ro2), rbhi)); sts128(RS + ro, make_uint4(x[0], x[1], x[2], x[3])); sts128(RS + ro2, make_uint4(x[4], x[5], x[6], x[7]));
                     CUT(pa); __syncwarp(); SUM_R(); PUT_B(), bad)
            #define REQ_B() if (w8 == 3) { TRC(13, gtime() - tb); wait_g(tb, t16); GET_B(0); PROFW(13, 3); }
            if (!BL) REQ_B();
            const uint32_t ps = opq(pb & 0xFFFF), ps2 = opq(ps ^ HI8);
            char* const qd0 = TOK_DST() + ps; char* const qd1 = TOK_DST() + ps2;
            TAGM();
            wg_wait<0>();
            pack_tag(acc, u, taus, tm);
            #pragma unroll
            for (int i = 0; i < 8; i++) u[i] = opq(u[i]);
            CUT(pa);
            if (BL) REQ_B();
            bsync<B_S0, 128>();
            st_if(seg < NSEG, qd0, u); st_if(seg < NSEG, qd1, u + 4);
            if (XDL >= 200 && XDL < 300 && w8 == 1) { CUT(pb); DELAY(XDL - 200); load_x(tmX, c, seg + 1, (s & 1) ? XT : XT2); }
            PROF(12);
        } else {
            #define LAST() __reduce_max_sync(~0u, max(max(an[0], an[1]), max(an[2], an[3])))
            PK_O();
            CUT(pa);
            if (s == NSEG - 1) { ST_O(); break; }
            PROF(8);
            if (w8 != 7) {
                load_frag<16 - EV, 16 - EV + TA0, 2048>(VEB + t16, T);
                mbar_wait(MB_KV, s & 1);
                AGAIN(0, refetch_kv(c, s + 1, w8 - 4, l16), kv_stale(w8 - 4, l16, phase(s + 1)))
            } else {
                uint32_t tr = LAST();
                AGAIN(8, ld_g128(an, at(u_ta + l16, rbhi)); tr = LAST(), late(stale<2, 1>(an, s), stale<2, 1>(an + 2, s), 31))
                tr = (tr & ~31u) + P(0);
                TRC(14, gtime() - tr);
                wait_g(tr, t16);
                if (R4) { for (int i = 0; i < 4; i++) bulk_copy(RS + i * 1024, at(u_rl + i * 1024, rbhi), 1024, MB_R); }
                else bulk_copy(RS, at(u_rl, rbhi), 4096, MB_R);
                PROFW(14, 3);
                sts32(SUM + 272 + 28, tr + P(1));
                load_frag<16 - EV, 16 - EV + TA0, 2048>(VEB + t16, T);
                if (XDL < 100) { CUT(pb); DELAY(XDL); load_x(tmX, c, seg + 1, (s & 1) ? XT : XT2); }
            }
            CUT(pa);
            bsync<B_VX, 256>();
            lds128u(u, SC - 2048 + opq(t16)); lds128u(u + 4, SC + opq(t16));
            CUT(pa);
            ST_O();
            CUT(pa);
            load_frag<16 - EV + TA0, 16 - EV + TA, 2048>(VEB + t16, T);
            acc_init(acv, u);
            #pragma unroll
            for (int i = 0; i < 16; i++) acv[i] = opqf(acv[i]);
            const uint32_t ps = opq(pb & 0xFFFF), ps2 = opq(ps ^ HI8);
            CUT(pa);
            PROF(9);
            if (XDL == 100 && w8 == 7) load_x(tmX, c, seg + 1, (s & 1) ? XT : XT2);
            bsync<B_BT, 256>();
            CUT(pa);
            wg_run<0, 3>(acc, W, dq);
            PROF(11);
            wg_run<3, NT, true>(acc, W, dq);
            __syncwarp();
            load_frag<16 - EV + TA, 16, 2048>(VEB + t16, T);
            __syncwarp();
            wg_run<NT, NB>(acc, W, dq);
            char* const qd0 = TOK_DST() + ps; char* const qd1 = TOK_DST() + ps2;
            TAGM();
            wg_run<NB, 32>(acc, W, dq);
            wg_run<0, 5, true>(acv, T, dv);
            wg_wait<1>();
            PROF(12);
            pack_tag(acc, u, taus, tm);
            #pragma unroll
            for (int i = 0; i < 8; i++) u[i] = opq(u[i]);
            CUT(pa);
            wg_run<5, 16 - EV>(acv, T, dv);
            __syncwarp();
            st_if(seg < NSEG, qd0, u); st_if(seg < NSEG, qd1, u + 4);
            __syncwarp();
            wg_run<16 - EV, 16>(acv, T, dv);
            CUT(pa);
            PROF(10);
            wg_wait<0>();
            PROF(13);
            pack_tag(acv, u, taus, tm);
            st_if(seg < NSEG, qd0 + 16384, u); st_if(seg < NSEG, qd1 + 16384, u + 4);
        }
        sb++;
        u_rs ^= 1 << 20; u_rl ^= 1 << 20; u_bs ^= 1 << 20; u_bl ^= 1 << 20; u_x ^= 1 << 20; u_xs ^= 1 << 20; u_ta ^= 1 << 20; u_rp ^= 1 << 20; u_og += 262144;
    }
}

namespace ck {
constexpr uint32_t UPL = 144 * 16 + 64, UCH = 2 * UPL;
constexpr uint32_t FCP = 4160, FCH = 2 * FCP;
template <int NW> struct At { static constexpr uint32_t K = NW == 2 ? mk::XT : mk::SB, V = K + 32768, F = NW == 2 ? V : V + 32768, U = F + 8 / NW * FCH; };
static_assert(At<2>::U + 4 * UCH <= mk::OB && At<1>::U + 8 * UCH <= mk::OB, "");
}
struct ConvIn { const bf16 *shift_k, *ssm_k, *ssm_D; };
template <int NW> struct ConvRaw { uint4 f[8 / NW], sk[4 / NW]; uint32_t fn, d; };
template <int NW> __device__ __forceinline__ void strip_request(const CUtensorMap* tmK, int grp) {
    mbar_expect(mk::MB_C, 65536);
    #pragma unroll 1
    for (int i = 0; i < 16; i++) tma3d(ck::At<NW>::K + i * 4096, tmK + (i >> 3), grp * 8, 0, i & 7, mk::MB_C);
}
template <int NW> __device__ __forceinline__ void conv_load(ConvRaw<NW>& r, const ConvIn& in, int ch0) {
    const int tid = threadIdx.x, w = tid >> 5, ch = ch0 + w / NW, e = w % NW;
    const bf16* fp = in.ssm_k + (size_t)ch * SEQ + e * 1024;
    #pragma unroll
    for (int i = 0; i < 8 / NW; i++) r.f[i] = __ldg((const uint4*)fp + (tid & 31) + 32 * i);
    r.fn = e == NW - 1 ? 0 : __ldg((const uint32_t*)(fp + 1024));
    r.d = __ldg((const unsigned short*)in.ssm_D + ch);
    #pragma unroll
    for (int i = 0; i < 4 / NW; i++) r.sk[i] = __ldg((const uint4*)(in.shift_k + ch0 * 4) + i);
}
template <int NW> __device__ __forceinline__ void kv_build(const ConvRaw<NW>& r, int ch0) {
    using namespace ck;
    const int tid = threadIdx.x;
    if (tid < 32 * 8 / NW) sts128(At<NW>::U + (tid >> 4) * UPL + (tid & 15) * 16, make_uint4(0, 0, 0, 0));
    #pragma unroll
    for (int hf = 0; hf < 2 / NW; hf++) {
        const uint32_t a = tid * 16 + (ch0 & 4) * 2 + hf * 8;
        float2 kr[11], vr[8];
        #pragma unroll
        for (int i = 0; i < 11; i++) { kr[i] = lds64f(At<NW>::K + ((i + 5) & 7) * 4096 - (i < 3) * 16 + a); if (i < 3 && !tid) kr[i] = make_float2(0.f, 0.f); }
        #pragma unroll
        for (int i = 0; i < 8; i++) vr[i] = lds64f(At<NW>::V + i * 4096 + a);
        #pragma unroll
        for (int ch = 0; ch < 4; ch++) {
            const uint32_t s01 = ((const uint32_t*)r.sk)[8 * hf + 2 * ch], s23 = ((const uint32_t*)r.sk)[8 * hf + 2 * ch + 1];
            const float sk[4] = {bflo(s01), bfhi(s01), bflo(s23), bfhi(s23)};
            float kf[11], kv[8];
            #pragma unroll
            for (int i = 0; i < 11; i++) { const uint32_t wd = __float_as_uint((ch & 2) ? kr[i].y : kr[i].x); kf[i] = (ch & 1) ? bfhi(wd) : bflo(wd); }
            #pragma unroll
            for (int i = 0; i < 8; i++) {
                const uint32_t wv = __float_as_uint((ch & 2) ? vr[i].y : vr[i].x);
                kv[i] = fmaf(kf[i + 3], sk[0], fmaf(kf[i + 2], sk[1], fmaf(kf[i + 1], sk[2], kf[i] * sk[3]))) * ((ch & 1) ? bfhi(wv) : bflo(wv));
            }
            sts128(At<NW>::U + (hf * 4 + ch) * UCH + (tid & 1) * UPL + (16 + (tid >> 1)) * 16,
                   make_uint4(pack2(kv[0], kv[1]), pack2(kv[2], kv[3]), pack2(kv[4], kv[5]), pack2(kv[6], kv[7])));
        }
    }
}
template <int NW> __device__ __forceinline__ void conv_filter(const ConvRaw<NW>& r) {
    using namespace ck;
    constexpr int N = 8 / NW;
    const int w = threadIdx.x >> 5, lane = threadIdx.x & 31, e = w % NW;
    const uint32_t fb = At<NW>::F + w / NW * FCH;
    if (!e && lane < 8) { sts32(fb + 4128 + lane * 4, 0); sts32(fb + FCP + 4128 + lane * 4, lane ? 0 : r.f[0].x & 0xFFFFu); }
    #pragma unroll
    for (int i = 0; i < N; i++) {
        const int vi = e * 128 + lane + 32 * i;
        const uint4 x = r.f[i];
        const uint32_t a = __shfl_down_sync(~0u, x.x, 1), b = i < N - 1 ? __shfl_sync(~0u, r.f[i < N - 1 ? i + 1 : i].x, 0) : r.fn;
        const uint32_t nxt = lane == 31 ? b : a;
        const uint32_t ea = fb + (2056 - 8 * vi) * 2;
        sts128(ea, make_uint4(__byte_perm(x.w, 0, 0x1032), __byte_perm(x.z, 0, 0x1032), __byte_perm(x.y, 0, 0x1032), __byte_perm(x.x, 0, 0x1032)));
        sts128(ea + FCP, make_uint4(__byte_perm(nxt, x.w, 0x7610), __byte_perm(x.w, x.z, 0x7610), __byte_perm(x.z, x.y, 0x7610), __byte_perm(x.y, x.x, 0x7610)));
    }
}
template <int NW> __device__ __forceinline__ void conv_mma(int ch0, uint32_t d, uint32_t zero) {
    using namespace ck;
    constexpr int N = 16 / NW;
    const int w = threadIdx.x >> 5, lane = threadIdx.x & 31, ch = w / NW, e = w % NW, g = lane >> 2, t = lane & 3;
    float acc[N][4] = {};
    uint32_t fa = At<NW>::F + ch * FCH + ((g & 1) ? (2063 - g + 2 * t) * 2 : FCP + (2064 - g + 2 * t) * 2);
    uint32_t ua = At<NW>::U + ch * UCH + ((lane >> 3) & 1) * UPL + (24 + (e - NW) * 8 + (lane >> 4) * 8 + (lane & 7)) * 16;
    uint32_t Fr[32], A[2][8], yo = (ch0 + ch) * 512 + e * 32 + t * 8 + g;
    const uint32_t t16 = lane | zero;
    #define LD_U(m0, m1) _Pragma("unroll") for (int m = m0; m < m1; m++) ldsm4(Fr[4 * m], Fr[4 * m + 1], Fr[4 * m + 2], Fr[4 * m + 3], ua + m * 256)
    #define LD_F(b, o, p) _Pragma("unroll") for (int i = 0; i < 2; i++) { const uint32_t x_ = fa - (o) * 32 - (i ? 15 - (p) : (p)) * 256; \
        A[b][4 * i] = lds32(x_); A[b][4 * i + 1] = lds32(x_ - 16); A[b][4 * i + 2] = lds32(x_ + 16); }
    #define ROW(a, q, j0, j1) _Pragma("unroll") for (int j = j0; j < j1; j++) mmaq(acc[j], a, Fr[2 * (NW * j + NW - 1 - (q))], Fr[2 * (NW * j + NW - 1 - (q)) + 1])
    LD_U(0, 8);
    LD_F(0, 0, 0);
    {
        const uint32_t da = (g >> 1) == t ? d << ((g & 1) * 16) : 0, D[4] = {da, zero, zero >> 1, da ^ zero};
        ROW(D, 0, 0, N);
    }
    #pragma unroll 1
    for (int r = 0; r < 8; r++) {
        ua -= 16;
        #pragma unroll
        for (int p = 0; p < 8; p++) {
            uint32_t* const a = A[p & 1];
            a[3] = a[0] ^ zero; a[7] = a[4] ^ zero;
            LD_F(~p & 1, p == 7, (p + 1) & 7);
            if (p >= 2 && !(p & 1)) { LD_U(8 - p / 2, 9 - p / 2); }
            const int j0 = p / NW, j1 = (15 - p) / NW, jm = j0 + (j1 - j0) / 2;
            ROW(a, p, j0, jm);
            if (CC) CUT(yo);
            _Pragma("unroll") for (int j2 = j1; j2 < N; j2++) { ROW(a + 4, 15 - p, j2, j2 + 1); if (CC) CUT(yo); }
            ROW(a, p, jm, j1);
            if (CC) CUT(yo);
            _Pragma("unroll") for (int j2 = j1; j2 < N; j2++) { ROW(a, p, j2, j2 + 1); if (CC) CUT(yo); }
        }
        LD_U(0, 5);
        fa -= 32;
    }
    uint2* y = (uint2*)g_Y + yo;
    #pragma unroll
    for (int j = 0; j < N; j++) {
        const uint32_t p0 = pack2(acc[j][0], acc[j][2]), p1 = pack2(acc[j][1], acc[j][3]), x = __shfl_xor_sync(~0u, (g & 1) ? p0 : p1, 4);
        const uint32_t lo = (g & 1) ? x : p0, hi = (g & 1) ? p1 : x;
        y[j * 32 * NW] = make_uint2(__byte_perm(lo, hi, 0x5410), __byte_perm(lo, hi, 0x7632));
    }
}
__device__ __noinline__ void spare(const CUtensorMap* tmK, const ConvIn in, int i, uint32_t zero) {
    const int w = __shfl_sync(~0u, threadIdx.x >> 5, 0);
    ConvRaw<1> raw;
    #pragma unroll 1
    for (int grp = 56 + i, n = 0; grp < NSP; grp += 4, n++) {
        if (n) { mbar_wait(mk::MB_C, ~n & 1); kv_build<1>(raw, grp * 8); conv_filter<1>(raw); }
        const uint32_t d = raw.d;
        asm volatile("fence.proxy.async.shared::cta;" ::: "memory");
        __syncthreads();
        if (grp + 4 < NSP) {
            if (w == 0 && elect()) { mbar_expect(mk::MB_C, 65536); for (int j = 0; j < 2; j++) tma3d(ck::At<1>::K + j * 32768, tmK + 2 + j, grp * 8 + 32, 0, 0, mk::MB_C); }
            __syncwarp();
            conv_load<1>(raw, in, grp * 8 + 32);
        }
        if (n) conv_mma<1>(grp * 8, d, zero);
        __syncthreads();
    }
}

__device__ __forceinline__ uint32_t round_trip(char* a, int n) {
    uint32_t best = 0x7FFFu;
    #pragma unroll 1
    for (int i = 0; i < n; i++) {
        uint32_t v; const uint32_t t0 = clk();
        asm volatile("atom.relaxed.gpu.global.exch.b32 %0, [%1], %2;" : "=r"(v) : "l"(a), "r"(i) : "memory");
        if (v == 0x7FC1A5A5u) g_err = 2;
        best = min(best, clk() - t0);
    }
    return (__popc((uint32_t)(uintptr_t)a & HOME_BITS) & 1) ? best << 16 | 0x7FFFu : best | 0x7FFF0000u;
}
__device__ __forceinline__ int place(int by_sm) {
    uint32_t sm = blockIdx.x;
    if (by_sm) asm volatile("mov.u32 %0, %%smid;" : "=r"(sm));
    const uint32_t g = sm < 64 ? (sm & 15) >> 1 : 1 + (sm - 64) % 14 / 2, j = sm < 64 ? sm >> 4 : 4 + (sm - 64) / 14;
    return sm < 120 ? (g ? g * 16 - 8 : 0) + j * 2 + (sm & 1) : sm;
}
__device__ __forceinline__ void publish(char* rb, int p) {
    const int t = threadIdx.x, i = p * 4 + (t >> 6);
    char* line = rb + RB_P + (i & 31) * 128 + (i >> 5) * 8192 + (t & 32) * 128;
    if ((t & 31) < 2) st_g128(line + (t & 1) * 16, 0, 0, 0, 0);
    __syncwarp();
    if (!(t & 31)) sts32(mk::SUM + (t >> 3), round_trip(line, NPR));
    __syncthreads();
    if (t == 32) {
        const uint4 x = lds128(mk::SUM), y = lds128(mk::SUM + 16);
        st_g32(g_cls + p, 0x80000000u | __vminu2(__vminu2(__vminu2(x.x, x.y), __vminu2(x.z, x.w)), __vminu2(__vminu2(y.x, y.y), __vminu2(y.z, y.w))));
    }
}
__device__ __forceinline__ uint32_t survey(uint32_t& x) {
    const int lane = threadIdx.x & 31;
    uint32_t a[4], b[2];
    int n = 0;
    do { ld_g128(a, g_cls + lane * 4); ld_g64(b, g_cls + 120 + lane % 6 * 2); } while (__any_sync(~0u, !((a[0] & a[1] & a[2] & a[3] & b[0] & b[1]) >> 31)) && ++n < SPIN_LIMIT);
    const uint32_t m = __vminu2(__vminu2(a[0], a[1]), __vminu2(a[2], a[3])), e = __vminu2(b[0], b[1]);
    const uint32_t M = __ballot_sync(~0u, (m >> 16 & 0x7FFF) < (m & 0xFFFF)) & 0x3FFFFFFF, E = __ballot_sync(~0u, (e >> 16 & 0x7FFF) < (e & 0xFFFF)) & 63;
    const int x0 = min(max(max(__popc(M) - 14, 2 - __popc(E) / 2), 0), min(2, (6 - __popc(E)) / 2));
    x = E | x0 << 8;
    return M | (x0 < 1) << 30 | (x0 < 2) << 31;
}
__device__ __forceinline__ int role(int p, uint32_t x) {
    const int i = (p - 120) >> 1, x0 = x >> 8, side = x >> i & 1, r = __popc((side ? x : ~x) & ((1 << i) - 1)), e0 = 6 - __popc(x & 63);
    const int pair = !side ? (r < 2 * x0 ? r : 4 + r - 2 * x0) : (r < 4 - 2 * x0 ? 2 * x0 + r : e0 + r);
    return 120 + 2 * pair + (p & 1);
}
__device__ __forceinline__ void tma_prefetch(const CUtensorMap* m, int c0, int c1) {
    asm volatile("cp.async.bulk.prefetch.tensor.2d.L2.global [%0, {%1, %2}];" :: "l"(m), "r"(c0), "r"(c1) : "memory");
}

struct KVMaps { CUtensorMap m[4]; };
__global__ void __launch_bounds__(256, 1)
main_kernel(const __grid_constant__ CUtensorMap tmWq, const __grid_constant__ CUtensorMap tmWk, const __grid_constant__ CUtensorMap tmWv,
            const __grid_constant__ CUtensorMap tmWo, const __grid_constant__ CUtensorMap tmX,
            const __grid_constant__ KVMaps tmK, const bf16* __restrict__ mem0,
            const __grid_constant__ ConvIn in, const __grid_constant__ MainParams prm) {
    using namespace mk;
    extern __shared__ __align__(1024) uint8_t smem_raw[];
    if (smem_u32(smem_raw) != SB) __trap();
    TL(0); TL(2);
    const int tid0 = threadIdx.x, w8 = __shfl_sync(~0u, tid0 >> 5, 0), wg = w8 >> 2;
    const int p = __shfl_sync(~0u, place(prm.by_sm), 0);
    if (w8 == 0 && elect()) {
        for (int i = 0; i < 9; i++) mbar_init(BAR + i * 8, 1);
        asm volatile("fence.mbarrier_init.release.cluster;" ::: "memory");
        asm volatile("fence.proxy.async.shared::cta;" ::: "memory");
        sts32(SUM + 256, 0); sts32(SUM + 268, 0); mbar_arrive(MB_B);
    }
    if (tid0 >= 252) asm volatile("prefetch.tensormap [%0];" :: "l"(tid0 == 252 ? &tmWq : tid0 == 253 ? &tmWk : tmK.m + (tid0 & 1)) : "memory");
    __syncwarp();
    const uint64_t xd = c_xd[w8 * 12 + (tid0 & 8)];
    publish(prm.rb, p);
    if (!xd) __trap();
    TLX(16);
    int c = p;
    asm volatile("griddepcontrol.launch_dependents;" ::: "memory");
    if (p >= 120) {
        uint32_t x;
        survey(x);
        c = role(p, x);
        TLX(17);
        if (c >= 128) { spare(tmK.m, in, c - 128, prm.zero); TLX(18); return; }
    }
    const int kap = c & 1;
    uint32_t m0[8];
    {
        ConvRaw<2> raw;
        conv_load<2>(raw, in, p * 4);
        #pragma unroll
        for (int i = 0; i < 8; i++) m0[i] = __ldg((const uint32_t*)(mem0 + i * DM + kap * 512) + tid0);
        if (tid0 < 16) g_gate[c * 16 + tid0] = -1.f;
        if (w8 == 0 && elect()) {
            if (p < 120) strip_request<2>(tmK.m, p >> 1);
            mbar_expect(MB_WQ, 65536); mbar_expect(MB_WK, 65536);
            for (int i = 0; i < 2; i++) { tma2d(WO + i * 32768, &tmWq, (c >> 1) * 64, kap * 512 + i * 256, MB_WQ); tma2d(WV + i * 32768, &tmWk, (c >> 1) * 64, kap * 512 + i * 256, MB_WK); }
        }
        __syncwarp();
        if (p < 120) {
            mbar_wait(MB_C, 0);
            TLX(22);
            kv_build<2>(raw, p * 4);
        }
        __syncthreads();
        TLX(14);
        if (w8 == 0 && elect()) {
            mbar_expect(MB_X, 32768); tma3d(XT, &tmX, 0, 32, kap * 8, MB_X);
            for (int i = 0; i < 4; i++) tma_prefetch(&tmWo, (c & 3) * 256 + i * 64, (c >> 2) * DH);
            for (int i = 0; i < 2; i++) tma_prefetch(&tmWv, (c >> 1) * 64, kap * 512 + i * 256);
        }
        __syncwarp();
        if (p < 120) {
            conv_filter<2>(raw);
            __syncthreads();
            TL(9);
            conv_mma<2>(p * 4, raw.d, prm.zero);
        }
    }
    TL(1);
    asm volatile("fence.proxy.async.shared::cta;" ::: "memory");
    __syncthreads();
    if (w8 == 0 && elect()) { mbar_expect(MB_KV, 32768); tma3d(TK, &tmX, 0, 0, kap * 8, MB_KV); }
    #pragma unroll
    for (int i = 0; i < 2; i++) {
        const uint32_t e = i ? 0x7632 : 0x5410;
        sts128(MEM + tid0 * 32 + i * 16, make_uint4(__byte_perm(m0[0], m0[1], e), __byte_perm(m0[2], m0[3], e), __byte_perm(m0[4], m0[5], e), __byte_perm(m0[6], m0[7], e)));
    }
    uint32_t W[128], T[64];
    mbar_wait(wg ? MB_WK : MB_WQ, 0);
    TLX(19);
    load_tile<0, 32>(tile_off(tid0 & 31, 2 * (w8 & 3)) + (wg ? WV : WO), W);
    __syncthreads();
    if (w8 == 0 && elect()) {
        mbar_expect(MB_WO, 65536);
        for (int i = 0; i < 4; i++) tma2d(WO + i * 16384, &tmWo, (c & 3) * 256 + i * 64, (c >> 2) * DH, MB_WO);
        mbar_expect(MB_WV, 65536); tma2d(WV, &tmWv, (c >> 1) * 64, kap * 512, MB_WV); tma2d(WV + 32768, &tmWv, (c >> 1) * 64, kap * 512 + 256, MB_WV);
    }
    uint32_t t16 = tid0 * 16, pa, pb;
    {
        const int lane = tid0 & 31, w = w8 & 3, g = lane >> 2, t = lane & 3;
        auto vec = [](int hf, int gg, int ch) { return hf * 512 + (gg >> 1) * 128 + (gg & 1) * 64 + ((ch ^ (gg >> 1) ^ (hf << 1)) << 4); };
        const int kg = ((lane >> 3) & 1) * 4 + ((lane & 7) >> 1);
        pa = wg ? w * 1024 + vec((lane >> 3) & 1, lane & 7, lane >> 4)
                : ((lane >> 4) * 4096 + w * 1024 + vec(lane & 1, kg, 2 * (w & 1))) | ((lane & 8) * 256 + w * 256 + (lane & 1) * 128 + ((((lane >> 4) ^ (lane & 1)) * 4 + ((lane & 7) >> 1)) << 4)) << 16;
        pb = (wg ? w * 1024 + vec(0, g, t) : t * 4096 + w * 256 + g * 16) | (w * 256 + t * 64 + (g & 3) * 8 + (g >> 2) * 4) << 16;
    }
    int budget = SPIN_LIMIT;
    const uint32_t ps = pb & 0xFFFF;
    #define ST_TOK(o) do { TAGM(); pack_tag(acc, u, 1, tm); st_if(true, tok_dst(c, seg, wg) + ((o) + ps), u); st_if(true, tok_dst(c, seg, wg) + ((o) + (ps ^ HI8)), u + 4); } while (0)
    #pragma unroll 1
    for (int seg = 1; seg >= 0; seg--) {
        float acc[16];
        uint32_t u[8];
        mbar_wait(seg ? MB_X : MB_KV, 0);
        wg_run<0, 32>(acc, W, c_xd + (seg ? 0 : 64));
        wg_wait<0>();
        ST_TOK(0);
    }
    {
        mbar_wait(MB_WO, 0);
        TLX(20);
        const int lane = tid0 & 31;
        const uint32_t a = (tid0 >> 6) * 16384 + tile_off(lane, (w8 & 1) * 4) + WO;
        #pragma unroll
        for (int i = 0; i < 16; i++) ldsm4t(T[4 * i], T[4 * i + 1], T[4 * i + 2], T[4 * i + 3], ((i & 2) ? a ^ 32 : a) + ((i >> 2) + 4 * (i & 1)) * 2048);
        __syncthreads();
        const uint32_t d = WO + w8 * 512 + ((lane >> 3) * 4 + (lane & 3)) * 16 + ((lane >> 2) & 1) * 4;
        #pragma unroll
        for (int i = 0; i < 64; i++) sts32(d + (i >> 2) * 4096 + (i & 1) * 256 + (i & 2) * 4, T[i]);
    }
    mbar_wait(MB_WV, 0);
    TLX(21);
    load_tile<0, 16>(tile_off(tid0 & 31, 2 * (w8 & 3)) + wg * 32768 + WV, T);
    #pragma unroll 1
    for (int seg = 0; seg < 2; seg++) {
        float acc[16];
        uint32_t u[8];
        wg_run<0, 16>(acc, T, c_xd + (seg ? 0 : 64) + wg * 16);
        wg_wait<0>();
        const uint32_t x = SC + seg * 4096 + (t16 & 2047);
        if (!wg) { qk_pack(acc, u); sts128(x, make_uint4(u[0], u[1], u[2], u[3])); sts128(x + 2048, make_uint4(u[4], u[5], u[6], u[7])); }
        __syncthreads();
        if (wg) { lds128u(u, x); lds128u(u + 4, x + 2048); acc_add(acc, u); ST_TOK(16384); }
    }
    if (w8 == 1) { bulk_expect(MB_X, 32768); load_x(&tmX, c, 2, XT); }
    uint32_t u_rs, u_rl, u_bs, u_bl;
    const uint32_t rbhi = (uint32_t)((uintptr_t)prm.rb >> 32);
    {
        const int lane = tid0 & 31, h = c >> 2, j = c & 3;
        uint32_t cl;
        const uint32_t M = survey(cl), below = (1u << h) - 1;
        const int pos = ((M >> h) & 1) ? 32 - __popc(M) + __popc(M & below) : __popc(~M & below), G = pos >> 4, rk = pos & 15;
        auto half = [&](uint32_t off) { return (uint32_t)(uintptr_t)prm.rb + off + ((__popc(off & HOME_BITS) ^ G) & 1) * 4096; };
        auto rpair = [&](int m) { return RB_R + (j << 16) + ((m & 1) << 13) + (((m >> 1) & 3) << 14) + ((m >> 3) << 18); };
        u_rs = (half(rpair(2 * w8)) ^ (G << 12)) + h * 128 + (h & 7) * 16;
        u_rl = half(rpair(rk));
        u_bs = (uint32_t)(uintptr_t)prm.rb + RB_B + ((j & 1) << 13) + ((j >> 1) << 16) + rk * 256 + G * 128 + (w8 & 3) * 32;
        u_bl = half(RB_B + (kap << 16));
        if (w8 == 0) {
            const char* v0 = kv_src(c, 0) + 16384 + lane * 128 + (lane & 3) * 4;
            do cl = ld_g32(v0) & ld_g32(v0 + 4096) & ld_g32(v0 + 8192) & ld_g32(v0 + 12288); while (__any_sync(~0u, !(cl & 1)) && --budget > 0);
            get_kv(c, 0);
        }
    }
    mbar_wait(MB_KV, 1);
    if (w8 < 3) while (kv_stale(w8, t16 & 0x1F0, 1) && --budget > 0) refetch_kv(c, 0, w8, t16 & 0x1F0);
    asm volatile("fence.proxy.async.shared::cta;" ::: "memory");
    TLX(7);
    __syncwarp();
    const Ctx cx = {u_rs, u_rl, u_bs, u_bl, (uint32_t)(uintptr_t)prm.rb, rbhi, w8, c};
    if (wg) steps<1>(W, T, t16, pa, pb, cx, &tmX, prm); else steps<0>(W, T, t16, pa, pb, cx, &tmX, prm);
    TLX(3);
}

namespace ok {
constexpr int STAGES = 4;
constexpr uint32_t STG = 49152, TOTAL = STAGES * STG + 32768 + 768, NOG = 0xBF800000u;
}
#define R8(o) F4(d, o), F4(d, o + 4)
__device__ __forceinline__ void wgmma_n256_ss_tt(float* d, uint64_t da, uint64_t db, int accum) {
    asm volatile("{.reg .pred p; setp.ne.b32 p, %130, 0;\n"
        "wgmma.mma_async.sync.aligned.m64n256k16.f32.bf16.bf16 {%0,%1,%2,%3,%4,%5,%6,%7,%8,%9,%10,%11,%12,%13,%14,%15,"
        "%16,%17,%18,%19,%20,%21,%22,%23,%24,%25,%26,%27,%28,%29,%30,%31,%32,%33,%34,%35,%36,%37,%38,%39,%40,%41,%42,%43,%44,%45,%46,%47,"
        "%48,%49,%50,%51,%52,%53,%54,%55,%56,%57,%58,%59,%60,%61,%62,%63,%64,%65,%66,%67,%68,%69,%70,%71,%72,%73,%74,%75,%76,%77,%78,%79,"
        "%80,%81,%82,%83,%84,%85,%86,%87,%88,%89,%90,%91,%92,%93,%94,%95,%96,%97,%98,%99,%100,%101,%102,%103,%104,%105,%106,%107,%108,%109,%110,%111,"
        "%112,%113,%114,%115,%116,%117,%118,%119,%120,%121,%122,%123,%124,%125,%126,%127}, %128, %129, p, 1, 1, 1, 1;}"
        : R8(0), R8(8), R8(16), R8(24), R8(32), R8(40), R8(48), R8(56), R8(64), R8(72), R8(80), R8(88), R8(96), R8(104), R8(112), R8(120)
        : "l"(da), "l"(db), "r"(accum));
}
#undef R8
__global__ void __cluster_dims__(2, 1, 1) __launch_bounds__(320, 1)
out_kernel(const __grid_constant__ CUtensorMap tmO, const __grid_constant__ CUtensorMap tmWo, const __grid_constant__ CUtensorMap tmA,
           const __grid_constant__ CUtensorMap tmOut, const __grid_constant__ CUtensorMap tmQ, const bf16* __restrict__ q, const bf16* __restrict__ gate_w) {
    using namespace ok;
    extern __shared__ __align__(1024) uint8_t smem_raw[];
    const uint32_t SB = smem_u32(smem_raw), AT = SB + STAGES * STG, BAR = AT + 32768;
    if (SB & 1023) __trap();
    const int tid = threadIdx.x, w = tid >> 5, lane = tid & 31;
    const int rank = blockIdx.x & 1, mt = blockIdx.x >> 3, nt = (blockIdx.x >> 1) & 3;
    const uint32_t full = BAR, empty = BAR + 64, afull = BAR + 128;
    if (tid == 0) {
        for (int i = 0; i < STAGES; i++) { mbar_init(full + i * 8, 1); mbar_init(empty + i * 8, 8); }
        mbar_init(afull, 2);
        asm volatile("fence.mbarrier_init.release.cluster;" ::: "memory");
    }
    __syncthreads();
    asm volatile("griddepcontrol.wait;" ::: "memory");
    if (blockIdx.x == 0 && tid < 160) g_cls[tid] = 0;
    TL(4);
    if (w >= 8) {
        if (w == 9) {
            uint4 gw[4];
            #pragma unroll
            for (int i = 0; i < 4; i++) gw[i] = __ldg((const uint4*)gate_w + lane + 32 * i);
            #pragma unroll 2
            for (int row = blockIdx.x * 16; row < blockIdx.x * 16 + 16; row++) {
                float a = 0.f;
                #pragma unroll
                for (int i = 0; i < 4; i++) {
                    const uint4 x = __ldg((const uint4*)(q + (size_t)row * DM) + lane + 32 * i);
                    #pragma unroll
                    for (int j = 0; j < 4; j++) { const uint32_t gg = ((const uint32_t*)&gw[i])[j], u = ((const uint32_t*)&x)[j]; a = fmaf(bflo(u), bflo(gg), fmaf(bfhi(u), bfhi(gg), a)); }
                }
                #pragma unroll
                for (int o = 16; o; o >>= 1) a += __shfl_xor_sync(~0u, a, o);
                if (lane == 0) st_g32(g_gate + row, __float_as_uint(1.f / (1.f + __expf(-a))));
            }
            uint32_t x[4];
            int n = 0;
            do ld_g128(x, g_gate + mt * 128 + lane * 4); while ((x[0] == NOG || x[1] == NOG || x[2] == NOG || x[3] == NOG) && ++n < SPIN_LIMIT);
            sts128(BAR + 256 + lane * 16, make_uint4(x[0], x[1], x[2], x[3]));
        } else if (lane == 0) {
            int st = 0, ph = 1;
            for (int kb = 0; kb < 32; kb++) {
                if (kb >= STAGES) mbar_wait(empty + st * 8, ph);
                mbar_expect(full + st * 8, STG);
                tma3d(SB + st * STG, &tmO, 0, (rank * 32 + kb) * 2, mt * 16, full + st * 8);
                tma3d(SB + st * STG + 16384, &tmWo, 0, (rank * 32 + kb) * 64, nt * 4, full + st * 8);
                if (kb == STAGES - 1) { mbar_expect(afull, 32768); tma3d(AT, &tmA, 0, (nt * 2 + rank) * 128, mt * 2, afull); }
                if (kb >> 1 == 4) asm volatile("cp.async.bulk.prefetch.tensor.5d.L2.global [%0, {%1, %2, %2, %2, %3}];" :: "l"(&tmQ), "r"(nt * 256 + rank * 128 + (kb & 1) * 64), "r"(0), "r"(mt * 4) : "memory");
                if (++st == STAGES) { st = 0; ph ^= 1; }
            }
            mbar_wait(empty, ph);
            mbar_expect(afull, 32768);
            for (int hf = 0; hf < 2; hf++)
                asm volatile("cp.async.bulk.tensor.5d.shared::cluster.global.mbarrier::complete_tx::bytes [%0], [%1, {%3, %4, %4, %4, %5}], [%2];"
                    :: "r"(SB + hf * 16384), "l"(&tmQ), "r"(afull), "r"(nt * 256 + rank * 128 + hf * 64), "r"(0), "r"(mt * 4) : "memory");
        }
        __syncwarp();
        asm volatile("barrier.cluster.arrive.aligned; barrier.cluster.wait.aligned;" ::: "memory");
        asm volatile("barrier.cluster.arrive.aligned; barrier.cluster.wait.aligned;" ::: "memory");
    } else {
        const int wg = w >> 2, g = lane >> 2;
        float acc[128];
        int st = 0, ph = 0, pst = 0;
        #pragma unroll 1
        for (int kb = 0; kb < 32; kb++) {
            mbar_wait(full + st * 8, ph);
            const uint64_t da = mkdesc(SB + st * STG + wg * 8192, 128, 1024, 0), db = mkdesc(SB + st * STG + 16384, 8192, 1024, 1);
            wg_fence();
            #pragma unroll
            for (int ks = 0; ks < 4; ks++) wgmma_n256_ss_tt(acc, da + ks * 16, db + ks * 128, (kb | ks) != 0);
            wg_commit();
            wg_wait<1>();
            if (kb > 0 && lane == 0) mbar_arrive(empty + pst * 8);
            pst = st;
            if (++st == STAGES) { st = 0; ph ^= 1; }
        }
        wg_wait<0>();
        TLX(12);
        asm volatile("barrier.cluster.arrive.aligned; barrier.cluster.wait.aligned;" ::: "memory");
        uint32_t peer;
        asm volatile("mapa.shared::cluster.u32 %0, %1, %2;" : "=r"(peer) : "r"(SB + 65536 + tid * 16), "r"(rank ^ 1));
        #define SND(e) pack2(rank ? acc[8 * i + (e)] : acc[64 + 8 * i + (e)], rank ? acc[8 * i + (e) + 1] : acc[65 + 8 * i + (e)])
        #pragma unroll
        for (int i = 0; i < 8; i++)
            asm volatile("st.shared::cluster.v4.b32 [%0], {%1,%2,%3,%4};" :: "r"(peer + i * 4096), "r"(SND(0)), "r"(SND(2)), "r"(SND(4)), "r"(SND(6)) : "memory");
        #undef SND
        asm volatile("barrier.cluster.arrive.aligned; barrier.cluster.wait.aligned;" ::: "memory");
        mbar_wait(afull, 0);
        const uint32_t ga = BAR + 256 + (32 * (w >> 1) + 8 * (g >> 1) + 4 * (w & 1) + (g & 1)) * 4;
        const float g0 = __uint_as_float(lds32(ga)), g1 = __uint_as_float(lds32(ga + 8)), h0 = 1.f - g0, h1 = 1.f - g1;
        const uint32_t la = AT + wg * 16384 + ((lane >> 4) * 8 + (lane & 7)) * 128 + ((((w & 3) * 2 + ((lane >> 3) & 1)) ^ (lane & 7)) << 4);
        const uint32_t ra = SB + (w * 16 + (lane & 15)) * 128;
        #pragma unroll
        for (int i = 0; i < 8; i++) {
            const uint32_t a = ra + (i >> 2) * 16384 + ((((i & 3) * 2 + (lane >> 4)) ^ (lane & 7)) << 4);
            uint32_t r0, r1, r2, r3, x0, x1, x2, x3;
            ldsm4t(r0, r1, r2, r3, la + i * 2048);
            ldsm4(x0, x1, x2, x3, a);
            const uint4 u = lds128(SB + 65536 + tid * 16 + i * 4096);
            float p[8];
            #pragma unroll
            for (int e = 0; e < 8; e++) { const uint32_t x = ((const uint32_t*)&u)[e >> 1]; p[e] = (rank ? acc[64 + 8 * i + e] : acc[8 * i + e]) + ((e & 1) ? bfhi(x) : bflo(x)); }
            #define MIX(g, h, r, x, e) pack2(fmaf(g * bflo(x), bflo(r), h * p[e]), fmaf(g * bfhi(x), bfhi(r), h * p[e + 1]))
            stsm4(a, MIX(g0, h0, r0, x0, 0), MIX(g1, h1, r1, x1, 2), MIX(g0, h0, r2, x2, 4), MIX(g1, h1, r3, x3, 6));
        }
        asm volatile("fence.proxy.async.shared::cta;" ::: "memory");
        bsync<1, 256>();
        if (tid == 0) {
            for (int hf = 0; hf < 2; hf++)
                asm volatile("cp.async.bulk.tensor.5d.global.shared::cta.bulk_group [%0, {%2, %3, %3, %3, %4}], [%1];"
                    :: "l"(&tmOut), "r"(SB + hf * 16384), "r"(nt * 256 + rank * 128 + hf * 64), "r"(0), "r"(mt * 4) : "memory");
            asm volatile("cp.async.bulk.commit_group;" ::: "memory");
            asm volatile("cp.async.bulk.wait_group 0;" ::: "memory");
        }
        TL(5);
    }
}

typedef CUresult (*EncodeFn)(CUtensorMap*, CUtensorMapDataType, cuuint32_t, void*, const cuuint64_t*, const cuuint64_t*, const cuuint32_t*,
                             const cuuint32_t*, CUtensorMapInterleave, CUtensorMapSwizzle, CUtensorMapL2promotion, CUtensorMapFloatOOBfill);
static void enc(EncodeFn fn, CUtensorMap* m, void* base, int rank, const cuuint64_t* dims, const cuuint64_t* strides, const cuuint32_t* box, CUtensorMapSwizzle sw) {
    cuuint32_t es[5] = {1, 1, 1, 1, 1};
    fn(m, CU_TENSOR_MAP_DATA_TYPE_BFLOAT16, rank, base, dims, strides, box, es, CU_TENSOR_MAP_INTERLEAVE_NONE, sw,
       CU_TENSOR_MAP_L2_PROMOTION_L2_128B, CU_TENSOR_MAP_FLOAT_OOB_FILL_NONE);
}
static MainParams h_prm = {{768, 576, 512, 0, 0, 0, 0, 0, 0, 0, 0, 0}, 0, 1, nullptr, nullptr};

extern "C" void kernel_launch(void* const* d_in, const int* in_sizes, int n_in, void* d_out, int out_size) {
    const bf16* q = (const bf16*)d_in[0];
    const bf16* shift_k = (const bf16*)d_in[3];
    const bf16* ssm_k = (const bf16*)d_in[4];
    const bf16* ssm_D = (const bf16*)d_in[5];
    const bf16* mem0 = (const bf16*)d_in[7];
    const bf16* gate_w = (const bf16*)d_in[13];

    static EncodeFn fn = nullptr;
    static void* pO = nullptr;
    static void* pA = nullptr;
    if (!fn) {
        cudaDriverEntryPointQueryResult qr;
        cudaGetDriverEntryPoint("cuTensorMapEncodeTiled", (void**)&fn, cudaEnableDefault, &qr);
        cudaGetSymbolAddress(&pO, g_O);
        cudaGetSymbolAddress(&pA, g_Y);
        void* pRB; cudaGetSymbolAddress(&pRB, g_RB);
        h_prm.rb = (char*)(((uintptr_t)pRB + (4u << 20) - 1) & ~(uintptr_t)((4u << 20) - 1));
        int dev, sms; cudaGetDevice(&dev); cudaDeviceGetAttribute(&sms, cudaDevAttrMultiProcessorCount, dev);
        h_prm.by_sm = sms == NCTA;
        cudaFuncSetAttribute(main_kernel, cudaFuncAttributeMaxDynamicSharedMemorySize, mk::TOTAL);
        cudaFuncSetAttribute(out_kernel, cudaFuncAttributeMaxDynamicSharedMemorySize, ok::TOTAL);
    }
    CUtensorMap mWq, mWk, mWv, mWo, mX, mO, mWo2, mA, mOut, mQ;
    {
        cuuint64_t d[2] = {4096, 1024}, s[1] = {8192}; cuuint32_t b[2] = {64, 256};
        enc(fn, &mWq, d_in[8], 2, d, s, b, CU_TENSOR_MAP_SWIZZLE_128B);
        enc(fn, &mWk, d_in[9], 2, d, s, b, CU_TENSOR_MAP_SWIZZLE_128B);
        enc(fn, &mWv, d_in[10], 2, d, s, b, CU_TENSOR_MAP_SWIZZLE_128B);
    }
    {
        cuuint64_t d[2] = {1024, 4096}, s[1] = {2048}; cuuint32_t b[2] = {64, 128};
        enc(fn, &mWo, d_in[11], 2, d, s, b, CU_TENSOR_MAP_SWIZZLE_128B);
        cuuint64_t d2[3] = {64, 4096, 16}, s2[2] = {2048, 128}; cuuint32_t b2[3] = {64, 64, 4};
        enc(fn, &mWo2, d_in[11], 3, d2, s2, b2, CU_TENSOR_MAP_SWIZZLE_128B);
    }
    {
        cuuint64_t d[3] = {64, 2048, 16}, s[2] = {2048, 128}; cuuint32_t b[3] = {64, 32, 8};
        enc(fn, &mX, d_in[0], 3, d, s, b, CU_TENSOR_MAP_SWIZZLE_128B);
    }
    {
        cuuint64_t d[3] = {256, 128, 256}, s[2] = {512, 65536}; cuuint32_t b[3] = {256, 2, 16};
        enc(fn, &mO, pO, 3, d, s, b, CU_TENSOR_MAP_SWIZZLE_NONE);
    }
    {
        cuuint64_t d[5] = {1024, 2, 4, 4, 64}, s[4] = {2048, 16384, 4096, 65536}; cuuint32_t b[5] = {64, 2, 4, 4, 4};
        cuuint64_t da[3] = {64, 1024, 32}, sa[2] = {4096, 128}; cuuint32_t ba[3] = {64, 128, 2};
        enc(fn, &mA, pA, 3, da, sa, ba, CU_TENSOR_MAP_SWIZZLE_128B);
        enc(fn, &mQ, d_in[0], 5, d, s, b, CU_TENSOR_MAP_SWIZZLE_128B);
        enc(fn, &mOut, d_out, 5, d, s, b, CU_TENSOR_MAP_SWIZZLE_128B);
    }
    KVMaps mK;
    {
        cuuint64_t d[3] = {1024, 256, 8}, s[2] = {16384, 2048}; cuuint32_t b[3] = {8, 256, 1};
        for (int i = 0; i < 4; i++) { b[2] = i < 2 ? 1 : 8; enc(fn, &mK.m[i], d_in[1 + (i & 1)], 3, d, s, b, CU_TENSOR_MAP_SWIZZLE_NONE); }
    }
    cudaStream_t st = cudaStreamPerThread;
    cudaLaunchAttribute at[1];
    at[0].id = cudaLaunchAttributeProgrammaticStreamSerialization;
    at[0].val.programmaticStreamSerializationAllowed = 1;
    cudaLaunchConfig_t cfg = {};
    cfg.stream = st; cfg.attrs = at;
    cfg.gridDim = dim3(NCTA); cfg.blockDim = dim3(256); cfg.dynamicSmemBytes = mk::TOTAL;
    h_prm.x = (const char*)q;
    const ConvIn cin = {shift_k, ssm_k, ssm_D};
    cudaLaunchKernelEx(&cfg, main_kernel, mWq, mWk, mWv, mWo, mX, mK, mem0, cin, h_prm);
    cfg.numAttrs = PDL;
    cfg.gridDim = dim3(128); cfg.blockDim = dim3(320); cfg.dynamicSmemBytes = ok::TOTAL;
    cudaLaunchKernelEx(&cfg, out_kernel, mO, mWo2, mA, mOut, mQ, q, gate_w);
}
```

```cpp
#include <cuda_runtime.h>
#include <cuda_bf16.h>
#include <cuda.h>
#include <stdint.h>

typedef __nv_bfloat16 bf16;

constexpr int SEQ = 2048, DM = 1024, NH = 32, DH = 128, NSEG = 64;
constexpr int SPIN_LIMIT = 1 << 13, NCTA = 132;
#define NPR 2
#define RF 0
#define CC 0
#define DRY 1
#define XDL 10
#define NSP 128
#define XPF 2
#define FRONT __forceinline__
#define PDL 1
#define TPF 1

constexpr uint32_t HOME_BITS = 0xB3000;
constexpr uint32_t RB_R = 0;
constexpr uint32_t RB_B = 0x80000;
constexpr uint32_t RB_T = RB_B + 0x4000;
constexpr uint32_t RB_P = RB_B + 0x20000;
constexpr uint32_t RB_X = 2u << 20;
__device__ uint4 g_RB[(8 << 20) / 16];
__device__ uint32_t g_cls[160];
__device__ uint4 g_T[2 * NH * 3072];
__device__ uint4 g_O[NSEG * 4 * 4096];
__device__ uint4 g_Y[SEQ * DM / 8];
__device__ float g_gate[SEQ];
__device__ uint32_t g_err;
#define TL(i) do {} while (0)
#define TLX(i)
#define TS(i)

__device__ __forceinline__ uint32_t smem_u32(const void* p) { return (uint32_t)__cvta_generic_to_shared(p); }
__device__ __forceinline__ uint32_t clk() { uint32_t c; asm volatile("mov.u32 %0, %%clock;" : "=r"(c) :: "memory"); return c; }
__device__ __forceinline__ void ldsm4(uint32_t& r0, uint32_t& r1, uint32_t& r2, uint32_t& r3, uint32_t a) {
    asm volatile("ldmatrix.sync.aligned.m8n8.x4.shared.b16 {%0,%1,%2,%3}, [%4];" : "=r"(r0), "=r"(r1), "=r"(r2), "=r"(r3) : "r"(a) : "memory");
}
__device__ __forceinline__ void ldsm4t(uint32_t& r0, uint32_t& r1, uint32_t& r2, uint32_t& r3, uint32_t a) {
    asm volatile("ldmatrix.sync.aligned.m8n8.x4.trans.shared.b16 {%0,%1,%2,%3}, [%4];" : "=r"(r0), "=r"(r1), "=r"(r2), "=r"(r3) : "r"(a) : "memory");
}
__device__ __forceinline__ void ldsm2(uint32_t& r0, uint32_t& r1, uint32_t a) {
    asm volatile("ldmatrix.sync.aligned.m8n8.x2.shared.b16 {%0,%1}, [%2];" : "=r"(r0), "=r"(r1) : "r"(a) : "memory");
}
__device__ __forceinline__ void stsm4t(uint32_t a, uint32_t r0, uint32_t r1, uint32_t r2, uint32_t r3) {
    asm volatile("stmatrix.sync.aligned.m8n8.x4.trans.shared.b16 [%0], {%1,%2,%3,%4};" :: "r"(a), "r"(r0), "r"(r1), "r"(r2), "r"(r3) : "memory");
}
__device__ __forceinline__ void mma16(float* c, uint32_t a0, uint32_t a1, uint32_t a2, uint32_t a3, uint32_t b0, uint32_t b1) {
    asm volatile("mma.sync.aligned.m16n8k16.row.col.f32.bf16.bf16.f32 {%0,%1,%2,%3}, {%4,%5,%6,%7}, {%8,%9}, {%0,%1,%2,%3};"
        : "+f"(c[0]), "+f"(c[1]), "+f"(c[2]), "+f"(c[3]) : "r"(a0), "r"(a1), "r"(a2), "r"(a3), "r"(b0), "r"(b1));
}
__device__ __forceinline__ void mma8(float* c, uint32_t a0, uint32_t a1, uint32_t b0) {
    asm volatile("mma.sync.aligned.m16n8k8.row.col.f32.bf16.bf16.f32 {%0,%1,%2,%3}, {%4,%5}, {%6}, {%0,%1,%2,%3};"
        : "+f"(c[0]), "+f"(c[1]), "+f"(c[2]), "+f"(c[3]) : "r"(a0), "r"(a1), "r"(b0));
}
__device__ __forceinline__ uint32_t pack2(float lo, float hi) {
    uint32_t r; asm("cvt.rn.bf16x2.f32 %0, %1, %2;" : "=r"(r) : "f"(hi), "f"(lo)); return r;
}
__device__ __forceinline__ uint32_t hadd2(uint32_t a, uint32_t b) {
    uint32_t r; asm("add.rn.bf16x2 %0, %1, %2;" : "=r"(r) : "r"(a), "r"(b)); return r;
}
__device__ __forceinline__ float bflo(uint32_t w) { return __uint_as_float(w << 16); }
__device__ __forceinline__ float bfhi(uint32_t w) { return __uint_as_float(w & 0xFFFF0000u); }
__device__ __forceinline__ void st_g32(void* p, uint32_t v) { asm volatile("st.relaxed.gpu.global.u32 [%0], %1;" :: "l"(p), "r"(v) : "memory"); }
__device__ __forceinline__ void st_g128(void* p, uint32_t a, uint32_t b, uint32_t c, uint32_t d) {
    asm volatile("st.relaxed.gpu.global.v4.u32 [%0], {%1,%2,%3,%4};" :: "l"(p), "r"(a), "r"(b), "r"(c), "r"(d) : "memory");
}
__device__ __forceinline__ uint4 lds128(uint32_t a) { uint4 v; asm volatile("ld.shared.v4.u32 {%0,%1,%2,%3}, [%4];" : "=r"(v.x), "=r"(v.y), "=r"(v.z), "=r"(v.w) : "r"(a) : "memory"); return v; }
__device__ __forceinline__ void sts128(uint32_t a, uint4 v) { asm volatile("st.shared.v4.u32 [%0], {%1,%2,%3,%4};" :: "r"(a), "r"(v.x), "r"(v.y), "r"(v.z), "r"(v.w) : "memory"); }
__device__ __forceinline__ float2 lds64f(uint32_t a) { float2 v; asm volatile("ld.shared.v2.f32 {%0,%1}, [%2];" : "=f"(v.x), "=f"(v.y) : "r"(a) : "memory"); return v; }
__device__ __forceinline__ void sts64f(uint32_t a, float x, float y) { asm volatile("st.shared.v2.f32 [%0], {%1,%2};" :: "r"(a), "f"(x), "f"(y) : "memory"); }
__device__ __forceinline__ void sts32f(uint32_t a, float x) { asm volatile("st.shared.f32 [%0], %1;" :: "r"(a), "f"(x) : "memory"); }
__device__ __forceinline__ void sts32(uint32_t a, uint32_t x) { asm volatile("st.shared.u32 [%0], %1;" :: "r"(a), "r"(x) : "memory"); }
__device__ __forceinline__ uint32_t lds32(uint32_t a) { uint32_t v; asm volatile("ld.shared.u32 %0, [%1];" : "=r"(v) : "r"(a) : "memory"); return v; }
__device__ __forceinline__ void cpa16(uint32_t dst, const void* src) { asm volatile("cp.async.cg.shared.global [%0], [%1], 16;" :: "r"(dst), "l"(src) : "memory"); }
__device__ __forceinline__ void cpa_commit() { asm volatile("cp.async.commit_group;" ::: "memory"); }
__device__ __forceinline__ void cpa_wait() { asm volatile("cp.async.wait_all;" ::: "memory"); }
template <int ID, int N> __device__ __forceinline__ void bsync() { asm volatile("bar.sync %0, %1;" :: "n"(ID), "n"(N) : "memory"); }
template <int ID, int N> __device__ __forceinline__ void barrive() { asm volatile("bar.arrive %0, %1;" :: "n"(ID), "n"(N) : "memory"); }
template <int ID, int N> __device__ __forceinline__ void bsync_if(bool on) { asm volatile("{ .reg .pred p; setp.ne.b32 p, %2, 0; @p bar.sync %0, %1; }" :: "n"(ID), "n"(N), "r"((int)on) : "memory"); }
template <int ID, int N> __device__ __forceinline__ void barrive_if(bool on) { asm volatile("{ .reg .pred p; setp.ne.b32 p, %2, 0; @p bar.arrive %0, %1; }" :: "n"(ID), "n"(N), "r"((int)on) : "memory"); }
template <int ID> __device__ __forceinline__ uint32_t any128(uint32_t x) {
    uint32_t r; asm volatile("{ .reg .pred p; setp.ne.b32 p, %1, 0; bar.red.or.pred p, %2, 128, p; selp.u32 %0, 1, 0, p; }" : "=r"(r) : "r"(x), "n"(ID) : "memory"); return r;
}
__device__ __forceinline__ bool elect() {
    uint32_t p; asm volatile("{ .reg .pred p; elect.sync _|p, 0xFFFFFFFF; selp.u32 %0, 1, 0, p; }" : "=r"(p)); return p;
}
__device__ __forceinline__ void mbar_init(uint32_t mb, uint32_t n) { asm volatile("mbarrier.init.shared::cta.b64 [%0], %1;" :: "r"(mb), "r"(n) : "memory"); }
__device__ __forceinline__ void mbar_expect(uint32_t mb, uint32_t bytes) { asm volatile("mbarrier.arrive.expect_tx.shared::cta.b64 _, [%0], %1;" :: "r"(mb), "r"(bytes) : "memory"); }
__device__ __forceinline__ void mbar_arrive(uint32_t mb) { asm volatile("mbarrier.arrive.shared::cta.b64 _, [%0];" :: "r"(mb) : "memory"); }
__device__ __forceinline__ void mbar_wait(uint32_t mb, uint32_t ph) {
    asm volatile("{ .reg .pred p; .reg .u32 n; mov.u32 n, 0;\n"
                 "MW_%=: mbarrier.try_wait.parity.shared::cta.b64 p, [%0], %1; add.u32 n, n, 1; setp.lt.and.u32 p, n, %2, !p; @p bra.uni MW_%=; }"
                 :: "r"(mb), "r"(ph), "n"(SPIN_LIMIT) : "memory");
}
__device__ __forceinline__ void tma2d(uint32_t dst, const CUtensorMap* m, int c0, int c1, uint32_t mb) {
    asm volatile("cp.async.bulk.tensor.2d.shared::cluster.global.mbarrier::complete_tx::bytes [%0], [%1, {%3, %4}], [%2];"
        :: "r"(dst), "l"(m), "r"(mb), "r"(c0), "r"(c1) : "memory");
}
__device__ __forceinline__ void tma3d(uint32_t dst, const CUtensorMap* m, int c0, int c1, int c2, uint32_t mb) {
    asm volatile("cp.async.bulk.tensor.3d.shared::cluster.global.mbarrier::complete_tx::bytes [%0], [%1, {%3, %4, %5}], [%2];"
        :: "r"(dst), "l"(m), "r"(mb), "r"(c0), "r"(c1), "r"(c2) : "memory");
}
__device__ __forceinline__ void bulk_ld(uint32_t dst, const void* src, uint32_t bytes, uint32_t mb) {
    asm volatile("cp.async.bulk.shared::cluster.global.mbarrier::complete_tx::bytes [%0], [%1], %2, [%3];" :: "r"(dst), "l"(src), "r"(bytes), "r"(mb) : "memory");
}
__device__ __forceinline__ uint64_t mkdesc(uint32_t addr, uint32_t lbo, uint32_t sbo, uint32_t swz) {
    return (uint64_t)((addr & 0x3FFFF) >> 4) | ((uint64_t)(lbo >> 4) << 16) | ((uint64_t)(sbo >> 4) << 32) | ((uint64_t)swz << 62);
}
__device__ __forceinline__ void wg_fence() { asm volatile("wgmma.fence.sync.aligned;" ::: "memory"); }
__device__ __forceinline__ void wg_commit() { asm volatile("wgmma.commit_group.sync.aligned;" ::: "memory"); }
template <int N> __device__ __forceinline__ void wg_wait() { asm volatile("wgmma.wait_group.sync.aligned %0;" :: "n"(N) : "memory"); }
#define F4(d, o) "+f"(d[o]), "+f"(d[o + 1]), "+f"(d[o + 2]), "+f"(d[o + 3])
__device__ __forceinline__ void wgmma_n32_rs(float* d, const uint32_t* a, uint64_t db, int accum) {
    asm volatile("{.reg .pred p; setp.ne.b32 p, %21, 0;\n"
        "wgmma.mma_async.sync.aligned.m64n32k16.f32.bf16.bf16 {%0,%1,%2,%3,%4,%5,%6,%7,%8,%9,%10,%11,%12,%13,%14,%15}, {%16,%17,%18,%19}, %20, p, 1, 1, 0;}"
        : F4(d, 0), F4(d, 4), F4(d, 8), F4(d, 12) : "r"(a[0]), "r"(a[1]), "r"(a[2]), "r"(a[3]), "l"(db), "r"(accum));
}
__device__ __forceinline__ void wait_until(uint32_t tgt, uint32_t any) {
    asm volatile("{ .reg .pred p, q; .reg .u32 t; .reg .s32 d; mov.u32 t, %0; setp.ne.u32 q, %1, 0xFFFFFFFF;\n"
                 "WU_%=: @q mov.u32 t, %%clock; sub.s32 d, t, %0; setp.lt.s32 p, d, 0; @p bra.uni WU_%=; }" :: "r"(tgt), "r"(any) : "memory");
}

namespace mk {
constexpr uint32_t SB = 1024;
constexpr uint32_t WV = SB, WO = SB + 65536, XT = SB + 131072, TK = SB + 163840  , TQ = TK + 32768, MEM = TQ + 4096,
                   SC = MEM + 8192  , PT = SC + 6144,
                   OB = SC + 8192, SUM = OB + 2048, BAR = SUM + 512, GRP = BAR + 128, PROFB = BAR + 192,
                   TOTAL = PROFB - SB;
static_assert(TOTAL <= 232448, "shared memory");
constexpr uint32_t MB_WQ = BAR, MB_WK = BAR + 8, MB_WV = BAR + 16, MB_WO = BAR + 24, MB_X = BAR + 32, MB_KV = BAR + 40, MB_R = BAR + 48, MB_B = BAR + 56, MB_C = BAR + 64;
constexpr uint32_t XT2 = WV, RS = WV + 32768, VE = RS + 4096;
enum { B_START = 1, B_H0, B_H2, B_H3, B_S1, B_SC, B_SC2, B_S0, B_O, B_O2, B_PT, B_GO, B_VX, B_RD, B_BT };
constexpr uint64_t XD0 = (uint64_t)(XT >> 4) | ((uint64_t)1 << 16) | ((uint64_t)64 << 32) | ((uint64_t)1 << 62);
constexpr uint32_t TSLOT = NH * 49152;
}
struct MainParams { int d[12]; uint32_t zero; int by_sm; char* rb; const char* x; };
#define XD(i) (mk::XD0 - (((i) >> 5) & 1) * ((mk::XT - mk::XT2) >> 4) + ((i) >> 6) * ((mk::TK - mk::XT) >> 4) + (((i) & 31) >> 2) * 256 + ((i) & 3) * 2)
#define XD4(i) XD(i), XD(i + 1), XD(i + 2), XD(i + 3)
#define XD16(i) XD4(i), XD4(i + 4), XD4(i + 8), XD4(i + 12)
__constant__ __align__(256) uint64_t c_xd[96] = {XD16(0), XD16(16), XD16(32), XD16(48), XD16(64), XD16(80)};
#define CUT(r) asm volatile("{ .reg .pred q; setp.eq.u32 q, %1, 0xFFFFFFFF; @q mov.u32 %0, %%clock; }" : "+r"(r) : "r"(t16) : "memory")
__device__ __forceinline__ uint32_t opq(uint32_t x) { asm volatile("" : "+r"(x)); return x; }
__device__ __forceinline__ float opqf(float x) { asm volatile("" : "+f"(x)); return x; }
#define PROF(i)
#define PROFW(i, w)
#define TRC(i, v)
#define RETRY(i, on)
#define P(i) prm.d[i]
#define DELAY(n) do { if (n) { _Pragma("unroll") for (int i_ = 0; i_ < n; i_++) asm volatile("mad.lo.u32 %0, %0, %1, %0;" : "+r"(pb) : "r"(prm.zero)); CUT(pa); } } while (0)

__device__ __forceinline__ uint32_t tagw(uint32_t w, uint32_t tau) { return (w & ~1u) | tau; }
__device__ __forceinline__ uint32_t ld_g32(const void* p) { uint32_t v; asm volatile("ld.relaxed.gpu.global.u32 %0, [%1];" : "=r"(v) : "l"(p) : "memory"); return v; }
__device__ __forceinline__ void ld_g64(uint32_t* v, const void* p) { asm volatile("ld.relaxed.gpu.global.v2.u32 {%0,%1}, [%2];" : "=r"(v[0]), "=r"(v[1]) : "l"(p) : "memory"); }
__device__ __forceinline__ void ld_g128(uint32_t* v, const void* p) {
    asm volatile("ld.relaxed.gpu.global.v4.u32 {%0,%1,%2,%3}, [%4];" : "=r"(v[0]), "=r"(v[1]), "=r"(v[2]), "=r"(v[3]) : "l"(p) : "memory");
}
__device__ __forceinline__ void st_g64(void* p, uint32_t a, uint32_t b) { asm volatile("st.relaxed.gpu.global.v2.u32 [%0], {%1,%2};" :: "l"(p), "r"(a), "r"(b) : "memory"); }
__device__ __forceinline__ void lds128f(float* v, uint32_t a) { asm volatile("ld.shared.v4.f32 {%0,%1,%2,%3}, [%4];" : "=f"(v[0]), "=f"(v[1]), "=f"(v[2]), "=f"(v[3]) : "r"(a) : "memory"); }
__device__ __forceinline__ void sts128f(uint32_t a, float x, float y, float z, float w) { asm volatile("st.shared.v4.f32 [%0], {%1,%2,%3,%4};" :: "r"(a), "f"(x), "f"(y), "f"(z), "f"(w) : "memory"); }
__device__ __forceinline__ void stsm4(uint32_t a, uint32_t r0, uint32_t r1, uint32_t r2, uint32_t r3) {
    asm volatile("stmatrix.sync.aligned.m8n8.x4.shared.b16 [%0], {%1,%2,%3,%4};" :: "r"(a), "r"(r0), "r"(r1), "r"(r2), "r"(r3) : "memory");
}
__device__ __forceinline__ void mmaq(float* c, const uint32_t* a, uint32_t b0, uint32_t b1) { mma16(c, a[0], a[1], a[2], a[3], b0, b1); }
template <int LUT> __device__ __forceinline__ uint32_t lop3(uint32_t a, uint32_t b, uint32_t c) { uint32_t r; asm("lop3.b32 %0, %1, %2, %3, %4;" : "=r"(r) : "r"(a), "r"(b), "r"(c), "n"(LUT)); return r; }
template <int N, int S> __device__ __forceinline__ uint32_t stale(const uint32_t* x, uint32_t tau) {
    if constexpr (N == 2) return lop3<0x7E>(x[0], tau, x[S]);
    else if constexpr (N == 3) return lop3<0xF6>(stale<2, S>(x, tau), x[2 * S], tau);
    else if constexpr (N == 4 || N == 16) return lop3<0xFC>(stale<N / 2, S>(x, tau), stale<N / 2, S>(x + N / 2 * S, tau), 0);
    else return lop3<0xFE>(stale<3, S>(x, tau), stale<3, S>(x + 3 * S, tau), stale<2, S>(x + 6 * S, tau));
}
__device__ __forceinline__ uint32_t late(uint32_t a, uint32_t b, uint32_t mask) {
    uint32_t r;
    asm volatile("{ .reg .pred p; .reg .b32 t; lop3.b32 t, %1, %2, %3, 0xA8; setp.ne.b32 p, t, 0; vote.sync.any.pred p, p, 0xFFFFFFFF; selp.u32 %0, 1, 0, p; }" : "=r"(r) : "r"(a), "r"(b), "r"(mask));
    return r;
}
#define AGAIN(id, reload, ...) _Pragma("unroll 1") for (int n_ = 0; __builtin_expect(__VA_ARGS__, 0) && n_ < SPIN_LIMIT; n_++) { RETRY(id, 1); reload; }
__device__ __forceinline__ uint32_t tile_off(int lane, int chunk0) {
    return ((lane >> 4) * 8 + (lane & 7)) * 128 + (((chunk0 + ((lane >> 3) & 1)) ^ (lane & 7)) << 4);
}
template <int K0, int K1>
__device__ __forceinline__ void load_tile(uint32_t a, uint32_t* T) {
    #pragma unroll
    for (int ks = K0; ks < K1; ks++) ldsm4t(T[4 * ks], T[4 * ks + 1], T[4 * ks + 2], T[4 * ks + 3], a + ks * 2048);
}
__device__ __forceinline__ void lds128u(uint32_t* v, uint32_t a) { asm volatile("ld.shared.v4.u32 {%0,%1,%2,%3}, [%4];" : "=r"(v[0]), "=r"(v[1]), "=r"(v[2]), "=r"(v[3]) : "r"(a) : "memory"); }
template <int K0, int K1, int STRIDE = 4096>
__device__ __forceinline__ void load_frag(uint32_t a, uint32_t* T) {
    #pragma unroll
    for (int ks = K0; ks < K1; ks++) lds128u(&T[4 * ks], a + ks * STRIDE);
}
template <int L0, int L1, bool INIT = false>
__device__ __forceinline__ void wg_run(float* acc, const uint32_t* A, const uint64_t* d) {
    if (L1 > L0) {
        wg_fence();
        #pragma unroll
        for (int l = L0; l < L1; l++) wgmma_n32_rs(acc, &A[4 * l], d[l], INIT || l != 0);
        wg_commit();
    }
}
__device__ __forceinline__ void load_x(const CUtensorMap* tmX, int c, int seg, uint32_t dst) {
    asm volatile("{ .reg .pred p; elect.sync _|p, 0xFFFFFFFF;\n"
        "@p cp.async.bulk.tensor.3d.shared::cluster.global.mbarrier::complete_tx::bytes [%4], [%0, {%5, %1, %2}], [%3]; }"
        :: "l"(tmX), "r"(seg * 32), "r"((c & 1) * 8), "r"(mk::MB_X), "r"(dst), "r"(0) : "memory");
    __syncwarp();
}
__device__ __forceinline__ void bulk_expect(uint32_t mb, uint32_t bytes) {
    asm volatile("{ .reg .pred p; elect.sync _|p, 0xFFFFFFFF; @p mbarrier.arrive.expect_tx.shared::cta.b64 _, [%0], %1; }" :: "r"(mb), "r"(bytes) : "memory");
}
__device__ __forceinline__ void bulk_copy(uint32_t dst, const void* src, uint32_t bytes, uint32_t mb) {
    asm volatile("{ .reg .pred p; elect.sync _|p, 0xFFFFFFFF; @p cp.async.bulk.shared::cluster.global.mbarrier::complete_tx::bytes [%0], [%1], %2, [%3]; }"
        :: "r"(dst), "l"(src), "r"(bytes), "r"(mb) : "memory");
    __syncwarp();
}
__device__ __forceinline__ void bulk_copy_if(bool on, uint32_t dst, const void* src, uint32_t bytes, uint32_t mb) {
    asm volatile("{ .reg .pred p; elect.sync _|p, 0xFFFFFFFF; setp.ne.and.b32 p, %4, 0, p; @p cp.async.bulk.shared::cluster.global.mbarrier::complete_tx::bytes [%0], [%1], %2, [%3]; }"
        :: "r"(dst), "l"(src), "r"(bytes), "r"(mb), "r"((int)on) : "memory");
    __syncwarp();
}
__device__ __forceinline__ void kv_expect(uint32_t bytes) { bulk_expect(mk::MB_KV, bytes); }
__device__ __forceinline__ void kv_copy(uint32_t dst, const void* src, uint32_t bytes) { bulk_copy(dst, src, bytes, mk::MB_KV); }
__device__ __forceinline__ uint32_t gtime() { uint32_t c; asm volatile("mov.u32 %0, %%globaltimer_lo;" : "=r"(c) :: "memory"); return c; }
__device__ __forceinline__ void wait_g(uint32_t tgt, uint32_t any) {
    asm volatile("{ .reg .pred p, q; .reg .u32 t; mov.u32 t, %0; setp.ne.u32 q, %1, 0xFFFFFFFF;\n"
                 "WG_%=: @q mov.u32 t, %%globaltimer_lo; sub.u32 t, t, %0; setp.gt.u32 p, t, 0xFFFF0000; @p bra.uni WG_%=; }" :: "r"(tgt), "r"(any) : "memory");
    __syncwarp();
}
__device__ __forceinline__ uint32_t clkv(uint32_t any) {
    uint32_t c; asm volatile("{ .reg .pred q; setp.ne.u32 q, %1, 0xFFFFFFFF; mov.u32 %0, 0; @q mov.u32 %0, %%clock; }" : "=r"(c) : "r"(any) : "memory"); return c;
}
__device__ __forceinline__ char* kv_src(int c, int seg) { return (char*)g_T + ((seg & 1) * mk::TSLOT + (c >> 2) * 49152); }
__device__ __forceinline__ void prefetch_l2(const void* p, uint32_t bytes) {
    asm volatile("{ .reg .pred p; elect.sync _|p, 0xFFFFFFFF; @p cp.async.bulk.prefetch.L2.global [%0], %1; }" :: "l"(p), "r"(bytes) : "memory");
}
__device__ __forceinline__ uint32_t phase(int i) { return (~i >> 1) & 1; }
__device__ __forceinline__ void qk_pack(const float* acc, uint32_t* p) {
    #pragma unroll
    for (int i = 0; i < 4; i++) { p[i] = pack2(acc[4 * i], acc[4 * i + 1]); p[4 + i] = pack2(acc[4 * i + 2], acc[4 * i + 3]); }
}
__device__ __forceinline__ void sts32_if(bool on, uint32_t a, uint32_t x) {
    asm volatile("{ .reg .pred p; setp.ne.b32 p, %2, 0; @p st.shared.u32 [%0], %1; }" :: "r"(a), "r"(x), "r"((int)on) : "memory");
}
__device__ __forceinline__ void sts128_if(bool on, uint32_t a, const uint32_t* p) {
    asm volatile("{ .reg .pred p; setp.ne.b32 p, %5, 0; @p st.shared.v4.u32 [%0], {%1,%2,%3,%4}; }" :: "r"(a), "r"(p[0]), "r"(p[1]), "r"(p[2]), "r"(p[3]), "r"((int)on) : "memory");
}
__device__ __forceinline__ void st_if(bool on, char* a, const uint32_t* p) {
    asm volatile("{ .reg .pred p; setp.ne.b32 p, %5, 0; @p st.relaxed.gpu.global.v4.u32 [%0], {%1,%2,%3,%4}; }" :: "l"(a), "r"(p[0]), "r"(p[1]), "r"(p[2]), "r"(p[3]), "r"((int)on) : "memory");
}
__device__ __forceinline__ char* tok_dst(int c, int seg, int wg) { return kv_src(c, seg) + (wg ? (c & 1) * 8192 + (c & 2) * 2048 : 32768 + (c & 1) * 2048 + (c & 2) * 512); }
#define HI8 (wg ? 0x220 : 0xC0)
#define TAGM() uint32_t tm[4]; tag_masks(tm, (t16 >> (wg ? 4 : 6)) & 24)
__device__ __forceinline__ void acc_init(float* acc, const uint32_t* p) {
    #pragma unroll
    for (int i = 0; i < 4; i++) { acc[4 * i] = bflo(p[i]); acc[4 * i + 1] = bfhi(p[i]); acc[4 * i + 2] = bflo(p[4 + i]); acc[4 * i + 3] = bfhi(p[4 + i]); }
}
__device__ __forceinline__ void acc_add(float* acc, const uint32_t* p) {
    #pragma unroll
    for (int i = 0; i < 4; i++) { acc[4 * i] += bflo(p[i]); acc[4 * i + 1] += bfhi(p[i]); acc[4 * i + 2] += bflo(p[4 + i]); acc[4 * i + 3] += bfhi(p[4 + i]); }
}
__device__ __forceinline__ void tag_masks(uint32_t* m, uint32_t j8) {
    const uint32_t x = 1u << j8;
    #pragma unroll
    for (int i = 0; i < 4; i++) m[i] = opq(__byte_perm(x, 0, 0x4440 + i));
}
__device__ __forceinline__ void pack_tag(const float* acc, uint32_t* p, uint32_t tau, const uint32_t* m) {
    qk_pack(acc, p);
    #pragma unroll
    for (int i = 0; i < 8; i++) p[i] = lop3<0xB8>(p[i], m[i & 3], tau);
}
__device__ __forceinline__ uint32_t kv_stale(uint32_t w, uint32_t l16, uint32_t tau) {
    uint32_t x[12];
    const uint32_t a = opq(l16 * 2 + ((l16 >> 4) & 0x1C) + w * 12288), aq = w == 2 ? opq(l16 * 2 + ((l16 >> 2) & 0x10) + ((l16 >> 5) & 0xC) + 24576) : a;
    #pragma unroll
    for (int i = 0; i < 12; i++) x[i] = lds32(mk::TK + i * 1024 + (i < 8 ? a : aq));
    return late(stale<8, 1>(x, tau), stale<4, 1>(x + 8, tau), 1);
}
__device__ __forceinline__ void refetch_kv(int c, int seg, int w, uint32_t l16) {
    #pragma unroll 1
    for (int i = w * 24; i < w * 24 + 24; i++) {
        uint32_t v[4];
        ld_g128(v, kv_src(c, seg) + (i * 512 + (i >> 6) * (c & 3) * 4096) + l16);
        sts128(mk::TK + i * 512 + l16, make_uint4(v[0], v[1], v[2], v[3]));
    }
    __syncwarp();
}
__device__ __forceinline__ void get_kv(int c, int seg) {
    kv_expect(36864); kv_copy(mk::TK, kv_src(c, seg), 32768); kv_copy(mk::TQ, kv_src(c, seg) + (32768 + (c & 3) * 4096), 4096);
}
constexpr uint32_t ONES = 0x3F803F80u;
__device__ __forceinline__ float rcpf(float x) { float r; asm("rcp.approx.ftz.f32 %0, %1;" : "=f"(r) : "f"(x)); return r; }

#define ANN 2
#define POL 8
#define PRE0 4
#define PRE1 4
#define HC 2
#define HR 4
#define BL 1
#define NA 2
#define QF 0
#define DEEP 6
#define AHEAD(n) (PRE0 + 2 * (n) < (n) + DEEP ? PRE0 + 2 * (n) : (n) + DEEP < 16 ? (n) + DEEP : 16)
#define CO 1
#define HS 2
#define VP 0
#define KM 1
#define NLDS 2
#define AL 2
#define RP 26
#define RQ 2
#define RL 29
#define R4 1
#define KVP 12
#define LD7 8
#define XP 3
#define G2 0
#define NB 26
#define BD 8
#define NP 22
#define TA 4
#define TA0 2
#define NT 19
#define VH 1
#define TRIES 200
#define NPW 3
#define EV0 5
#define EV1 8
#define WA1 6
#define WA2 9
#define H2 10
#define QV 1
#define QD 0
#define KD 0
#define VD 0
#define WA0 4
#define ONE 0
#define PP 12
#define OBA 3
#define WA3 1
#define WB1 0
#define WB2 12
#define WB3 13
#define H0 6
#define H3 10
__device__ __forceinline__ uint32_t tagm(uint32_t w, uint32_t mask, uint32_t tau) { return lop3<0xB8>(w, mask, tau); }
__device__ __forceinline__ char* at(uint32_t lo, uint32_t hi) { char* p; asm("mov.b64 %0, {%1,%2};" : "=l"(p) : "r"(lo), "r"(hi)); return p; }
__device__ __forceinline__ float ex2(float x) { float r; asm("ex2.approx.ftz.f32 %0, %1;" : "=f"(r) : "f"(x)); return r; }
__device__ __forceinline__ float max8(const float* x) { return fmaxf(fmaxf(fmaxf(x[0], x[1]), fmaxf(x[2], x[3])), fmaxf(fmaxf(x[4], x[5]), fmaxf(x[6], x[7]))); }
__device__ __forceinline__ float max4lanes(float m) { return fmaxf(fmaxf(m, __shfl_xor_sync(~0u, m, 1)), fmaxf(__shfl_xor_sync(~0u, m, 2), __shfl_xor_sync(~0u, m, 3))); }
constexpr float SCL = 0.08838834764831845f * 1.4426950408889634f;
__device__ __forceinline__ void tok_scores(float* x, uint32_t sa) {
    float y[8];
    lds128f(x, sa); lds128f(y, sa + 1024); lds128f(x + 4, sa + 512); lds128f(y + 4, sa + 1536);
    #pragma unroll
    for (int i = 0; i < 8; i++) x[i] += y[i];
}
__device__ __forceinline__ void mem_scores(float* x, uint32_t sa) {
    float z[8];
    lds128f(z, sa + 2048); lds128f(z + 4, sa + 2560);
    x[8] = (z[0] + z[2]) + (z[4] + z[6]); x[9] = (z[1] + z[3]) + (z[5] + z[7]);
}

struct Ctx { uint32_t u_rs, u_rl, u_bs, u_bl, rblo, rbhi; int w8, c; };
template <int wg>
__device__ __forceinline__ void steps(uint32_t* W, uint32_t* T, uint32_t t16, uint32_t pa, uint32_t pb, const Ctx& cx, const CUtensorMap* tmX, const MainParams& prm) {
    using namespace mk;
    const int c = cx.c, kap = c & 1, w8 = cx.w8;
    const uint32_t rbhi = cx.rbhi;
    uint32_t u_rs = cx.u_rs, u_rl = cx.u_rl, u_bs = cx.u_bs, u_bl = cx.u_bl ^ ((c & 2) << 14);
    uint32_t u_x = cx.rblo + RB_X + (c >> 2) * 16384, u_xs = u_x + kap * 2048 + (c & 2) * 512;
    uint32_t u_ta = ((cx.u_bl & ~0x10000u) ^ (kap << 12)) + (RB_T - RB_B) + 1024;
    uint32_t u_rp = cx.rblo + RB_T + 1024 + c * 4;
    uint32_t u_og = (c & 3) * 65536 + (c >> 2) * 2048 + (w8 & 3) * 256;
    const uint32_t u_sa = (w8 & 2) * 256 + (w8 & 1) * 8;
    #define TOK_DST() tok_dst(c, seg, wg)
    constexpr int EV = wg ? EV1 : EV0;
    constexpr uint32_t VEB = VE + (wg ? EV0 * 2048 - 2048 : 0) - (16 - EV) * 2048;
    static_assert((EV0 + EV1) * 2048 <= 28672, "");
    __syncthreads();
    #pragma unroll
    for (int i = 16 - EV; i < 16; i++) sts128(VEB + i * 2048 + t16, make_uint4(T[4 * i], T[4 * i + 1], T[4 * i + 2], T[4 * i + 3]));
    asm volatile("fence.proxy.async.shared::cta;" ::: "memory");
    #pragma unroll 1
    for (uint32_t sb = 0, redo = 0, uz = prm.zero;;) {
        sb = opq(sb + 256);
        const int s = sb & 255, bc = sb >> 8;
        t16 |= uz;
        uz &= sb;
        const int seg = s + 2;
        const uint32_t tau = phase(s);
        const uint32_t l16 = opq(t16 & 0x1F0);
        uint32_t F[64];
        float ot[3][2][4];
        uint32_t an[4];
        #define LDB(i) ldsm4t(b[i][0], b[i][1], b[i][2], b[i][3], MEM + l16 + (i) * 512)
        #define ST_X() do { char* xs = at(u_xs + (pb >> 16), rbhi) + wg * 4096; \
            st_g32(xs, tagm(pack2((a[0][0] + a[1][0]) + (a[2][0] + a[3][0]), (a[0][2] + a[1][2]) + (a[2][2] + a[3][2])), mG, tau * 0x10001u)); \
            st_g32(xs + 32, tagm(pack2((a[0][1] + a[1][1]) + (a[2][1] + a[3][1]), (a[0][3] + a[1][3]) + (a[2][3] + a[3][3])), mG, tau * 0x10001u)); } while (0)
        #define ST_V() st_g64(at(u_xs + (t16 >> 1), rbhi) + (8192 + wg * 3072), \
            tagm(pack2((v[0][0] + v[1][0]) + (v[2][0] + v[3][0]), (v[0][1] + v[1][1]) + (v[2][1] + v[3][1])), mT, tau), \
            pack2((v[0][2] + v[1][2]) + (v[2][2] + v[3][2]), (v[0][3] + v[1][3]) + (v[2][3] + v[3][3])))
        #define V_MMA(i, o) do { mmaq(v[2 * ((i) & 1)], &T[8 * (i)], b[(o) + (i)][0], b[(o) + (i)][1]); mmaq(v[2 * ((i) & 1) + 1], &T[8 * (i) + 4], b[(o) + (i)][2], b[(o) + (i)][3]); } while (0)
        #define ST_R(i) do { \
                const uint32_t r0 = pack2((r[i][0][0] + r[i][1][0]) * i0, (r[i][0][1] + r[i][1][1]) * i1); \
                const uint32_t r1 = pack2((r[i][0][2] + r[i][1][2]) * i0, (r[i][0][3] + r[i][1][3]) * i1); \
                st_g64(at(ra ^ (i * 0x3000), rbhi), tagm(r0, mT, tau), r1); } while (0)
        #define LD_OB(i) ldsm4t(ob[4 * (i)], ob[4 * (i) + 1], ob[4 * (i) + 2], ob[4 * (i) + 3], OB + l16 + (i) * 512)
        #define WO_MMA(have, more, mid, tail) uint32_t ob[16], ra; float r[2][2][4] = {}; \
            LD_OB(0); __syncwarp(); LD_OB(1); __syncwarp(); if (OBA > 2) { LD_OB(2); __syncwarp(); } \
            _Pragma("unroll") for (int i = have; i < have + more; i++) { lds128u(&F[4 * i], WO + t16 + i * 4096); __syncwarp(); } \
            _Pragma("unroll") for (int i = 0; i < 16; i++) { \
                if (!(i & 1) || (i > 4 && i < 8)) CUT(pb); \
                if (i == 4) LD_OB(OBA); \
                if (i == 5 && OBA == 2) LD_OB(3); \
                { const int n = have + more + i - 8 + OBA; if (i >= 8 - OBA && n < 16) lds128u(&F[4 * n], WO + t16 + n * 4096); } \
                if (wg == 0 && i == 4) { const float2 su = lds64f(SUM + (l16 >> 1)); i0 = su.x; i1 = su.y; } \
                mmaq(r[(i >> 1) & 1][i & 1], &F[4 * i], ob[(i >> 2) * 4 + 2 * (i & 1)], ob[(i >> 2) * 4 + 2 * (i & 1) + 1]); \
                if (wg && i == 2) { i0 = opqf(rcpf(i0)); i1 = opqf(rcpf(i1)); } \
                if (i == PP) { mid; } \
                if (wg && i == POL) POLL(); \
                if (!wg && i == KVP) bulk_copy(TK + 16384 + w8 * 4096, kv_src(c, s + 1) + (16384 + w8 * 4096), 4096, MB_KV); \
                if (i == 11) { ra = (l16 >> 1) * 33 & 0x1078; CUT(ra); } \
                if (i == 13) ra = opq(ra ^ u_rs); } \
            CUT(pb); tail; \
            if (!wg) { i0 = rcpf(i0); i1 = rcpf(i1); } \
            ST_R(0); ST_R(1)
        #define LD_X(r, o) do { ld_g64(r, xa + (o)); ld_g64(r + 2, xa + ((o) + 2048)); ld_g64(r + 4, xa + ((o) + 1024)); ld_g64(r + 6, xa + ((o) + 3072)); } while (0)
        #define REPORT(w, add) asm volatile("{ .reg .pred p; .reg .u32 t; setp.lt.u32 p, %1, 32; mov.u32 t, %1; @p mov.u32 t, %%globaltimer_lo; add.u32 t, t, %3; lop3.b32 t, t, 31, %2, 0xB8; @p st.relaxed.gpu.global.u32 [%0], t; }" \
            :: "l"(at(u_rp + (l16 << 8), rbhi)), "r"(t16 - (w) * 512), "r"(s), "r"(add) : "memory")
        #define POLL() asm volatile("{ .reg .pred p; setp.ge.u32 p, %5, 3584; mov.u32 %0, 0; mov.u32 %1, 0; mov.u32 %2, 0; mov.u32 %3, 0; @p ld.relaxed.gpu.global.v4.u32 {%0,%1,%2,%3}, [%4]; }" \
            : "=&r"(an[0]), "=&r"(an[1]), "=&r"(an[2]), "=&r"(an[3]) : "l"(at(u_ta + l16, rbhi)), "r"(t16) : "memory")
        #define GET_B(sl) do { const uint32_t a_ = u_bl ^ (sl); bulk_copy(MEM, at(a_, rbhi), 4096, MB_B); bulk_copy(MEM + 4096, at(a_ ^ 0x3000, rbhi), 4096, MB_B); } while (0)
        if constexpr (wg == 0) {
            float a[4][4], v[4][4] = {};
            uint32_t b[16][4];
            if (__builtin_expect(redo, 0)) {
                RETRY(6, 1);
                bsync<B_RD, 256>();
                if (w8 == 3) { bulk_expect(MB_B, 8192); GET_B(1 << 20); }
                __syncwarp();
            }
            const uint32_t ck = opq(t16 * 2 + ((l16 >> 4) & 0x1C)), tp = opq(phase(s - 1)), cm = opq((2 * bc + (s > 0 && bc < SPIN_LIMIT)) | (t16 >> 19));
            CUT(pa);
            mbar_wait(MB_B, ~bc & 1);
            #define ORD(n) (n)
            LDB(ORD(0)); __syncwarp(); LDB(ORD(1)); __syncwarp();
            const uint32_t c0 = lds32(MEM + ck), c1 = lds32(MEM + 4096 + ck);
            __syncwarp();
            #pragma unroll
            for (int n = 2; n < PRE0; n++) { LDB(ORD(n)); __syncwarp(); }
            PROF(0);
            uint32_t vw[2];
            #pragma unroll
            for (int n = 0; n < 16; n++) {
                const int i = ORD(n);
                CUT(pa);
                #pragma unroll
                for (int m = AHEAD(n); m < AHEAD(n + 1); m++) { LDB(ORD(m)); __syncwarp(); }
                if (n == HC) redo = opq(lop3<0x7E>(c0, tp, c1) & cm);
                if (n == HC + 1) asm volatile("{ .reg .pred p; setp.ne.u32 p, %2, 0; @p st.shared.u32 [%0], %1; }" :: "r"(SUM + 256), "r"(cm), "r"(redo & 1) : "memory");
                if (n == H0) barrive<B_H0, 256>();
                if (n == HR + 1) { redo = lds32(SUM + 256 + opq(t16 >> 20)); __syncwarp(); }
                if (n == HR) bsync<B_START, 128>();
                if (n == 12) redo = !late(redo ^ (2 * bc + 1), 0, ~0u);
                const int e = n < 8 ? 0 : 2 * (~n & 1);
                if (!(n & 7)) a[e][0] = a[e][1] = a[e][2] = a[e][3] = a[e + 1][0] = a[e + 1][1] = a[e + 1][2] = a[e + 1][3] = 0.f;
                mmaq(a[e], &W[8 * i], b[i][0], b[i][1]);
                if (n < 8) { mmaq(v[0], &T[8 * i], b[i][0], b[i][1]); CUT(pa); }
                mmaq(a[e + 1], &W[8 * i + 4], b[i][2], b[i][3]);
                if (n < 8) mmaq(v[1], &T[8 * i + 4], b[i][2], b[i][3]);
                if (n == 10) { vw[0] = opq(pack2(v[0][0] + v[1][0], v[0][1] + v[1][1])); vw[1] = opq(pack2(v[0][2] + v[1][2], v[0][3] + v[1][3])); }
            }
            CUT(pa);
            if (__builtin_expect(redo, 0)) { __syncwarp(); continue; }
            CUT(pa); CUT(pb);
            const uint32_t mG = (l16 & 0x1C0) ? 0 : 0x10001u, mT = (l16 & 0x30) ? 0 : 1;
            ST_X();
            CUT(pa);
            PROF(1);
            const char* const xa = at(u_x + (t16 >> 1), rbhi);
            float sc[4][4];
            uint32_t k[8], A[16], q[16], kf[16];
            #define LD_Q(xb) do { LD_X(q, 0); { const char* const xa = xb; LD_X(q + 8, 0); } } while (0)
            #define XB() at((u_x + (opq(t16) >> 1)) ^ 256, rbhi)
            #define LD_A(i) ldsm4t(A[4 * i], A[4 * i + 1], A[4 * i + 2], A[4 * i + 3], TQ + (i & 1) * 1024 + ((i & 2) ? qb : qa))
            uint32_t k1[16];
            #define LD_K(i) do { ldsm4t(kf[4 * i], kf[4 * i + 1], kf[4 * i + 2], kf[4 * i + 3], TK + ka[i]); ldsm4t(k1[4 * i], k1[4 * i + 1], k1[4 * i + 2], k1[4 * i + 3], TK + 8192 + ka[i]); __syncwarp(); } while (0)
            const char* const xb = XB();
            const uint32_t ka[4] = {opq(pa & 0xFFFF), opq((pa & 0xFFFF) ^ 0x400), opq((pa & 0xFFFF) ^ 0x10), opq((pa & 0xFFFF) ^ 0x410)}, qa = opq(pa >> 16), qb = opq(qa ^ 0x100);
            st_g64(at(u_xs + (t16 >> 1), rbhi) + 8192, tagm(vw[0], mT, tau), vw[1]);
            CUT(pb);
            bsync<B_H2, 256>();
            if (QF) { LD_Q(xb); __syncwarp(); }
            #pragma unroll
            for (int i = 0; i < NA; i++) LD_K(i);
            CUT(pb);
            #pragma unroll
            for (int i = 0; i < 4 * NA; i++) kf[i] = opq(hadd2(kf[i], k1[i]));
            CUT(pb);
            if (!QF) { DELAY(QD); LD_Q(xb); CUT(pb); }
            bsync<B_H3, 256>();
            #pragma unroll
            for (int i = NA; i < 4; i++) LD_K(i);
            LD_A(0); LD_A(1); LD_A(2); LD_A(3);
            CUT(pb);
            if (KM == 1) {
                #pragma unroll
                for (int i = 4 * NA; i < 16; i++) kf[i] = opq(hadd2(kf[i], k1[i]));
                CUT(pb);
            }
            DELAY(KD);
            LD_X(k, 4096);
            barrive<B_VX, 256>();
            CUT(pb);
            PROF(3);
            if (KM == 2) {
                #pragma unroll
                for (int i = 4 * NA; i < 16; i++) kf[i] = opq(hadd2(kf[i], k1[i]));
            }
            #pragma unroll
            for (int i = 0; i < 8; i++) A[2 * i + 1] = opq(hadd2(A[2 * i], A[2 * i + 1]));
            CUT(pb);
            AGAIN(1, LD_Q(XB()); LD_X(k, 4096); sts32(SUM + 268, s + 1), late(stale<4, 2>(q, tau), stale<4, 2>(q + 8, tau), mT))
            #pragma unroll
            for (int i = 0; i < 4; i++) {
                A[4 * i] = hadd2(q[4 * i], q[4 * i + 2]); A[4 * i + 2] = hadd2(q[4 * i + 1], q[4 * i + 3]);
                if (i < 2) { sc[i][0] = sc[i][1] = sc[i][2] = sc[i][3] = sc[2 + i][0] = sc[2 + i][1] = sc[2 + i][2] = sc[2 + i][3] = 0.f; }
                mmaq(sc[i & 1], A + 4 * i, kf[2 * i], kf[2 * i + 1]); mmaq(sc[2 + (i & 1)], A + 4 * i, kf[8 + 2 * i], kf[9 + 2 * i]);
            }
            sts128f(SC + t16, sc[0][0] + sc[1][0], sc[0][1] + sc[1][1], sc[2][0] + sc[3][0], sc[2][1] + sc[3][1]);
            barrive<B_S1, 256>();
            sts128f(SC + 3072 + t16, sc[0][2] + sc[1][2], sc[0][3] + sc[1][3], sc[2][2] + sc[3][2], sc[2][3] + sc[3][3]);
            load_frag<0, WB1>(WO + t16, F);
            const uint32_t sa = opq(l16 + u_sa);
            CUT(pb);
            PROF(4);
            float d[16];
            #pragma unroll 1
            for (int n_ = 0;; n_++) {
                #pragma unroll
                for (int i = 0; i < 4; i++) { d[4 * i] = d[4 * i + 1] = d[4 * i + 2] = d[4 * i + 3] = 0.f; mmaq(d + 4 * i, A + 4 * (i >> 1), k[2 * i], k[2 * i + 1]); }
                if (__builtin_expect(!late(stale<2, 2>(k, tau), stale<2, 2>(k + 4, tau), mT), 1) || n_ >= SPIN_LIMIT) break;
                RETRY(2, 1);
                LD_X(k, 4096);
            }
            sts64f(SC + 2048 + sa, (d[0] + d[4]) + (d[8] + d[12]), (d[1] + d[5]) + (d[9] + d[13]));
            barrive<B_SC, 256>();
            CUT(pb);
            sts64f(SC + 5120 + sa, (d[2] + d[6]) + (d[10] + d[14]), (d[3] + d[7]) + (d[11] + d[15]));
            PROF(5);
            if (w8 == 0) {
                float x[10];
                bsync<B_S0, 128>();
                tok_scores(x, SC + 3072 + l16); mem_scores(x, SC + 3072 + l16);
                __syncwarp();
                load_frag<WB1, WB2>(WO + t16, F);
                const int g = l16 >> 6, lim = 8 * (g >> 1) + 2 * (c & 3) + (g & 1) - ((l16 >> 1) & 0x18);
                #pragma unroll
                for (int i = 0; i < 8; i++) if (i > lim) x[i] = -INFINITY;
                const float ms = opqf(-SCL * max4lanes(fmaxf(max8(x), fmaxf(x[8], x[9]))));
                CUT(pb);
                #pragma unroll
                for (int i = 0; i < 10; i++) x[i] = ex2(fmaf(x[i], SCL, ms));
                load_frag<WB2, WB3>(WO + t16, F);
                sts128(PT + l16, make_uint4(pack2(x[0], x[1]), pack2(x[2], x[3]), pack2(x[4], x[5]), pack2(x[6], x[7])));
                sts32(PT + 512 + (l16 >> 2), pack2(x[8], x[9]));
                if (!ONE) barrive<B_PT, 160>();
            } else {
                if (ANN == 2) { bsync<B_S0, 128>(); const uint32_t f = lds32(SUM + 268 + opq(t16 >> 16)); REPORT(3, f == s + 1 ? P(2) : 0); } else barrive<B_S0, 128>();
                if (w8 == 1) {
                    mbar_wait(MB_X, ~seg & 1); bulk_expect(MB_X, 32768);
                    if (XPF) prefetch_l2(prm.x + (((seg + XPF) & 63) * 65536 + c * 512), 512);
                    __syncwarp();
                    if (XDL == 300) load_x(tmX, c, seg + 1, (s & 1) ? XT : XT2);
                }
                else if (w8 == 2) {
                    bulk_expect(MB_KV, 36864);
                    bulk_copy(TK, kv_src(c, s + 1), 16384, MB_KV); bulk_copy(TQ, kv_src(c, s + 1) + (32768 + (c & 3) * 4096), 4096, MB_KV);
                    bulk_expect(MB_B, 8192); bulk_expect(MB_R, 4096);
                    __syncwarp();
                }
                bsync<B_SC2, 224>();
                load_frag<WB1, WB3>(WO + t16, F);
                __syncwarp();
                CUT(pb);
            }
            bsync<B_O2, 256>();
            PROF(6);
            float i0, i1;
            WO_MMA(WB3, 0, , );
        } else {
            float a[4][4], v[4][4] = {};
            uint32_t b[16][4];
            barrive_if<B_RD, 256>(redo);
            CUT(pa);
            bsync<B_H0, 256>();
            #pragma unroll
            for (int n = 0; n < PRE1; n++) { LDB(n); __syncwarp(); }
            redo = lds32(SUM + 256 + opq(t16 >> 20));
            PROF(0);
            #pragma unroll
            for (int i = 0; i < 16; i++) {
                if (!(i & 1)) {
                    CUT(pa);
                    if (PRE1 < 8 && i + PRE1 < 16) { LDB(i + PRE1); __syncwarp(); LDB(i + PRE1 + 1); __syncwarp(); }
                    if (PRE1 == 8 && i >= 2 && i < 10) { LDB(i + 6); __syncwarp(); LDB(i + 7); __syncwarp(); }
                    if (i == 6) redo = !late(redo ^ (2 * bc + 1), 0, ~0u);
                    if (i == H2) { barrive_if<B_H2, 256>(!redo); CUT(pa); }
                }
                else if (CO) CUT(pa);
                if (i < 2) { a[2 * i][0] = a[2 * i][1] = a[2 * i][2] = a[2 * i][3] = a[2 * i + 1][0] = a[2 * i + 1][1] = a[2 * i + 1][2] = a[2 * i + 1][3] = 0.f; }
                mmaq(a[2 * (i & 1)], &W[8 * i], b[i][0], b[i][1]); mmaq(a[2 * (i & 1) + 1], &W[8 * i + 4], b[i][2], b[i][3]);
            }
            if (__builtin_expect(redo, 0)) { __syncwarp(); continue; }
            CUT(pa); CUT(pb);
            const uint32_t mG = (l16 & 0x1C0) ? 0 : 0x10001u, mT = (l16 & 0x30) ? 0 : 1;
            ST_X();
            barrive<B_H3, 256>();
            CUT(pa);
            PROF(1);
            #pragma unroll
            for (int i = 7; i >= 0; i--) V_MMA(i, 8);
            ST_V();
            CUT(pb);
            bsync<B_VX, 256>();
            PROF(2);
            uint32_t vf[16], vm[16];
            const uint32_t va = opq(pa), vb = opq(va ^ 0x20);
            #define LD_V() do { _Pragma("unroll") for (int i = 0; i < 4; i++) { const uint32_t a_ = TK + 16384 + ((i & 1) ? vb : va) + (i >> 1) * 4096; \
                ldsm4(vf[4 * i], vf[4 * i + 1], vf[4 * i + 2], vf[4 * i + 3], a_); ldsm4(vm[4 * i], vm[4 * i + 1], vm[4 * i + 2], vm[4 * i + 3], a_ + 8192); } } while (0)
            LD_V();
            __syncwarp();
            load_frag<0, WA0>(WO + t16, F);
            #pragma unroll
            for (int i = 0; i < 16; i++) vf[i] = opq(hadd2(vf[i], vm[i]));
            const char* const xa = at(u_x + (t16 >> 1), rbhi) + (8192 - 1024);
            if (VP) CUT(pb);
            DELAY(VD);
            LD_X(vm, 0); LD_X(vm + 8, 4096);
            __syncwarp();
            load_frag<WA0, WA1>(WO + t16, F);
            CUT(pb);
            float x[10];
            bsync<B_S1, 256>();
            tok_scores(x, SC + l16);
            const float mt = opqf(max8(x));
            if (ANN == 3) REPORT(7, 0);
            CUT(pb);
            PROF(3);
            bsync<B_SC, 256>();
            mem_scores(x, SC + l16);
            const float m1 = fmaxf(mt, fmaxf(x[8], x[9]));
            const float m2 = __shfl_xor_sync(~0u, m1, 1), m3 = __shfl_xor_sync(~0u, m1, 2), m4 = __shfl_xor_sync(~0u, m1, 3);
            CUT(pb);
            load_frag<WA1, WA2>(WO + t16, F);
            barrive<B_SC2, 224>();
            uint32_t p[5], vs[4];
            #define SUM_V() do { _Pragma("unroll") for (int i = 0; i < 4; i++) { const int e = (i >> 1) * 4 + (i & 1); vs[i] = hadd2(hadd2(vm[e], vm[e + 8]), hadd2(vm[e + 2], vm[e + 10])); } } while (0)
            CUT(pb);
            const float ms = -SCL * fmaxf(fmaxf(m1, m2), fmaxf(m3, m4));
            PROF(5);
            #pragma unroll
            for (int i = 0; i < 10; i++) x[i] = fmaf(x[i], SCL, ms);
            x[8] = opqf(ex2(x[8])); x[9] = opqf(ex2(x[9]));
            CUT(pb);
            uint32_t badv = late(stale<4, 2>(vm, tau), stale<4, 2>(vm + 8, tau), mT);
            SUM_V();
            #pragma unroll
            for (int i = 0; i < 4; i++) { x[i] = opqf(ex2(x[i])); vs[i] = opq(vs[i]); }
            const uint32_t z0 = t16 >> 16;
            uint32_t one[4] = {opq(ONES | z0), opq(ONES ^ z0), opq(ONES + z0), opq(ONES - z0)};
            CUT(pb);
            #pragma unroll
            for (int i = 4; i < 8; i++) x[i] = ex2(x[i]);
            #pragma unroll
            for (int i = 0; i < 5; i++) p[i] = pack2(x[2 * i], x[2 * i + 1]);
            float sm[4] = {};
            #define PV(also) do { float o[8] = {}; \
                mma8(o, vs[0], vs[1], p[4]); mma8(o + 4, vs[2], vs[3], p[4]); if (also) mma8(sm, one[0], one[1], p[4]); \
                mmaq(o, vf, p[0], p[1]); mmaq(o + 4, vf + 8, p[0], p[1]); if (also) mmaq(sm, one, p[0], p[1]); \
                mmaq(o, vf + 4, p[2], p[3]); mmaq(o + 4, vf + 12, p[2], p[3]); if (also) mmaq(sm, one, p[2], p[3]); \
                stsm4(OB - 2048 + opq(t16), pack2(o[0], o[1]), pack2(o[2], o[3]), pack2(o[4], o[5]), pack2(o[6], o[7])); } while (0)
            PV(true);
            if (w8 == 4) sts64f(SUM + (l16 >> 1), sm[0], sm[1]);
            if (__builtin_expect(badv, 0)) {
                int n_ = 0;
                uint32_t vm[16];
                const char* const xa = at(u_x + (8192 - 1024) + (opq(t16) >> 1), rbhi);
                do { RETRY(3, 1); LD_X(vm, 0); LD_X(vm + 8, 4096); } while (late(stale<4, 2>(vm, tau), stale<4, 2>(vm + 8, tau), mT) && ++n_ < SPIN_LIMIT);
                SUM_V();
                PV(false);
            }
            if (ONE) bsync<B_O2, 256>(); else { barrive<B_O2, 256>(); bsync<B_O, 128>(); }
            PROF(6);
            float i0 = sm[0], i1 = sm[1];
            #define GET_P() if (!ONE) bsync<B_PT, 160>(); lds128u(p, PT + l16); p[4] = lds32(PT + 512 + (l16 >> 2))
            #define TOK_PV() { const uint32_t z = t16 >> 17; one[0] = ONES | z; one[1] = ONES ^ z; one[2] = ONES + z; one[3] = ONES - z; } \
                _Pragma("unroll") for (int i = 0; i < 12; i++) ot[i >> 2][0][i & 3] = ot[i >> 2][1][i & 3] = 0.f; \
                mma8(ot[0][0], vs[0], vs[1], p[4]); mma8(ot[1][0], vs[2], vs[3], p[4]); mma8(ot[2][0], one[0], one[1], p[4]); \
                mmaq(ot[0][1], vf + 4, p[2], p[3]); mmaq(ot[1][1], vf + 12, p[2], p[3]); mmaq(ot[2][1], one, p[2], p[3]); CUT(pa)
            WO_MMA(WA2, WA3, GET_P(), TOK_PV());
            CUT(pa);
            mmaq(ot[0][0], vf, p[0], p[1]); mmaq(ot[1][0], vf + 8, p[0], p[1]); mmaq(ot[2][0], one, p[0], p[1]);
            CUT(pb);
            barrive<B_GO, 256>();
        }
        CUT(pb);
        PROF(7);
        #define PK_O() const float j0 = rcpf(ot[2][0][0] + ot[2][1][0]), j1 = rcpf(ot[2][0][1] + ot[2][1][1]); uint32_t ow[4]; \
            _Pragma("unroll") for (int i = 0; i < 4; i++) \
                ow[i] = opq(pack2((ot[i >> 1][0][2 * (i & 1)] + ot[i >> 1][1][2 * (i & 1)]) * j0, (ot[i >> 1][0][2 * (i & 1) + 1] + ot[i >> 1][1][2 * (i & 1) + 1]) * j1))
        #define ST_O() do { uint32_t* og = (uint32_t*)((char*)g_O + (u_og + (l16 >> 2))); \
            _Pragma("unroll") for (int i = 0; i < 4; i++) og[(i >> 1) * 256 + (i & 1) * 32] = ow[i]; } while (0)
        #define BSO() ((u_bs) ^ ((l16 & 0x10) + ((l16 >> 3) & 0xC) + (l16 & 0x80) * 0x20 + (l16 & 0x100) * 0x80))
        const uint32_t taus = phase(seg);
        const uint64_t* const dq = c_xd + (s & 1) * 32; const uint64_t* const dv = dq + (wg * 16 | uz);
        float acc[16], acv[16];
        uint32_t u[8];
        if constexpr (wg == 0) {
            if (s == NSEG - 1) { bsync<B_GO, 256>(); st_g32(at(BSO(), rbhi), 0); mbar_wait(MB_KV, 1); if (XDL == 300) mbar_wait(MB_X, 1); break; }
            load_frag<16 - EV, 16, 2048>(VEB + t16, T);
            bsync<B_GO, 256>();
            PROF(8);
            wg_run<0, 16 - EV>(acv, T, dv);
            wg_run<16 - EV, 16>(acv, T, dv);
            wg_run<0, 5>(acc, W, dq); wg_wait<1>();
            qk_pack(acv, u);
            #pragma unroll
            for (int i = 0; i < 8; i++) u[i] = opq(u[i]);
            CUT(pa);
            wg_run<5, 8>(acc, W, dq);
            __syncwarp();
            sts128(SC + opq(t16), make_uint4(u[0], u[1], u[2], u[3])); sts128(SC + 2048 + opq(t16), make_uint4(u[4], u[5], u[6], u[7]));
            barrive<B_VX, 256>();
            __syncwarp();
            PROF(9);
            wg_run<8, 12>(acc, W, dq);
            CUT(pa);
            char* const bs = at(opq(BSO()), opq(rbhi));
            CUT(pa);
            wg_run<12, 15>(acc, W, dq);
            CUT(pa);
            const uint32_t ro = opq(l16 * 8 + ((l16 & 0x70) ^ ((w8 & 3) << 5))), ro2 = opq(ro ^ 0x10);
            const uint32_t mG = opq((l16 & 0x1C0) ? 0 : 0x10001u), mB = opq((((l16 >> 2) & 4) + ((l16 >> 5) & 3)) == ((u_bs >> 7) & 7) ? 1 : 0), zz = t16 >> 18;
            CUT(pa);
            wg_run<15, 18>(acc, W, dq);
            CUT(pa);
            const uint32_t one[4] = {opq(ONES | zz), opq(ONES ^ zz), opq(ONES + zz), opq(ONES - zz)};
            const uint32_t par = s & 1, tt = tau * 0x10001u;
            CUT(pa);
            wg_run<18, RP>(acc, W, dq);
            CUT(pa);
            PROF(10);
            mbar_wait(MB_R, par);
            PROF(14);
            uint32_t x[8], bad;
            float d[4][4];
            #define SUM_R() do { ldsm4t(x[0], x[1], x[2], x[3], RS + ro); ldsm4t(x[4], x[5], x[6], x[7], RS + ro2); \
                _Pragma("unroll") for (int i = 0; i < 4; i++) { d[i][0] = d[i][1] = d[i][2] = d[i][3] = 0.f; mmaq(d[i], one, x[2 * i], x[2 * i + 1]); } } while (0)
            #define PUT_B() do { bad = late(stale<2, 1>(x, tt), stale<2, 1>(x + 2, tt), mG); \
                const uint32_t w0 = pack2(d[0][0] + d[1][0], d[0][1] + d[1][1]), w1 = pack2(d[2][0] + d[3][0], d[2][1] + d[3][1]); \
                asm volatile("{ .reg .pred p; setp.eq.b32 p, %2, 0; @p st.relaxed.gpu.global.u32 [%0], %1; }" :: "l"(bs), "r"(tagm((l16 & 0x40) ? w1 : w0, mB, tt)), "r"(bad) : "memory"); } while (0)
            SUM_R();
            CUT(pa);
            wg_run<RP, (RP + RQ < 32 ? RP + RQ : 32)>(acc, W, dq);
            if (RP + RQ >= RL) barrive<B_BT, 256>();
            CUT(pa);
            PUT_B();
            const uint32_t tb = lds32(SUM + 272 + 28 + zz);
            CUT(pa);
            PROF(11);
            if (RP + RQ < RL) { wg_run<RP + RQ, RL>(acc, W, dq); __syncwarp(); barrive<B_BT, 256>(); __syncwarp(); }
            wg_run<(RP + RQ < RL ? RL : RP + RQ), 32>(acc, W, dq);
            CUT(pa);
            AGAIN(5, ld_g128(x, at(u_rl + opq(ro), rbhi)); ld_g128(x + 4, at(u_rl + opq(ro2), rbhi)); sts128(RS + ro, make_uint4(x[0], x[1], x[2], x[3])); sts128(RS + ro2, make_uint4(x[4], x[5], x[6], x[7]));
                     CUT(pa); __syncwarp(); SUM_R(); PUT_B(), bad)
            #define REQ_B() if (w8 == 3) { TRC(13, gtime() - tb); wait_g(tb, t16); GET_B(0); PROFW(13, 3); }
            if (!BL) REQ_B();
            const uint32_t ps = opq(pb & 0xFFFF), ps2 = opq(ps ^ HI8);
            char* const qd0 = TOK_DST() + ps; char* const qd1 = TOK_DST() + ps2;
            TAGM();
            wg_wait<0>();
            pack_tag(acc, u, taus, tm);
            #pragma unroll
            for (int i = 0; i < 8; i++) u[i] = opq(u[i]);
            CUT(pa);
            if (BL) REQ_B();
            bsync<B_S0, 128>();
            st_if(seg < NSEG, qd0, u); st_if(seg < NSEG, qd1, u + 4);
            if (XDL >= 200 && XDL < 300 && w8 == 1) { CUT(pb); DELAY(XDL - 200); load_x(tmX, c, seg + 1, (s & 1) ? XT : XT2); }
            PROF(12);
        } else {
            #define LAST() __reduce_max_sync(~0u, max(max(an[0], an[1]), max(an[2], an[3])))
            PK_O();
            CUT(pa);
            if (s == NSEG - 1) { ST_O(); break; }
            PROF(8);
            if (w8 != 7) {
                load_frag<16 - EV, 16 - EV + TA0, 2048>(VEB + t16, T);
                mbar_wait(MB_KV, s & 1);
                AGAIN(0, refetch_kv(c, s + 1, w8 - 4, l16), kv_stale(w8 - 4, l16, phase(s + 1)))
            } else {
                uint32_t tr = LAST();
                AGAIN(8, ld_g128(an, at(u_ta + l16, rbhi)); tr = LAST(), late(stale<2, 1>(an, s), stale<2, 1>(an + 2, s), 31))
                tr = (tr & ~31u) + P(0);
                TRC(14, gtime() - tr);
                wait_g(tr, t16);
                if (R4) { for (int i = 0; i < 4; i++) bulk_copy(RS + i * 1024, at(u_rl + i * 1024, rbhi), 1024, MB_R); }
                else bulk_copy(RS, at(u_rl, rbhi), 4096, MB_R);
                PROFW(14, 3);
                sts32(SUM + 272 + 28, tr + P(1));
                load_frag<16 - EV, 16 - EV + TA0, 2048>(VEB + t16, T);
                if (XDL < 100) { CUT(pb); DELAY(XDL); load_x(tmX, c, seg + 1, (s & 1) ? XT : XT2); }
            }
            CUT(pa);
            bsync<B_VX, 256>();
            lds128u(u, SC - 2048 + opq(t16)); lds128u(u + 4, SC + opq(t16));
            CUT(pa);
            ST_O();
            CUT(pa);
            load_frag<16 - EV + TA0, 16 - EV + TA, 2048>(VEB + t16, T);
            acc_init(acv, u);
            #pragma unroll
            for (int i = 0; i < 16; i++) acv[i] = opqf(acv[i]);
            const uint32_t ps = opq(pb & 0xFFFF), ps2 = opq(ps ^ HI8);
            CUT(pa);
            PROF(9);
            if (XDL == 100 && w8 == 7) load_x(tmX, c, seg + 1, (s & 1) ? XT : XT2);
            bsync<B_BT, 256>();
            CUT(pa);
            wg_run<0, 3>(acc, W, dq);
            PROF(11);
            wg_run<3, NT, true>(acc, W, dq);
            __syncwarp();
            load_frag<16 - EV + TA, 16, 2048>(VEB + t16, T);
            __syncwarp();
            wg_run<NT, NB>(acc, W, dq);
            char* const qd0 = TOK_DST() + ps; char* const qd1 = TOK_DST() + ps2;
            TAGM();
            wg_run<NB, 32>(acc, W, dq);
            wg_run<0, 5, true>(acv, T, dv);
            wg_wait<1>();
            PROF(12);
            pack_tag(acc, u, taus, tm);
            #pragma unroll
            for (int i = 0; i < 8; i++) u[i] = opq(u[i]);
            CUT(pa);
            wg_run<5, 16 - EV>(acv, T, dv);
            __syncwarp();
            st_if(seg < NSEG, qd0, u); st_if(seg < NSEG, qd1, u + 4);
            __syncwarp();
            wg_run<16 - EV, 16>(acv, T, dv);
            CUT(pa);
            PROF(10);
            wg_wait<0>();
            PROF(13);
            pack_tag(acv, u, taus, tm);
            st_if(seg < NSEG, qd0 + 16384, u); st_if(seg < NSEG, qd1 + 16384, u + 4);
        }
        sb++;
        u_rs ^= 1 << 20; u_rl ^= 1 << 20; u_bs ^= 1 << 20; u_bl ^= 1 << 20; u_x ^= 1 << 20; u_xs ^= 1 << 20; u_ta ^= 1 << 20; u_rp ^= 1 << 20; u_og += 262144;
    }
}

namespace ck {
constexpr uint32_t UPL = 144 * 16 + 64, UCH = 2 * UPL;
constexpr uint32_t FCP = 4160, FCH = 2 * FCP;
template <int NW> struct At { static constexpr uint32_t K = NW == 2 ? mk::XT : mk::SB, V = K + 32768, F = NW == 2 ? V : V + 32768, U = F + 8 / NW * FCH; };
static_assert(At<2>::U + 4 * UCH <= mk::OB && At<1>::U + 8 * UCH <= mk::OB, "");
}
struct ConvIn { const bf16 *shift_k, *ssm_k, *ssm_D; };
template <int NW> struct ConvRaw { uint4 f[8 / NW], sk[4 / NW]; uint32_t fn, d; };
template <int NW> __device__ __forceinline__ void strip_request(const CUtensorMap* tmK, int grp) {
    mbar_expect(mk::MB_C, 65536);
    #pragma unroll 1
    for (int i = 0; i < 16; i++) tma3d(ck::At<NW>::K + i * 4096, tmK + (i >> 3), grp * 8, 0, i & 7, mk::MB_C);
}
template <int NW> __device__ __forceinline__ void conv_load(ConvRaw<NW>& r, const ConvIn& in, int ch0) {
    const int tid = threadIdx.x, w = tid >> 5, ch = ch0 + w / NW, e = w % NW;
    const bf16* fp = in.ssm_k + (size_t)ch * SEQ + e * 1024;
    #pragma unroll
    for (int i = 0; i < 8 / NW; i++) r.f[i] = __ldg((const uint4*)fp + (tid & 31) + 32 * i);
    r.fn = e == NW - 1 ? 0 : __ldg((const uint32_t*)(fp + 1024));
    r.d = __ldg((const unsigned short*)in.ssm_D + ch);
    #pragma unroll
    for (int i = 0; i < 4 / NW; i++) r.sk[i] = __ldg((const uint4*)(in.shift_k + ch0 * 4) + i);
}
template <int NW> __device__ __forceinline__ void kv_build(const ConvRaw<NW>& r, int ch0) {
    using namespace ck;
    const int tid = threadIdx.x;
    if (tid < 32 * 8 / NW) sts128(At<NW>::U + (tid >> 4) * UPL + (tid & 15) * 16, make_uint4(0, 0, 0, 0));
    #pragma unroll
    for (int hf = 0; hf < 2 / NW; hf++) {
        const uint32_t a = tid * 16 + (ch0 & 4) * 2 + hf * 8;
        float2 kr[11], vr[8];
        #pragma unroll
        for (int i = 0; i < 11; i++) { kr[i] = lds64f(At<NW>::K + ((i + 5) & 7) * 4096 - (i < 3) * 16 + a); if (i < 3 && !tid) kr[i] = make_float2(0.f, 0.f); }
        #pragma unroll
        for (int i = 0; i < 8; i++) vr[i] = lds64f(At<NW>::V + i * 4096 + a);
        #pragma unroll
        for (int ch = 0; ch < 4; ch++) {
            const uint32_t s01 = ((const uint32_t*)r.sk)[8 * hf + 2 * ch], s23 = ((const uint32_t*)r.sk)[8 * hf + 2 * ch + 1];
            const float sk[4] = {bflo(s01), bfhi(s01), bflo(s23), bfhi(s23)};
            float kf[11], kv[8];
            #pragma unroll
            for (int i = 0; i < 11; i++) { const uint32_t wd = __float_as_uint((ch & 2) ? kr[i].y : kr[i].x); kf[i] = (ch & 1) ? bfhi(wd) : bflo(wd); }
            #pragma unroll
            for (int i = 0; i < 8; i++) {
                const uint32_t wv = __float_as_uint((ch & 2) ? vr[i].y : vr[i].x);
                kv[i] = fmaf(kf[i + 3], sk[0], fmaf(kf[i + 2], sk[1], fmaf(kf[i + 1], sk[2], kf[i] * sk[3]))) * ((ch & 1) ? bfhi(wv) : bflo(wv));
            }
            sts128(At<NW>::U + (hf * 4 + ch) * UCH + (tid & 1) * UPL + (16 + (tid >> 1)) * 16,
                   make_uint4(pack2(kv[0], kv[1]), pack2(kv[2], kv[3]), pack2(kv[4], kv[5]), pack2(kv[6], kv[7])));
        }
    }
}
template <int NW> __device__ __forceinline__ void conv_filter(const ConvRaw<NW>& r, bool on) {
    using namespace ck;
    constexpr int N = 8 / NW;
    const int w = threadIdx.x >> 5, lane = threadIdx.x & 31, e = w % NW;
    const uint32_t fb = At<NW>::F + w / NW * FCH;
    if (on && !e && lane < 8) { sts32(fb + 4128 + lane * 4, 0); sts32(fb + FCP + 4128 + lane * 4, lane ? 0 : r.f[0].x & 0xFFFFu); }
    #pragma unroll
    for (int i = 0; i < N; i++) {
        const int vi = e * 128 + lane + 32 * i;
        const uint4 x = r.f[i];
        const uint32_t a = __shfl_down_sync(~0u, x.x, 1), b = i < N - 1 ? __shfl_sync(~0u, r.f[i < N - 1 ? i + 1 : i].x, 0) : r.fn;
        const uint32_t nxt = lane == 31 ? b : a;
        const uint32_t ea = fb + (2056 - 8 * vi) * 2;
        if (on) sts128(ea, make_uint4(__byte_perm(x.w, 0, 0x1032), __byte_perm(x.z, 0, 0x1032), __byte_perm(x.y, 0, 0x1032), __byte_perm(x.x, 0, 0x1032)));
        if (on) sts128(ea + FCP, make_uint4(__byte_perm(nxt, x.w, 0x7610), __byte_perm(x.w, x.z, 0x7610), __byte_perm(x.z, x.y, 0x7610), __byte_perm(x.y, x.x, 0x7610)));
    }
}
template <int NW> __device__ __forceinline__ void conv_mma(int ch0, uint32_t d, uint32_t zero, bool on) {
    using namespace ck;
    constexpr int N = 16 / NW;
    const int w = threadIdx.x >> 5, lane = threadIdx.x & 31, ch = w / NW, e = w % NW, g = lane >> 2, t = lane & 3;
    float acc[N][4] = {};
    uint32_t fa = At<NW>::F + ch * FCH + ((g & 1) ? (2063 - g + 2 * t) * 2 : FCP + (2064 - g + 2 * t) * 2);
    uint32_t ua = At<NW>::U + ch * UCH + ((lane >> 3) & 1) * UPL + (24 + (e - NW) * 8 + (lane >> 4) * 8 + (lane & 7)) * 16;
    uint32_t Fr[32], A[2][8], yo = (ch0 + ch) * 512 + e * 32 + t * 8 + g;
    const uint32_t t16 = lane | zero;
    #define LD_U(m0, m1) _Pragma("unroll") for (int m = m0; m < m1; m++) ldsm4(Fr[4 * m], Fr[4 * m + 1], Fr[4 * m + 2], Fr[4 * m + 3], ua + m * 256)
    #define LD_F(b, o, p) _Pragma("unroll") for (int i = 0; i < 2; i++) { const uint32_t x_ = fa - (o) * 32 - (i ? 15 - (p) : (p)) * 256; \
        A[b][4 * i] = lds32(x_); A[b][4 * i + 1] = lds32(x_ - 16); A[b][4 * i + 2] = lds32(x_ + 16); }
    #define ROW(a, q, j0, j1, after) _Pragma("unroll") for (int j = 0; j < N; j++) if (j >= (j0) && j < (j1)) { \
        mmaq(acc[j], a, Fr[2 * (NW * j + NW - 1 - (q))], Fr[2 * (NW * j + NW - 1 - (q)) + 1]); after; }
    LD_U(0, 8);
    LD_F(0, 0, 0);
    {
        const uint32_t da = (g >> 1) == t ? d << ((g & 1) * 16) : 0, D[4] = {da, zero, zero >> 1, da ^ zero};
        ROW(D, 0, 0, N, );
    }
    #pragma unroll 1
    for (int r = on ? 0 : 7; r < 8; r++) {
        ua -= 16;
        #pragma unroll
        for (int p = 0; p < 8; p++) {
            uint32_t* const a = A[p & 1];
            a[3] = a[0] ^ zero; a[7] = a[4] ^ zero;
            LD_F(~p & 1, p == 7, (p + 1) & 7);
            if (p >= 2 && !(p & 1)) { LD_U(8 - p / 2, 9 - p / 2); }
            const int j0 = p / NW, j1 = (15 - p) / NW, jm = j0 + (j1 - j0) / 2;
            ROW(a, p, j0, jm, );
            if (CC) CUT(yo);
            ROW(a + 4, 15 - p, j1, N, if (CC) CUT(yo));
            ROW(a, p, jm, j1, );
            if (CC) CUT(yo);
            ROW(a, p, j1, N, if (CC) CUT(yo));
        }
        LD_U(0, 5);
        fa -= 32;
    }
    uint2* y = (uint2*)g_Y + yo;
    #pragma unroll
    for (int j = 0; j < N; j++) {
        const uint32_t p0 = pack2(acc[j][0], acc[j][2]), p1 = pack2(acc[j][1], acc[j][3]), x = __shfl_xor_sync(~0u, (g & 1) ? p0 : p1, 4);
        const uint32_t lo = (g & 1) ? x : p0, hi = (g & 1) ? p1 : x;
        if (on) y[j * 32 * NW] = make_uint2(__byte_perm(lo, hi, 0x5410), __byte_perm(lo, hi, 0x7632));
    }
}
__device__ __noinline__ void spare(const CUtensorMap* tmK, const ConvIn in, int i, uint32_t zero) {
    const int w = __shfl_sync(~0u, threadIdx.x >> 5, 0);
    ConvRaw<1> raw;
    #pragma unroll 1
    for (int grp = 56 + i, n = 0; grp < NSP; grp += 4, n++) {
        if (n) { mbar_wait(mk::MB_C, ~n & 1); kv_build<1>(raw, grp * 8); conv_filter<1>(raw, true); }
        const uint32_t d = raw.d;
        asm volatile("fence.proxy.async.shared::cta;" ::: "memory");
        __syncthreads();
        if (grp + 4 < NSP) {
            if (w == 0 && elect()) { mbar_expect(mk::MB_C, 65536); for (int j = 0; j < 2; j++) tma3d(ck::At<1>::K + j * 32768, tmK + 2 + j, grp * 8 + 32, 0, 0, mk::MB_C); }
            __syncwarp();
            conv_load<1>(raw, in, grp * 8 + 32);
        }
        if (n) conv_mma<1>(grp * 8, d, zero, true);
        __syncthreads();
    }
}

__device__ __forceinline__ uint32_t round_trip(char* a, int n) {
    uint32_t best = 0x7FFFu;
    #pragma unroll 1
    for (int i = 0; i < n; i++) {
        uint32_t v; const uint32_t t0 = clk();
        asm volatile("atom.relaxed.gpu.global.exch.b32 %0, [%1], %2;" : "=r"(v) : "l"(a), "r"(i) : "memory");
        if (v == 0x7FC1A5A5u) g_err = 2;
        best = min(best, clk() - t0);
    }
    return (__popc((uint32_t)(uintptr_t)a & HOME_BITS) & 1) ? best << 16 | 0x7FFFu : best | 0x7FFF0000u;
}
__device__ __forceinline__ int place(int by_sm) {
    uint32_t sm = blockIdx.x;
    if (by_sm) asm volatile("mov.u32 %0, %%smid;" : "=r"(sm));
    const uint32_t g = sm < 64 ? (sm & 15) >> 1 : 1 + (sm - 64) % 14 / 2, j = sm < 64 ? sm >> 4 : 4 + (sm - 64) / 14;
    return sm < 120 ? (g ? g * 16 - 8 : 0) + j * 2 + (sm & 1) : sm;
}
__device__ __forceinline__ void publish(char* rb, int p) {
    const int t = threadIdx.x, i = p * 2 + (t >> 6);
    char* line = rb + RB_P + (i & 31) * 128 + (i >> 5) * 8192 + (t & 32) * 128;
    if ((t & 31) < 2) st_g128(line + (t & 1) * 16, 0, 0, 0, 0);
    __syncwarp();
    if (!(t & 31)) sts32(mk::SUM + (t >> 3), round_trip(line, NPR));
    bsync<1, 128>();
    if (t == 32) {
        const uint4 x = lds128(mk::SUM);
        st_g32(g_cls + p, 0x80000000u | __vminu2(__vminu2(x.x, x.y), __vminu2(x.z, x.w)));
    }
    __syncwarp();
}
__device__ __forceinline__ uint32_t survey(uint32_t& x, int n) {
    const int lane = threadIdx.x & 31;
    uint32_t a[4] = {}, b[2] = {};
    while (__any_sync(~0u, !((a[0] & a[1] & a[2] & a[3] & b[0] & b[1]) >> 31)) && --n > 0) { ld_g128(a, g_cls + lane * 4); ld_g64(b, g_cls + 120 + lane % 6 * 2); }
    const uint32_t m = __vminu2(__vminu2(a[0], a[1]), __vminu2(a[2], a[3])), e = __vminu2(b[0], b[1]);
    const uint32_t M = __ballot_sync(~0u, (m >> 16 & 0x7FFF) < (m & 0xFFFF)) & 0x3FFFFFFF, E = __ballot_sync(~0u, (e >> 16 & 0x7FFF) < (e & 0xFFFF)) & 63;
    const int x0 = min(max(max(__popc(M) - 14, 2 - __popc(E) / 2), 0), min(2, (6 - __popc(E)) / 2));
    x = E | x0 << 8;
    return M | (x0 < 1) << 30 | (x0 < 2) << 31;
}
__device__ __forceinline__ int role(int p, uint32_t x) {
    const int i = (p - 120) >> 1, x0 = x >> 8, side = x >> i & 1, r = __popc((side ? x : ~x) & ((1 << i) - 1)), e0 = 6 - __popc(x & 63);
    const int pair = !side ? (r < 2 * x0 ? r : 4 + r - 2 * x0) : (r < 4 - 2 * x0 ? 2 * x0 + r : e0 + r);
    return 120 + 2 * pair + (p & 1);
}
__device__ __forceinline__ void tma_prefetch(const CUtensorMap* m, int c0, int c1) {
    asm volatile("cp.async.bulk.prefetch.tensor.2d.L2.global [%0, {%1, %2}];" :: "l"(m), "r"(c0), "r"(c1) : "memory");
}

struct KVMaps { CUtensorMap m[4]; };
__global__ void __launch_bounds__(256, 1)
main_kernel(const __grid_constant__ CUtensorMap tmWq, const __grid_constant__ CUtensorMap tmWk, const __grid_constant__ CUtensorMap tmWv,
            const __grid_constant__ CUtensorMap tmWo, const __grid_constant__ CUtensorMap tmX,
            const __grid_constant__ KVMaps tmK, const bf16* __restrict__ mem0,
            const __grid_constant__ ConvIn in, const __grid_constant__ MainParams prm) {
    using namespace mk;
    extern __shared__ __align__(1024) uint8_t smem_raw[];
    if (smem_u32(smem_raw) != SB) __trap();
    TL(0); TL(2); TS(0);
    const int tid0 = threadIdx.x, w8 = __shfl_sync(~0u, tid0 >> 5, 0), wg = w8 >> 2;
    const int p = __shfl_sync(~0u, place(prm.by_sm), 0);
    const uint32_t t16 = tid0 * 16, rbhi = (uint32_t)((uintptr_t)prm.rb >> 32);
    int c = p, budget = 1;
    uint32_t W[128], T[64], m0[8], pa, pb, u_rs, u_rl, u_bs, u_bl;
    ConvRaw<2> raw;
    asm volatile("griddepcontrol.launch_dependents;" ::: "memory");
    uint32_t on = opq(DRY ? wg ^ 1 : 1);
    #define PART(L) if (!on) goto START; L:
    #define SYNC() if (on) __syncthreads()
    #define WAIT(mb, ph) if (on) mbar_wait(mb, ph)
    if (!wg) {
        if (w8 == 0 && elect()) {
            for (int i = 0; i < 9; i++) mbar_init(BAR + i * 8, 1);
            asm volatile("fence.mbarrier_init.release.cluster;" ::: "memory");
            asm volatile("fence.proxy.async.shared::cta;" ::: "memory");
            sts32(SUM + 256, 0); sts32(SUM + 268, 0); mbar_arrive(MB_B);
        }
        if (tid0 >= 124) asm volatile("prefetch.tensormap [%0];" :: "l"(tid0 == 124 ? &tmWq : tid0 == 125 ? &tmWk : tmK.m + (tid0 & 1)) : "memory");
        __syncwarp();
        publish(prm.rb, p);
    } else {
        if (!c_xd[(tid0 >> 3 & 15) * 6]) g_err = 3;
        __syncwarp();
        if (DRY) switch (p & 7) { case 0: goto P0; case 1: goto P1; case 2: goto P2; case 3: goto P3; case 4: goto P4; case 5: goto P5; case 6: goto P6; default: goto P7; }
    }
START:
    on = opq(1);
    budget = SPIN_LIMIT;
    TS(1);
    if (p >= 120) {
        uint32_t x;
        survey(x, SPIN_LIMIT);
        c = role(p, x);
        TS(2);
        if (c >= 128) { spare(tmK.m, in, c - 128, prm.zero); TLX(18); return; }
    }
    conv_load<2>(raw, in, p * 4);
    #pragma unroll
    for (int i = 0; i < 8; i++) m0[i] = __ldg((const uint32_t*)(mem0 + i * DM + (c & 1) * 512) + tid0);
    if (tid0 < 16) g_gate[c * 16 + tid0] = -1.f;
    if (w8 == 0 && elect()) {
        if (p < 120) strip_request<2>(tmK.m, p >> 1);
        mbar_expect(MB_WQ, 65536); mbar_expect(MB_WK, 65536);
        for (int i = 0; i < 2; i++) { tma2d(WO + i * 32768, &tmWq, (c >> 1) * 64, (c & 1) * 512 + i * 256, MB_WQ); tma2d(WV + i * 32768, &tmWk, (c >> 1) * 64, (c & 1) * 512 + i * 256, MB_WK); }
    }
    __syncthreads();
    if (p < 120) mbar_wait(MB_C, 0);
    TS(3);
P0:
    kv_build<2>(raw, p * 4);
    SYNC();
    TS(4);
PART(P1)
    if (w8 == 0 && elect()) {
        mbar_expect(MB_X, 32768); tma3d(XT, &tmX, 0, 32, (c & 1) * 8, MB_X);
        for (int i = 0; i < 4; i++) tma_prefetch(&tmWo, (c & 3) * 256 + i * 64, (c >> 2) * DH);
        for (int i = 0; i < 2; i++) tma_prefetch(&tmWv, (c >> 1) * 64, (c & 1) * 512 + i * 256);
    }
    __syncwarp();
    conv_filter<2>(raw, on);
    SYNC();
    TS(5);
PART(P2)
    conv_mma<2>(p * 4, raw.d, prm.zero, on && p < 120);
    TS(6);
PART(P3)
    asm volatile("fence.proxy.async.shared::cta;" ::: "memory");
    SYNC();
    if (w8 == 0 && elect()) { mbar_expect(MB_KV, 32768); tma3d(TK, &tmX, 0, 0, (c & 1) * 8, MB_KV); }
    #pragma unroll
    for (int i = 0; i < 2; i++) {
        const uint32_t e = i ? 0x7632 : 0x5410;
        sts128(MEM + tid0 * 32 + i * 16, make_uint4(__byte_perm(m0[0], m0[1], e), __byte_perm(m0[2], m0[3], e), __byte_perm(m0[4], m0[5], e), __byte_perm(m0[6], m0[7], e)));
    }
    WAIT(wg ? MB_WK : MB_WQ, 0);
    TS(7);
    load_tile<0, 32>(tile_off(tid0 & 31, 2 * (w8 & 3)) + (wg ? WV : WO), W);
    SYNC();
    TS(8);
    if (w8 == 0 && elect()) {
        mbar_expect(MB_WO, 65536);
        for (int i = 0; i < 4; i++) tma2d(WO + i * 16384, &tmWo, (c & 3) * 256 + i * 64, (c >> 2) * DH, MB_WO);
        mbar_expect(MB_WV, 65536);
        for (int i = 0; i < 2; i++) tma2d(WV + i * 32768, &tmWv, (c >> 1) * 64, (c & 1) * 512 + i * 256, MB_WV);
    }
    __syncwarp();
PART(P4)
    {
        const int lane = tid0 & 31, w = w8 & 3, g = lane >> 2, t = lane & 3;
        auto vec = [](int hf, int gg, int ch) { return hf * 512 + (gg >> 1) * 128 + (gg & 1) * 64 + ((ch ^ (gg >> 1) ^ (hf << 1)) << 4); };
        const int kg = ((lane >> 3) & 1) * 4 + ((lane & 7) >> 1);
        pa = wg ? w * 1024 + vec((lane >> 3) & 1, lane & 7, lane >> 4)
                : ((lane >> 4) * 4096 + w * 1024 + vec(lane & 1, kg, 2 * (w & 1))) | ((lane & 8) * 256 + w * 256 + (lane & 1) * 128 + ((((lane >> 4) ^ (lane & 1)) * 4 + ((lane & 7) >> 1)) << 4)) << 16;
        pb = (wg ? w * 1024 + vec(0, g, t) : t * 4096 + w * 256 + g * 16) | (w * 256 + t * 64 + (g & 3) * 8 + (g >> 2) * 4) << 16;
    }
    #define ST_TOK(o) do { const uint32_t ps = pb & 0xFFFF; TAGM(); pack_tag(acc, u, 1, tm); \
        st_if(on, tok_dst(c, seg, wg) + ((o) + ps), u); st_if(on, tok_dst(c, seg, wg) + ((o) + (ps ^ HI8)), u + 4); } while (0)
    #pragma unroll 1
    for (int seg = on; seg >= 0; seg--) {
        float acc[16];
        uint32_t u[8];
        WAIT(seg ? MB_X : MB_KV, 0);
        wg_run<0, 32>(acc, W, c_xd + (seg ? 0 : 64));
        wg_wait<0>();
        ST_TOK(0);
    }
    TS(9);
PART(P5)
    {
        WAIT(MB_WO, 0);
        TS(10);
        const int lane = tid0 & 31;
        const uint32_t a = (tid0 >> 6) * 16384 + tile_off(lane, (w8 & 1) * 4) + WO;
        #pragma unroll
        for (int i = 0; i < 16; i++) ldsm4t(T[4 * i], T[4 * i + 1], T[4 * i + 2], T[4 * i + 3], ((i & 2) ? a ^ 32 : a) + ((i >> 2) + 4 * (i & 1)) * 2048);
        SYNC();
        const uint32_t d = WO + w8 * 512 + ((lane >> 3) * 4 + (lane & 3)) * 16 + ((lane >> 2) & 1) * 4;
        #pragma unroll
        for (int i = 0; i < 64; i++) sts32_if(on, d + (i >> 2) * 4096 + (i & 1) * 256 + (i & 2) * 4, T[i]);
    }
    TS(11);
    WAIT(MB_WV, 0);
    TS(12);
    load_tile<0, 16>(tile_off(tid0 & 31, 2 * (w8 & 3)) + wg * 32768 + WV, T);
PART(P6)
    #pragma unroll 1
    for (int seg = 0; seg <= on; seg++) {
        float acc[16];
        uint32_t u[8];
        wg_run<0, 16>(acc, T, c_xd + (seg ? 0 : 64) + wg * 16);
        wg_wait<0>();
        const uint32_t x = SC + seg * 4096 + (t16 & 2047);
        if (!wg) { qk_pack(acc, u); sts128(x, make_uint4(u[0], u[1], u[2], u[3])); sts128(x + 2048, make_uint4(u[4], u[5], u[6], u[7])); }
        SYNC();
        if (wg) { lds128u(u, x); lds128u(u + 4, x + 2048); acc_add(acc, u); ST_TOK(16384); }
    }
    TS(13);
PART(P7)
    if (w8 == 1) { bulk_expect(MB_X, 32768); load_x(&tmX, c, 2, XT); }
    {
        const int lane = tid0 & 31, h = c >> 2, j = c & 3;
        uint32_t cl;
        const uint32_t M = survey(cl, budget), below = (1u << h) - 1;
        const int pos = ((M >> h) & 1) ? 32 - __popc(M) + __popc(M & below) : __popc(~M & below), G = pos >> 4, rk = pos & 15;
        auto half = [&](uint32_t off) { return (uint32_t)(uintptr_t)prm.rb + off + ((__popc(off & HOME_BITS) ^ G) & 1) * 4096; };
        auto rpair = [&](int m) { return RB_R + (j << 16) + ((m & 1) << 13) + (((m >> 1) & 3) << 14) + ((m >> 3) << 18); };
        u_rs = (half(rpair(2 * w8)) ^ (G << 12)) + h * 128 + (h & 7) * 16;
        u_rl = half(rpair(rk));
        u_bs = (uint32_t)(uintptr_t)prm.rb + RB_B + ((j & 1) << 13) + ((j >> 1) << 16) + rk * 256 + G * 128 + (w8 & 3) * 32;
        u_bl = half(RB_B + ((c & 1) << 16));
        if (w8 == 0) {
            const char* v0 = kv_src(c, 0) + 16384 + lane * 128 + (lane & 3) * 4;
            do cl = ld_g32(v0) & ld_g32(v0 + 4096) & ld_g32(v0 + 8192) & ld_g32(v0 + 12288); while (__any_sync(~0u, !(cl & 1)) && --budget > 0);
            get_kv(c, 0);
        }
    }
    TS(14);
    WAIT(MB_KV, 1);
    TS(15);
    if (w8 > 4) while (kv_stale(w8 - 5, t16 & 0x1F0, 1) && --budget > 0) refetch_kv(c, 0, w8 - 5, t16 & 0x1F0);
    if (!on) goto START;
    asm volatile("fence.proxy.async.shared::cta;" ::: "memory");
    TS(16); TLX(7);
    __syncwarp();
    const Ctx cx = {u_rs, u_rl, u_bs, u_bl, (uint32_t)(uintptr_t)prm.rb, rbhi, w8, c};
    if (wg) steps<1>(W, T, t16, pa, pb, cx, &tmX, prm); else steps<0>(W, T, t16, pa, pb, cx, &tmX, prm);
    TLX(3);
}

namespace ok {
constexpr int STAGES = 4;
constexpr uint32_t STG = 49152, TOTAL = STAGES * STG + 32768 + 768, NOG = 0xBF800000u;
}
#define R8(o) F4(d, o), F4(d, o + 4)
__device__ __forceinline__ void wgmma_n256_ss_tt(float* d, uint64_t da, uint64_t db, int accum) {
    asm volatile("{.reg .pred p; setp.ne.b32 p, %130, 0;\n"
        "wgmma.mma_async.sync.aligned.m64n256k16.f32.bf16.bf16 {%0,%1,%2,%3,%4,%5,%6,%7,%8,%9,%10,%11,%12,%13,%14,%15,"
        "%16,%17,%18,%19,%20,%21,%22,%23,%24,%25,%26,%27,%28,%29,%30,%31,%32,%33,%34,%35,%36,%37,%38,%39,%40,%41,%42,%43,%44,%45,%46,%47,"
        "%48,%49,%50,%51,%52,%53,%54,%55,%56,%57,%58,%59,%60,%61,%62,%63,%64,%65,%66,%67,%68,%69,%70,%71,%72,%73,%74,%75,%76,%77,%78,%79,"
        "%80,%81,%82,%83,%84,%85,%86,%87,%88,%89,%90,%91,%92,%93,%94,%95,%96,%97,%98,%99,%100,%101,%102,%103,%104,%105,%106,%107,%108,%109,%110,%111,"
        "%112,%113,%114,%115,%116,%117,%118,%119,%120,%121,%122,%123,%124,%125,%126,%127}, %128, %129, p, 1, 1, 1, 1;}"
        : R8(0), R8(8), R8(16), R8(24), R8(32), R8(40), R8(48), R8(56), R8(64), R8(72), R8(80), R8(88), R8(96), R8(104), R8(112), R8(120)
        : "l"(da), "l"(db), "r"(accum));
}
#undef R8
__global__ void __cluster_dims__(2, 1, 1) __launch_bounds__(320, 1)
out_kernel(const __grid_constant__ CUtensorMap tmO, const __grid_constant__ CUtensorMap tmWo, const __grid_constant__ CUtensorMap tmA,
           const __grid_constant__ CUtensorMap tmOut, const __grid_constant__ CUtensorMap tmQ, const bf16* __restrict__ q, const bf16* __restrict__ gate_w) {
    using namespace ok;
    extern __shared__ __align__(1024) uint8_t smem_raw[];
    const uint32_t SB = smem_u32(smem_raw), AT = SB + STAGES * STG, BAR = AT + 32768;
    if (SB & 1023) __trap();
    const int tid = threadIdx.x, w = tid >> 5, lane = tid & 31;
    const int rank = blockIdx.x & 1, mt = blockIdx.x >> 3, nt = (blockIdx.x >> 1) & 3;
    const uint32_t full = BAR, empty = BAR + 64, afull = BAR + 128;
    if (tid == 0) {
        for (int i = 0; i < STAGES; i++) { mbar_init(full + i * 8, 1); mbar_init(empty + i * 8, 8); }
        mbar_init(afull, 2);
        asm volatile("fence.mbarrier_init.release.cluster;" ::: "memory");
    }
    __syncthreads();
    asm volatile("griddepcontrol.wait;" ::: "memory");
    if (blockIdx.x == 0 && tid < 160) g_cls[tid] = 0;
    TL(4);
    if (w >= 8) {
        if (w == 9) {
            uint4 gw[4];
            #pragma unroll
            for (int i = 0; i < 4; i++) gw[i] = __ldg((const uint4*)gate_w + lane + 32 * i);
            #pragma unroll 2
            for (int row = blockIdx.x * 16; row < blockIdx.x * 16 + 16; row++) {
                float a = 0.f;
                #pragma unroll
                for (int i = 0; i < 4; i++) {
                    const uint4 x = __ldg((const uint4*)(q + (size_t)row * DM) + lane + 32 * i);
                    #pragma unroll
                    for (int j = 0; j < 4; j++) { const uint32_t gg = ((const uint32_t*)&gw[i])[j], u = ((const uint32_t*)&x)[j]; a = fmaf(bflo(u), bflo(gg), fmaf(bfhi(u), bfhi(gg), a)); }
                }
                #pragma unroll
                for (int o = 16; o; o >>= 1) a += __shfl_xor_sync(~0u, a, o);
                if (lane == 0) st_g32(g_gate + row, __float_as_uint(1.f / (1.f + __expf(-a))));
            }
            uint32_t x[4];
            int n = 0;
            do ld_g128(x, g_gate + mt * 128 + lane * 4); while ((x[0] == NOG || x[1] == NOG || x[2] == NOG || x[3] == NOG) && ++n < SPIN_LIMIT);
            sts128(BAR + 256 + lane * 16, make_uint4(x[0], x[1], x[2], x[3]));
        } else if (lane == 0) {
            int st = 0, ph = 1;
            for (int kb = 0; kb < 32; kb++) {
                if (kb >= STAGES) mbar_wait(empty + st * 8, ph);
                mbar_expect(full + st * 8, STG);
                tma3d(SB + st * STG, &tmO, 0, (rank * 32 + kb) * 2, mt * 16, full + st * 8);
                tma3d(SB + st * STG + 16384, &tmWo, 0, (rank * 32 + kb) * 64, nt * 4, full + st * 8);
                if (kb == STAGES - 1) { mbar_expect(afull, 32768); tma3d(AT, &tmA, 0, (nt * 2 + rank) * 128, mt * 2, afull); }
                if (kb >> 1 == 4) asm volatile("cp.async.bulk.prefetch.tensor.5d.L2.global [%0, {%1, %2, %2, %2, %3}];" :: "l"(&tmQ), "r"(nt * 256 + rank * 128 + (kb & 1) * 64), "r"(0), "r"(mt * 4) : "memory");
                if (++st == STAGES) { st = 0; ph ^= 1; }
            }
            mbar_wait(empty, ph);
            mbar_expect(afull, 32768);
            for (int hf = 0; hf < 2; hf++)
                asm volatile("cp.async.bulk.tensor.5d.shared::cluster.global.mbarrier::complete_tx::bytes [%0], [%1, {%3, %4, %4, %4, %5}], [%2];"
                    :: "r"(SB + hf * 16384), "l"(&tmQ), "r"(afull), "r"(nt * 256 + rank * 128 + hf * 64), "r"(0), "r"(mt * 4) : "memory");
        }
        __syncwarp();
        asm volatile("barrier.cluster.arrive.aligned; barrier.cluster.wait.aligned;" ::: "memory");
        asm volatile("barrier.cluster.arrive.aligned; barrier.cluster.wait.aligned;" ::: "memory");
    } else {
        const int wg = w >> 2, g = lane >> 2;
        float acc[128];
        int st = 0, ph = 0, pst = 0;
        #pragma unroll 1
        for (int kb = 0; kb < 32; kb++) {
            mbar_wait(full + st * 8, ph);
            const uint64_t da = mkdesc(SB + st * STG + wg * 8192, 128, 1024, 0), db = mkdesc(SB + st * STG + 16384, 8192, 1024, 1);
            wg_fence();
            #pragma unroll
            for (int ks = 0; ks < 4; ks++) wgmma_n256_ss_tt(acc, da + ks * 16, db + ks * 128, (kb | ks) != 0);
            wg_commit();
            wg_wait<1>();
            if (kb > 0 && lane == 0) mbar_arrive(empty + pst * 8);
            pst = st;
            if (++st == STAGES) { st = 0; ph ^= 1; }
        }
        wg_wait<0>();
        TLX(12);
        asm volatile("barrier.cluster.arrive.aligned; barrier.cluster.wait.aligned;" ::: "memory");
        uint32_t peer;
        asm volatile("mapa.shared::cluster.u32 %0, %1, %2;" : "=r"(peer) : "r"(SB + 65536 + tid * 16), "r"(rank ^ 1));
        #define SND(e) pack2(rank ? acc[8 * i + (e)] : acc[64 + 8 * i + (e)], rank ? acc[8 * i + (e) + 1] : acc[65 + 8 * i + (e)])
        #pragma unroll
        for (int i = 0; i < 8; i++)
            asm volatile("st.shared::cluster.v4.b32 [%0], {%1,%2,%3,%4};" :: "r"(peer + i * 4096), "r"(SND(0)), "r"(SND(2)), "r"(SND(4)), "r"(SND(6)) : "memory");
        #undef SND
        asm volatile("barrier.cluster.arrive.aligned; barrier.cluster.wait.aligned;" ::: "memory");
        mbar_wait(afull, 0);
        const uint32_t ga = BAR + 256 + (32 * (w >> 1) + 8 * (g >> 1) + 4 * (w & 1) + (g & 1)) * 4;
        const float g0 = __uint_as_float(lds32(ga)), g1 = __uint_as_float(lds32(ga + 8)), h0 = 1.f - g0, h1 = 1.f - g1;
        const uint32_t la = AT + wg * 16384 + ((lane >> 4) * 8 + (lane & 7)) * 128 + ((((w & 3) * 2 + ((lane >> 3) & 1)) ^ (lane & 7)) << 4);
        const uint32_t ra = SB + (w * 16 + (lane & 15)) * 128;
        #pragma unroll
        for (int i = 0; i < 8; i++) {
            const uint32_t a = ra + (i >> 2) * 16384 + ((((i & 3) * 2 + (lane >> 4)) ^ (lane & 7)) << 4);
            uint32_t r0, r1, r2, r3, x0, x1, x2, x3;
            ldsm4t(r0, r1, r2, r3, la + i * 2048);
            ldsm4(x0, x1, x2, x3, a);
            const uint4 u = lds128(SB + 65536 + tid * 16 + i * 4096);
            float p[8];
            #pragma unroll
            for (int e = 0; e < 8; e++) { const uint32_t x = ((const uint32_t*)&u)[e >> 1]; p[e] = (rank ? acc[64 + 8 * i + e] : acc[8 * i + e]) + ((e & 1) ? bfhi(x) : bflo(x)); }
            #define MIX(g, h, r, x, e) pack2(fmaf(g * bflo(x), bflo(r), h * p[e]), fmaf(g * bfhi(x), bfhi(r), h * p[e + 1]))
            stsm4(a, MIX(g0, h0, r0, x0, 0), MIX(g1, h1, r1, x1, 2), MIX(g0, h0, r2, x2, 4), MIX(g1, h1, r3, x3, 6));
        }
        asm volatile("fence.proxy.async.shared::cta;" ::: "memory");
        bsync<1, 256>();
        if (tid == 0) {
            for (int hf = 0; hf < 2; hf++)
                asm volatile("cp.async.bulk.tensor.5d.global.shared::cta.bulk_group [%0, {%2, %3, %3, %3, %4}], [%1];"
                    :: "l"(&tmOut), "r"(SB + hf * 16384), "r"(nt * 256 + rank * 128 + hf * 64), "r"(0), "r"(mt * 4) : "memory");
            asm volatile("cp.async.bulk.commit_group;" ::: "memory");
            asm volatile("cp.async.bulk.wait_group 0;" ::: "memory");
        }
        TL(5);
    }
}

typedef CUresult (*EncodeFn)(CUtensorMap*, CUtensorMapDataType, cuuint32_t, void*, const cuuint64_t*, const cuuint64_t*, const cuuint32_t*,
                             const cuuint32_t*, CUtensorMapInterleave, CUtensorMapSwizzle, CUtensorMapL2promotion, CUtensorMapFloatOOBfill);
static void enc(EncodeFn fn, CUtensorMap* m, void* base, int rank, const cuuint64_t* dims, const cuuint64_t* strides, const cuuint32_t* box, CUtensorMapSwizzle sw) {
    cuuint32_t es[5] = {1, 1, 1, 1, 1};
    fn(m, CU_TENSOR_MAP_DATA_TYPE_BFLOAT16, rank, base, dims, strides, box, es, CU_TENSOR_MAP_INTERLEAVE_NONE, sw,
       CU_TENSOR_MAP_L2_PROMOTION_L2_128B, CU_TENSOR_MAP_FLOAT_OOB_FILL_NONE);
}
static MainParams h_prm = {{768, 576, 512, 0, 0, 0, 0, 0, 0, 0, 0, 0}, 0, 1, nullptr, nullptr};

extern "C" void kernel_launch(void* const* d_in, const int* in_sizes, int n_in, void* d_out, int out_size) {
    const bf16* q = (const bf16*)d_in[0];
    const bf16* shift_k = (const bf16*)d_in[3];
    const bf16* ssm_k = (const bf16*)d_in[4];
    const bf16* ssm_D = (const bf16*)d_in[5];
    const bf16* mem0 = (const bf16*)d_in[7];
    const bf16* gate_w = (const bf16*)d_in[13];

    static EncodeFn fn = nullptr;
    static void* pO = nullptr;
    static void* pA = nullptr;
    if (!fn) {
        cudaDriverEntryPointQueryResult qr;
        cudaGetDriverEntryPoint("cuTensorMapEncodeTiled", (void**)&fn, cudaEnableDefault, &qr);
        cudaGetSymbolAddress(&pO, g_O);
        cudaGetSymbolAddress(&pA, g_Y);
        void* pRB; cudaGetSymbolAddress(&pRB, g_RB);
        h_prm.rb = (char*)(((uintptr_t)pRB + (4u << 20) - 1) & ~(uintptr_t)((4u << 20) - 1));
        int dev, sms; cudaGetDevice(&dev); cudaDeviceGetAttribute(&sms, cudaDevAttrMultiProcessorCount, dev);
        h_prm.by_sm = sms == NCTA;
        cudaFuncSetAttribute(main_kernel, cudaFuncAttributeMaxDynamicSharedMemorySize, mk::TOTAL);
        cudaFuncSetAttribute(out_kernel, cudaFuncAttributeMaxDynamicSharedMemorySize, ok::TOTAL);
    }
    CUtensorMap mWq, mWk, mWv, mWo, mX, mO, mWo2, mA, mOut, mQ;
    {
        cuuint64_t d[2] = {4096, 1024}, s[1] = {8192}; cuuint32_t b[2] = {64, 256};
        enc(fn, &mWq, d_in[8], 2, d, s, b, CU_TENSOR_MAP_SWIZZLE_128B);
        enc(fn, &mWk, d_in[9], 2, d, s, b, CU_TENSOR_MAP_SWIZZLE_128B);
        enc(fn, &mWv, d_in[10], 2, d, s, b, CU_TENSOR_MAP_SWIZZLE_128B);
    }
    {
        cuuint64_t d[2] = {1024, 4096}, s[1] = {2048}; cuuint32_t b[2] = {64, 128};
        enc(fn, &mWo, d_in[11], 2, d, s, b, CU_TENSOR_MAP_SWIZZLE_128B);
        cuuint64_t d2[3] = {64, 4096, 16}, s2[2] = {2048, 128}; cuuint32_t b2[3] = {64, 64, 4};
        enc(fn, &mWo2, d_in[11], 3, d2, s2, b2, CU_TENSOR_MAP_SWIZZLE_128B);
    }
    {
        cuuint64_t d[3] = {64, 2048, 16}, s[2] = {2048, 128}; cuuint32_t b[3] = {64, 32, 8};
        enc(fn, &mX, d_in[0], 3, d, s, b, CU_TENSOR_MAP_SWIZZLE_128B);
    }
    {
        cuuint64_t d[3] = {256, 128, 256}, s[2] = {512, 65536}; cuuint32_t b[3] = {256, 2, 16};
        enc(fn, &mO, pO, 3, d, s, b, CU_TENSOR_MAP_SWIZZLE_NONE);
    }
    {
        cuuint64_t d[5] = {1024, 2, 4, 4, 64}, s[4] = {2048, 16384, 4096, 65536}; cuuint32_t b[5] = {64, 2, 4, 4, 4};
        cuuint64_t da[3] = {64, 1024, 32}, sa[2] = {4096, 128}; cuuint32_t ba[3] = {64, 128, 2};
        enc(fn, &mA, pA, 3, da, sa, ba, CU_TENSOR_MAP_SWIZZLE_128B);
        enc(fn, &mQ, d_in[0], 5, d, s, b, CU_TENSOR_MAP_SWIZZLE_128B);
        enc(fn, &mOut, d_out, 5, d, s, b, CU_TENSOR_MAP_SWIZZLE_128B);
    }
    KVMaps mK;
    {
        cuuint64_t d[3] = {1024, 256, 8}, s[2] = {16384, 2048}; cuuint32_t b[3] = {8, 256, 1};
        for (int i = 0; i < 4; i++) { b[2] = i < 2 ? 1 : 8; enc(fn, &mK.m[i], d_in[1 + (i & 1)], 3, d, s, b, CU_TENSOR_MAP_SWIZZLE_NONE); }
    }
    cudaStream_t st = cudaStreamPerThread;
    cudaLaunchAttribute at[1];
    at[0].id = cudaLaunchAttributeProgrammaticStreamSerialization;
    at[0].val.programmaticStreamSerializationAllowed = 1;
    cudaLaunchConfig_t cfg = {};
    cfg.stream = st; cfg.attrs = at;
    cfg.gridDim = dim3(NCTA); cfg.blockDim = dim3(256); cfg.dynamicSmemBytes = mk::TOTAL;
    h_prm.x = (const char*)q;
    const ConvIn cin = {shift_k, ssm_k, ssm_D};
    cudaLaunchKernelEx(&cfg, main_kernel, mWq, mWk, mWv, mWo, mX, mK, mem0, cin, h_prm);
    cfg.numAttrs = PDL;
    cfg.gridDim = dim3(128); cfg.blockDim = dim3(320); cfg.dynamicSmemBytes = ok::TOTAL;
    cudaLaunchKernelEx(&cfg, out_kernel, mO, mWo2, mA, mOut, mQ, q, gate_w);
}
```

```cpp
#include <cuda_runtime.h>
#include <cuda_bf16.h>
#include <cuda.h>
#include <stdint.h>

typedef __nv_bfloat16 bf16;

constexpr int SEQ = 2048, DM = 1024, NH = 32, DH = 128, NSEG = 64;
constexpr int SPIN_LIMIT = 1 << 13, NCTA = 132;
#define NPR 2
#define RF 0
#define CC 0
#define DRY 1
#define XDL 10
#define NSP 128
#define XPF 2
#define FRONT __forceinline__
#define PDL 1
#define TPF 1

constexpr uint32_t HOME_BITS = 0xB3000;
constexpr uint32_t RB_R = 0;
constexpr uint32_t RB_B = 0x80000;
constexpr uint32_t RB_T = RB_B + 0x4000;
constexpr uint32_t RB_P = RB_B + 0x20000;
constexpr uint32_t RB_X = 2u << 20;
__device__ uint4 g_RB[(8 << 20) / 16];
__device__ uint32_t g_cls[160];
__device__ uint4 g_T[2 * NH * 3072];
__device__ uint4 g_O[NSEG * 4 * 4096];
__device__ uint4 g_Y[SEQ * DM / 8];
__device__ float g_gate[SEQ];
__device__ uint32_t g_err;
#define TL(i) do {} while (0)
#define TLX(i)
#define TS(i)

__device__ __forceinline__ uint32_t smem_u32(const void* p) { return (uint32_t)__cvta_generic_to_shared(p); }
__device__ __forceinline__ uint32_t clk() { uint32_t c; asm volatile("mov.u32 %0, %%clock;" : "=r"(c) :: "memory"); return c; }
__device__ __forceinline__ void ldsm4(uint32_t& r0, uint32_t& r1, uint32_t& r2, uint32_t& r3, uint32_t a) {
    asm volatile("ldmatrix.sync.aligned.m8n8.x4.shared.b16 {%0,%1,%2,%3}, [%4];" : "=r"(r0), "=r"(r1), "=r"(r2), "=r"(r3) : "r"(a) : "memory");
}
__device__ __forceinline__ void ldsm4t(uint32_t& r0, uint32_t& r1, uint32_t& r2, uint32_t& r3, uint32_t a) {
    asm volatile("ldmatrix.sync.aligned.m8n8.x4.trans.shared.b16 {%0,%1,%2,%3}, [%4];" : "=r"(r0), "=r"(r1), "=r"(r2), "=r"(r3) : "r"(a) : "memory");
}
__device__ __forceinline__ void ldsm2(uint32_t& r0, uint32_t& r1, uint32_t a) {
    asm volatile("ldmatrix.sync.aligned.m8n8.x2.shared.b16 {%0,%1}, [%2];" : "=r"(r0), "=r"(r1) : "r"(a) : "memory");
}
__device__ __forceinline__ void stsm4t(uint32_t a, uint32_t r0, uint32_t r1, uint32_t r2, uint32_t r3) {
    asm volatile("stmatrix.sync.aligned.m8n8.x4.trans.shared.b16 [%0], {%1,%2,%3,%4};" :: "r"(a), "r"(r0), "r"(r1), "r"(r2), "r"(r3) : "memory");
}
__device__ __forceinline__ void mma16(float* c, uint32_t a0, uint32_t a1, uint32_t a2, uint32_t a3, uint32_t b0, uint32_t b1) {
    asm volatile("mma.sync.aligned.m16n8k16.row.col.f32.bf16.bf16.f32 {%0,%1,%2,%3}, {%4,%5,%6,%7}, {%8,%9}, {%0,%1,%2,%3};"
        : "+f"(c[0]), "+f"(c[1]), "+f"(c[2]), "+f"(c[3]) : "r"(a0), "r"(a1), "r"(a2), "r"(a3), "r"(b0), "r"(b1));
}
__device__ __forceinline__ void mma8(float* c, uint32_t a0, uint32_t a1, uint32_t b0) {
    asm volatile("mma.sync.aligned.m16n8k8.row.col.f32.bf16.bf16.f32 {%0,%1,%2,%3}, {%4,%5}, {%6}, {%0,%1,%2,%3};"
        : "+f"(c[0]), "+f"(c[1]), "+f"(c[2]), "+f"(c[3]) : "r"(a0), "r"(a1), "r"(b0));
}
__device__ __forceinline__ uint32_t pack2(float lo, float hi) {
    uint32_t r; asm("cvt.rn.bf16x2.f32 %0, %1, %2;" : "=r"(r) : "f"(hi), "f"(lo)); return r;
}
__device__ __forceinline__ uint32_t hadd2(uint32_t a, uint32_t b) {
    uint32_t r; asm("add.rn.bf16x2 %0, %1, %2;" : "=r"(r) : "r"(a), "r"(b)); return r;
}
__device__ __forceinline__ float bflo(uint32_t w) { return __uint_as_float(w << 16); }
__device__ __forceinline__ float bfhi(uint32_t w) { return __uint_as_float(w & 0xFFFF0000u); }
__device__ __forceinline__ void st_g32(void* p, uint32_t v) { asm volatile("st.relaxed.gpu.global.u32 [%0], %1;" :: "l"(p), "r"(v) : "memory"); }
__device__ __forceinline__ void st_g128(void* p, uint32_t a, uint32_t b, uint32_t c, uint32_t d) {
    asm volatile("st.relaxed.gpu.global.v4.u32 [%0], {%1,%2,%3,%4};" :: "l"(p), "r"(a), "r"(b), "r"(c), "r"(d) : "memory");
}
__device__ __forceinline__ uint4 lds128(uint32_t a) { uint4 v; asm volatile("ld.shared.v4.u32 {%0,%1,%2,%3}, [%4];" : "=r"(v.x), "=r"(v.y), "=r"(v.z), "=r"(v.w) : "r"(a) : "memory"); return v; }
__device__ __forceinline__ void sts128(uint32_t a, uint4 v) { asm volatile("st.shared.v4.u32 [%0], {%1,%2,%3,%4};" :: "r"(a), "r"(v.x), "r"(v.y), "r"(v.z), "r"(v.w) : "memory"); }
__device__ __forceinline__ float2 lds64f(uint32_t a) { float2 v; asm volatile("ld.shared.v2.f32 {%0,%1}, [%2];" : "=f"(v.x), "=f"(v.y) : "r"(a) : "memory"); return v; }
__device__ __forceinline__ void sts64f(uint32_t a, float x, float y) { asm volatile("st.shared.v2.f32 [%0], {%1,%2};" :: "r"(a), "f"(x), "f"(y) : "memory"); }
__device__ __forceinline__ void sts32f(uint32_t a, float x) { asm volatile("st.shared.f32 [%0], %1;" :: "r"(a), "f"(x) : "memory"); }
__device__ __forceinline__ void sts32(uint32_t a, uint32_t x) { asm volatile("st.shared.u32 [%0], %1;" :: "r"(a), "r"(x) : "memory"); }
__device__ __forceinline__ uint32_t lds32(uint32_t a) { uint32_t v; asm volatile("ld.shared.u32 %0, [%1];" : "=r"(v) : "r"(a) : "memory"); return v; }
__device__ __forceinline__ void cpa16(uint32_t dst, const void* src) { asm volatile("cp.async.cg.shared.global [%0], [%1], 16;" :: "r"(dst), "l"(src) : "memory"); }
__device__ __forceinline__ void cpa_commit() { asm volatile("cp.async.commit_group;" ::: "memory"); }
__device__ __forceinline__ void cpa_wait() { asm volatile("cp.async.wait_all;" ::: "memory"); }
template <int ID, int N> __device__ __forceinline__ void bsync() { asm volatile("bar.sync %0, %1;" :: "n"(ID), "n"(N) : "memory"); }
template <int ID, int N> __device__ __forceinline__ void barrive() { asm volatile("bar.arrive %0, %1;" :: "n"(ID), "n"(N) : "memory"); }
template <int ID, int N> __device__ __forceinline__ void bsync_if(bool on) { asm volatile("{ .reg .pred p; setp.ne.b32 p, %2, 0; @p bar.sync %0, %1; }" :: "n"(ID), "n"(N), "r"((int)on) : "memory"); }
template <int ID, int N> __device__ __forceinline__ void barrive_if(bool on) { asm volatile("{ .reg .pred p; setp.ne.b32 p, %2, 0; @p bar.arrive %0, %1; }" :: "n"(ID), "n"(N), "r"((int)on) : "memory"); }
template <int ID> __device__ __forceinline__ uint32_t any128(uint32_t x) {
    uint32_t r; asm volatile("{ .reg .pred p; setp.ne.b32 p, %1, 0; bar.red.or.pred p, %2, 128, p; selp.u32 %0, 1, 0, p; }" : "=r"(r) : "r"(x), "n"(ID) : "memory"); return r;
}
__device__ __forceinline__ bool elect() {
    uint32_t p; asm volatile("{ .reg .pred p; elect.sync _|p, 0xFFFFFFFF; selp.u32 %0, 1, 0, p; }" : "=r"(p)); return p;
}
__device__ __forceinline__ void mbar_init(uint32_t mb, uint32_t n) { asm volatile("mbarrier.init.shared::cta.b64 [%0], %1;" :: "r"(mb), "r"(n) : "memory"); }
__device__ __forceinline__ void mbar_expect(uint32_t mb, uint32_t bytes) { asm volatile("mbarrier.arrive.expect_tx.shared::cta.b64 _, [%0], %1;" :: "r"(mb), "r"(bytes) : "memory"); }
__device__ __forceinline__ void mbar_arrive(uint32_t mb) { asm volatile("mbarrier.arrive.shared::cta.b64 _, [%0];" :: "r"(mb) : "memory"); }
__device__ __forceinline__ void mbar_wait(uint32_t mb, uint32_t ph) {
    asm volatile("{ .reg .pred p; .reg .u32 n; mov.u32 n, 0;\n"
                 "MW_%=: mbarrier.try_wait.parity.shared::cta.b64 p, [%0], %1; add.u32 n, n, 1; setp.lt.and.u32 p, n, %2, !p; @p bra.uni MW_%=; }"
                 :: "r"(mb), "r"(ph), "n"(SPIN_LIMIT) : "memory");
}
__device__ __forceinline__ void tma2d(uint32_t dst, const CUtensorMap* m, int c0, int c1, uint32_t mb) {
    asm volatile("cp.async.bulk.tensor.2d.shared::cluster.global.mbarrier::complete_tx::bytes [%0], [%1, {%3, %4}], [%2];"
        :: "r"(dst), "l"(m), "r"(mb), "r"(c0), "r"(c1) : "memory");
}
__device__ __forceinline__ void tma3d(uint32_t dst, const CUtensorMap* m, int c0, int c1, int c2, uint32_t mb) {
    asm volatile("cp.async.bulk.tensor.3d.shared::cluster.global.mbarrier::complete_tx::bytes [%0], [%1, {%3, %4, %5}], [%2];"
        :: "r"(dst), "l"(m), "r"(mb), "r"(c0), "r"(c1), "r"(c2) : "memory");
}
__device__ __forceinline__ void bulk_ld(uint32_t dst, const void* src, uint32_t bytes, uint32_t mb) {
    asm volatile("cp.async.bulk.shared::cluster.global.mbarrier::complete_tx::bytes [%0], [%1], %2, [%3];" :: "r"(dst), "l"(src), "r"(bytes), "r"(mb) : "memory");
}
__device__ __forceinline__ uint64_t mkdesc(uint32_t addr, uint32_t lbo, uint32_t sbo, uint32_t swz) {
    return (uint64_t)((addr & 0x3FFFF) >> 4) | ((uint64_t)(lbo >> 4) << 16) | ((uint64_t)(sbo >> 4) << 32) | ((uint64_t)swz << 62);
}
__device__ __forceinline__ void wg_fence() { asm volatile("wgmma.fence.sync.aligned;" ::: "memory"); }
__device__ __forceinline__ void wg_commit() { asm volatile("wgmma.commit_group.sync.aligned;" ::: "memory"); }
template <int N> __device__ __forceinline__ void wg_wait() { asm volatile("wgmma.wait_group.sync.aligned %0;" :: "n"(N) : "memory"); }
#define F4(d, o) "+f"(d[o]), "+f"(d[o + 1]), "+f"(d[o + 2]), "+f"(d[o + 3])
__device__ __forceinline__ void wgmma_n32_rs(float* d, const uint32_t* a, uint64_t db, int accum) {
    asm volatile("{.reg .pred p; setp.ne.b32 p, %21, 0;\n"
        "wgmma.mma_async.sync.aligned.m64n32k16.f32.bf16.bf16 {%0,%1,%2,%3,%4,%5,%6,%7,%8,%9,%10,%11,%12,%13,%14,%15}, {%16,%17,%18,%19}, %20, p, 1, 1, 0;}"
        : F4(d, 0), F4(d, 4), F4(d, 8), F4(d, 12) : "r"(a[0]), "r"(a[1]), "r"(a[2]), "r"(a[3]), "l"(db), "r"(accum));
}
__device__ __forceinline__ void wait_until(uint32_t tgt, uint32_t any) {
    asm volatile("{ .reg .pred p, q; .reg .u32 t; .reg .s32 d; mov.u32 t, %0; setp.ne.u32 q, %1, 0xFFFFFFFF;\n"
                 "WU_%=: @q mov.u32 t, %%clock; sub.s32 d, t, %0; setp.lt.s32 p, d, 0; @p bra.uni WU_%=; }" :: "r"(tgt), "r"(any) : "memory");
}

namespace mk {
constexpr uint32_t SB = 1024;
constexpr uint32_t WV = SB, WO = SB + 65536, XT = SB + 131072, TK = SB + 163840  , TQ = TK + 32768, MEM = TQ + 4096,
                   SC = MEM + 8192  , PT = SC + 6144,
                   OB = SC + 8192, SUM = OB + 2048, BAR = SUM + 512, GRP = BAR + 128, PROFB = BAR + 192,
                   TOTAL = PROFB - SB;
static_assert(TOTAL <= 232448, "shared memory");
constexpr uint32_t MB_WQ = BAR, MB_WK = BAR + 8, MB_WV = BAR + 16, MB_WO = BAR + 24, MB_X = BAR + 32, MB_KV = BAR + 40, MB_R = BAR + 48, MB_B = BAR + 56, MB_C = BAR + 64;
constexpr uint32_t XT2 = WV, RS = WV + 32768, VE = RS + 4096;
enum { B_START = 1, B_H0, B_H2, B_H3, B_S1, B_SC, B_SC2, B_S0, B_O, B_O2, B_PT, B_GO, B_VX, B_RD, B_BT };
constexpr uint64_t XD0 = (uint64_t)(XT >> 4) | ((uint64_t)1 << 16) | ((uint64_t)64 << 32) | ((uint64_t)1 << 62);
constexpr uint32_t TSLOT = NH * 49152;
}
struct MainParams { int d[12]; uint32_t zero; int by_sm; char* rb; const char* x; };
#define XD(i) (mk::XD0 - (((i) >> 5) & 1) * ((mk::XT - mk::XT2) >> 4) + ((i) >> 6) * ((mk::TK - mk::XT) >> 4) + (((i) & 31) >> 2) * 256 + ((i) & 3) * 2)
#define XD4(i) XD(i), XD(i + 1), XD(i + 2), XD(i + 3)
#define XD16(i) XD4(i), XD4(i + 4), XD4(i + 8), XD4(i + 12)
__constant__ __align__(256) uint64_t c_xd[96] = {XD16(0), XD16(16), XD16(32), XD16(48), XD16(64), XD16(80)};
#define CUT(r) asm volatile("{ .reg .pred q; setp.eq.u32 q, %1, 0xFFFFFFFF; @q mov.u32 %0, %%clock; }" : "+r"(r) : "r"(t16) : "memory")
__device__ __forceinline__ uint32_t opq(uint32_t x) { asm volatile("" : "+r"(x)); return x; }
__device__ __forceinline__ float opqf(float x) { asm volatile("" : "+f"(x)); return x; }
#define PROF(i)
#define PROFW(i, w)
#define TRC(i, v)
#define RETRY(i, on)
#define P(i) prm.d[i]
#define DELAY(n) do { if (n) { _Pragma("unroll") for (int i_ = 0; i_ < n; i_++) asm volatile("mad.lo.u32 %0, %0, %1, %0;" : "+r"(pb) : "r"(prm.zero)); CUT(pa); } } while (0)

__device__ __forceinline__ uint32_t tagw(uint32_t w, uint32_t tau) { return (w & ~1u) | tau; }
__device__ __forceinline__ uint32_t ld_g32(const void* p) { uint32_t v; asm volatile("ld.relaxed.gpu.global.u32 %0, [%1];" : "=r"(v) : "l"(p) : "memory"); return v; }
__device__ __forceinline__ void ld_g64(uint32_t* v, const void* p) { asm volatile("ld.relaxed.gpu.global.v2.u32 {%0,%1}, [%2];" : "=r"(v[0]), "=r"(v[1]) : "l"(p) : "memory"); }
__device__ __forceinline__ void ld_g128(uint32_t* v, const void* p) {
    asm volatile("ld.relaxed.gpu.global.v4.u32 {%0,%1,%2,%3}, [%4];" : "=r"(v[0]), "=r"(v[1]), "=r"(v[2]), "=r"(v[3]) : "l"(p) : "memory");
}
__device__ __forceinline__ void st_g64(void* p, uint32_t a, uint32_t b) { asm volatile("st.relaxed.gpu.global.v2.u32 [%0], {%1,%2};" :: "l"(p), "r"(a), "r"(b) : "memory"); }
__device__ __forceinline__ void lds128f(float* v, uint32_t a) { asm volatile("ld.shared.v4.f32 {%0,%1,%2,%3}, [%4];" : "=f"(v[0]), "=f"(v[1]), "=f"(v[2]), "=f"(v[3]) : "r"(a) : "memory"); }
__device__ __forceinline__ void sts128f(uint32_t a, float x, float y, float z, float w) { asm volatile("st.shared.v4.f32 [%0], {%1,%2,%3,%4};" :: "r"(a), "f"(x), "f"(y), "f"(z), "f"(w) : "memory"); }
__device__ __forceinline__ void stsm4(uint32_t a, uint32_t r0, uint32_t r1, uint32_t r2, uint32_t r3) {
    asm volatile("stmatrix.sync.aligned.m8n8.x4.shared.b16 [%0], {%1,%2,%3,%4};" :: "r"(a), "r"(r0), "r"(r1), "r"(r2), "r"(r3) : "memory");
}
__device__ __forceinline__ void mmaq(float* c, const uint32_t* a, uint32_t b0, uint32_t b1) { mma16(c, a[0], a[1], a[2], a[3], b0, b1); }
template <int LUT> __device__ __forceinline__ uint32_t lop3(uint32_t a, uint32_t b, uint32_t c) { uint32_t r; asm("lop3.b32 %0, %1, %2, %3, %4;" : "=r"(r) : "r"(a), "r"(b), "r"(c), "n"(LUT)); return r; }
template <int N, int S> __device__ __forceinline__ uint32_t stale(const uint32_t* x, uint32_t tau) {
    if constexpr (N == 2) return lop3<0x7E>(x[0], tau, x[S]);
    else if constexpr (N == 3) return lop3<0xF6>(stale<2, S>(x, tau), x[2 * S], tau);
    else if constexpr (N == 4 || N == 16) return lop3<0xFC>(stale<N / 2, S>(x, tau), stale<N / 2, S>(x + N / 2 * S, tau), 0);
    else return lop3<0xFE>(stale<3, S>(x, tau), stale<3, S>(x + 3 * S, tau), stale<2, S>(x + 6 * S, tau));
}
__device__ __forceinline__ uint32_t late(uint32_t a, uint32_t b, uint32_t mask) {
    uint32_t r;
    asm volatile("{ .reg .pred p; .reg .b32 t; lop3.b32 t, %1, %2, %3, 0xA8; setp.ne.b32 p, t, 0; vote.sync.any.pred p, p, 0xFFFFFFFF; selp.u32 %0, 1, 0, p; }" : "=r"(r) : "r"(a), "r"(b), "r"(mask));
    return r;
}
#define AGAIN(id, reload, ...) _Pragma("unroll 1") for (int n_ = 0; __builtin_expect(__VA_ARGS__, 0) && n_ < SPIN_LIMIT; n_++) { RETRY(id, 1); reload; }
__device__ __forceinline__ uint32_t tile_off(int lane, int chunk0) {
    return ((lane >> 4) * 8 + (lane & 7)) * 128 + (((chunk0 + ((lane >> 3) & 1)) ^ (lane & 7)) << 4);
}
template <int K0, int K1>
__device__ __forceinline__ void load_tile(uint32_t a, uint32_t* T) {
    #pragma unroll
    for (int ks = K0; ks < K1; ks++) ldsm4t(T[4 * ks], T[4 * ks + 1], T[4 * ks + 2], T[4 * ks + 3], a + ks * 2048);
}
__device__ __forceinline__ void lds128u(uint32_t* v, uint32_t a) { asm volatile("ld.shared.v4.u32 {%0,%1,%2,%3}, [%4];" : "=r"(v[0]), "=r"(v[1]), "=r"(v[2]), "=r"(v[3]) : "r"(a) : "memory"); }
template <int K0, int K1, int STRIDE = 4096>
__device__ __forceinline__ void load_frag(uint32_t a, uint32_t* T) {
    #pragma unroll
    for (int ks = K0; ks < K1; ks++) lds128u(&T[4 * ks], a + ks * STRIDE);
}
template <int L0, int L1, bool INIT = false>
__device__ __forceinline__ void wg_run(float* acc, const uint32_t* A, const uint64_t* d) {
    if (L1 > L0) {
        wg_fence();
        #pragma unroll
        for (int l = L0; l < L1; l++) wgmma_n32_rs(acc, &A[4 * l], d[l], INIT || l != 0);
        wg_commit();
    }
}
__device__ __forceinline__ void load_x(const CUtensorMap* tmX, int c, int seg, uint32_t dst) {
    asm volatile("{ .reg .pred p; elect.sync _|p, 0xFFFFFFFF;\n"
        "@p cp.async.bulk.tensor.3d.shared::cluster.global.mbarrier::complete_tx::bytes [%4], [%0, {%5, %1, %2}], [%3]; }"
        :: "l"(tmX), "r"(seg * 32), "r"((c & 1) * 8), "r"(mk::MB_X), "r"(dst), "r"(0) : "memory");
    __syncwarp();
}
__device__ __forceinline__ void bulk_expect(uint32_t mb, uint32_t bytes) {
    asm volatile("{ .reg .pred p; elect.sync _|p, 0xFFFFFFFF; @p mbarrier.arrive.expect_tx.shared::cta.b64 _, [%0], %1; }" :: "r"(mb), "r"(bytes) : "memory");
}
__device__ __forceinline__ void bulk_copy(uint32_t dst, const void* src, uint32_t bytes, uint32_t mb) {
    asm volatile("{ .reg .pred p; elect.sync _|p, 0xFFFFFFFF; @p cp.async.bulk.shared::cluster.global.mbarrier::complete_tx::bytes [%0], [%1], %2, [%3]; }"
        :: "r"(dst), "l"(src), "r"(bytes), "r"(mb) : "memory");
    __syncwarp();
}
__device__ __forceinline__ void bulk_copy_if(bool on, uint32_t dst, const void* src, uint32_t bytes, uint32_t mb) {
    asm volatile("{ .reg .pred p; elect.sync _|p, 0xFFFFFFFF; setp.ne.and.b32 p, %4, 0, p; @p cp.async.bulk.shared::cluster.global.mbarrier::complete_tx::bytes [%0], [%1], %2, [%3]; }"
        :: "r"(dst), "l"(src), "r"(bytes), "r"(mb), "r"((int)on) : "memory");
    __syncwarp();
}
__device__ __forceinline__ void kv_expect(uint32_t bytes) { bulk_expect(mk::MB_KV, bytes); }
__device__ __forceinline__ void kv_copy(uint32_t dst, const void* src, uint32_t bytes) { bulk_copy(dst, src, bytes, mk::MB_KV); }
__device__ __forceinline__ uint32_t gtime() { uint32_t c; asm volatile("mov.u32 %0, %%globaltimer_lo;" : "=r"(c) :: "memory"); return c; }
__device__ __forceinline__ void wait_g(uint32_t tgt, uint32_t any) {
    asm volatile("{ .reg .pred p, q; .reg .u32 t; mov.u32 t, %0; setp.ne.u32 q, %1, 0xFFFFFFFF;\n"
                 "WG_%=: @q mov.u32 t, %%globaltimer_lo; sub.u32 t, t, %0; setp.gt.u32 p, t, 0xFFFF0000; @p bra.uni WG_%=; }" :: "r"(tgt), "r"(any) : "memory");
    __syncwarp();
}
__device__ __forceinline__ uint32_t clkv(uint32_t any) {
    uint32_t c; asm volatile("{ .reg .pred q; setp.ne.u32 q, %1, 0xFFFFFFFF; mov.u32 %0, 0; @q mov.u32 %0, %%clock; }" : "=r"(c) : "r"(any) : "memory"); return c;
}
__device__ __forceinline__ char* kv_src(int c, int seg) { return (char*)g_T + ((seg & 1) * mk::TSLOT + (c >> 2) * 49152); }
__device__ __forceinline__ void prefetch_l2(const void* p, uint32_t bytes) {
    asm volatile("{ .reg .pred p; elect.sync _|p, 0xFFFFFFFF; @p cp.async.bulk.prefetch.L2.global [%0], %1; }" :: "l"(p), "r"(bytes) : "memory");
}
__device__ __forceinline__ uint32_t phase(int i) { return (~i >> 1) & 1; }
__device__ __forceinline__ void qk_pack(const float* acc, uint32_t* p) {
    #pragma unroll
    for (int i = 0; i < 4; i++) { p[i] = pack2(acc[4 * i], acc[4 * i + 1]); p[4 + i] = pack2(acc[4 * i + 2], acc[4 * i + 3]); }
}
__device__ __forceinline__ void sts32_if(bool on, uint32_t a, uint32_t x) {
    asm volatile("{ .reg .pred p; setp.ne.b32 p, %2, 0; @p st.shared.u32 [%0], %1; }" :: "r"(a), "r"(x), "r"((int)on) : "memory");
}
__device__ __forceinline__ void sts128_if(bool on, uint32_t a, const uint32_t* p) {
    asm volatile("{ .reg .pred p; setp.ne.b32 p, %5, 0; @p st.shared.v4.u32 [%0], {%1,%2,%3,%4}; }" :: "r"(a), "r"(p[0]), "r"(p[1]), "r"(p[2]), "r"(p[3]), "r"((int)on) : "memory");
}
__device__ __forceinline__ void st_if(bool on, char* a, const uint32_t* p) {
    asm volatile("{ .reg .pred p; setp.ne.b32 p, %5, 0; @p st.relaxed.gpu.global.v4.u32 [%0], {%1,%2,%3,%4}; }" :: "l"(a), "r"(p[0]), "r"(p[1]), "r"(p[2]), "r"(p[3]), "r"((int)on) : "memory");
}
__device__ __forceinline__ char* tok_dst(int c, int seg, int wg) { return kv_src(c, seg) + (wg ? (c & 1) * 8192 + (c & 2) * 2048 : 32768 + (c & 1) * 2048 + (c & 2) * 512); }
#define HI8 (wg ? 0x220 : 0xC0)
#define TAGM() uint32_t tm[4]; tag_masks(tm, (t16 >> (wg ? 4 : 6)) & 24)
__device__ __forceinline__ void acc_init(float* acc, const uint32_t* p) {
    #pragma unroll
    for (int i = 0; i < 4; i++) { acc[4 * i] = bflo(p[i]); acc[4 * i + 1] = bfhi(p[i]); acc[4 * i + 2] = bflo(p[4 + i]); acc[4 * i + 3] = bfhi(p[4 + i]); }
}
__device__ __forceinline__ void acc_add(float* acc, const uint32_t* p) {
    #pragma unroll
    for (int i = 0; i < 4; i++) { acc[4 * i] += bflo(p[i]); acc[4 * i + 1] += bfhi(p[i]); acc[4 * i + 2] += bflo(p[4 + i]); acc[4 * i + 3] += bfhi(p[4 + i]); }
}
__device__ __forceinline__ void tag_masks(uint32_t* m, uint32_t j8) {
    const uint32_t x = 1u << j8;
    #pragma unroll
    for (int i = 0; i < 4; i++) m[i] = opq(__byte_perm(x, 0, 0x4440 + i));
}
__device__ __forceinline__ void pack_tag(const float* acc, uint32_t* p, uint32_t tau, const uint32_t* m) {
    qk_pack(acc, p);
    #pragma unroll
    for (int i = 0; i < 8; i++) p[i] = lop3<0xB8>(p[i], m[i & 3], tau);
}
__device__ __forceinline__ uint32_t kv_stale(uint32_t w, uint32_t l16, uint32_t tau) {
    uint32_t x[12];
    const uint32_t a = opq(l16 * 2 + ((l16 >> 4) & 0x1C) + w * 12288), aq = w == 2 ? opq(l16 * 2 + ((l16 >> 2) & 0x10) + ((l16 >> 5) & 0xC) + 24576) : a;
    #pragma unroll
    for (int i = 0; i < 12; i++) x[i] = lds32(mk::TK + i * 1024 + (i < 8 ? a : aq));
    return late(stale<8, 1>(x, tau), stale<4, 1>(x + 8, tau), 1);
}
__device__ __forceinline__ void refetch_kv(int c, int seg, int w, uint32_t l16) {
    #pragma unroll 1
    for (int i = w * 24; i < w * 24 + 24; i++) {
        uint32_t v[4];
        ld_g128(v, kv_src(c, seg) + (i * 512 + (i >> 6) * (c & 3) * 4096) + l16);
        sts128(mk::TK + i * 512 + l16, make_uint4(v[0], v[1], v[2], v[3]));
    }
    __syncwarp();
}
__device__ __forceinline__ void get_kv(int c, int seg) {
    kv_expect(36864); kv_copy(mk::TK, kv_src(c, seg), 32768); kv_copy(mk::TQ, kv_src(c, seg) + (32768 + (c & 3) * 4096), 4096);
}
constexpr uint32_t ONES = 0x3F803F80u;
__device__ __forceinline__ float rcpf(float x) { float r; asm("rcp.approx.ftz.f32 %0, %1;" : "=f"(r) : "f"(x)); return r; }

#define ANN 2
#define POL 8
#define PRE0 4
#define PRE1 4
#define HC 2
#define HR 4
#define BL 1
#define NA 2
#define QF 0
#define DEEP 6
#define AHEAD(n) (PRE0 + 2 * (n) < (n) + DEEP ? PRE0 + 2 * (n) : (n) + DEEP < 16 ? (n) + DEEP : 16)
#define CO 1
#define HS 2
#define VP 0
#define KM 1
#define NLDS 2
#define AL 2
#define RP 26
#define RQ 2
#define RL 29
#define R4 1
#define KVP 12
#define LD7 8
#define XP 3
#define G2 0
#define NB 26
#define BD 8
#define NP 22
#define TA 4
#define TA0 2
#define NT 19
#define VH 1
#define TRIES 200
#define NPW 3
#define EV0 5
#define EV1 8
#define WA1 6
#define WA2 9
#define H2 10
#define QV 1
#define QD 0
#define KD 0
#define VD 0
#define WA0 4
#define ONE 0
#define PP 12
#define OBA 3
#define WA3 1
#define WB1 0
#define WB2 12
#define WB3 13
#define H0 6
#define H3 10
__device__ __forceinline__ uint32_t tagm(uint32_t w, uint32_t mask, uint32_t tau) { return lop3<0xB8>(w, mask, tau); }
__device__ __forceinline__ char* at(uint32_t lo, uint32_t hi) { char* p; asm("mov.b64 %0, {%1,%2};" : "=l"(p) : "r"(lo), "r"(hi)); return p; }
__device__ __forceinline__ float ex2(float x) { float r; asm("ex2.approx.ftz.f32 %0, %1;" : "=f"(r) : "f"(x)); return r; }
__device__ __forceinline__ float max8(const float* x) { return fmaxf(fmaxf(fmaxf(x[0], x[1]), fmaxf(x[2], x[3])), fmaxf(fmaxf(x[4], x[5]), fmaxf(x[6], x[7]))); }
__device__ __forceinline__ float max4lanes(float m) { return fmaxf(fmaxf(m, __shfl_xor_sync(~0u, m, 1)), fmaxf(__shfl_xor_sync(~0u, m, 2), __shfl_xor_sync(~0u, m, 3))); }
constexpr float SCL = 0.08838834764831845f * 1.4426950408889634f;
__device__ __forceinline__ void tok_scores(float* x, uint32_t sa) {
    float y[8];
    lds128f(x, sa); lds128f(y, sa + 1024); lds128f(x + 4, sa + 512); lds128f(y + 4, sa + 1536);
    #pragma unroll
    for (int i = 0; i < 8; i++) x[i] += y[i];
}
__device__ __forceinline__ void mem_scores(float* x, uint32_t sa) {
    float z[8];
    lds128f(z, sa + 2048); lds128f(z + 4, sa + 2560);
    x[8] = (z[0] + z[2]) + (z[4] + z[6]); x[9] = (z[1] + z[3]) + (z[5] + z[7]);
}

struct Ctx { uint32_t u_rs, u_rl, u_bs, u_bl, rblo, rbhi; int w8, c; };
template <int wg>
__device__ __forceinline__ void steps(uint32_t* W, uint32_t* T, uint32_t t16, uint32_t pa, uint32_t pb, const Ctx& cx, const CUtensorMap* tmX, const MainParams& prm) {
    using namespace mk;
    const int c = cx.c, kap = c & 1, w8 = cx.w8;
    const uint32_t rbhi = cx.rbhi;
    uint32_t u_rs = cx.u_rs, u_rl = cx.u_rl, u_bs = cx.u_bs, u_bl = cx.u_bl ^ ((c & 2) << 14);
    uint32_t u_x = cx.rblo + RB_X + (c >> 2) * 16384, u_xs = u_x + kap * 2048 + (c & 2) * 512;
    uint32_t u_ta = ((cx.u_bl & ~0x10000u) ^ (kap << 12)) + (RB_T - RB_B) + 1024;
    uint32_t u_rp = cx.rblo + RB_T + 1024 + c * 4;
    uint32_t u_og = (c & 3) * 65536 + (c >> 2) * 2048 + (w8 & 3) * 256;
    const uint32_t u_sa = (w8 & 2) * 256 + (w8 & 1) * 8;
    #define TOK_DST() tok_dst(c, seg, wg)
    constexpr int EV = wg ? EV1 : EV0;
    constexpr uint32_t VEB = VE + (wg ? EV0 * 2048 - 2048 : 0) - (16 - EV) * 2048;
    static_assert((EV0 + EV1) * 2048 <= 28672, "");
    __syncthreads();
    #pragma unroll
    for (int i = 16 - EV; i < 16; i++) sts128(VEB + i * 2048 + t16, make_uint4(T[4 * i], T[4 * i + 1], T[4 * i + 2], T[4 * i + 3]));
    asm volatile("fence.proxy.async.shared::cta;" ::: "memory");
    #pragma unroll 1
    for (uint32_t sb = 0, redo = 0, uz = prm.zero;;) {
        sb = opq(sb + 256);
        const int s = sb & 255, bc = sb >> 8;
        t16 |= uz;
        uz &= sb;
        const int seg = s + 2;
        const uint32_t tau = phase(s);
        const uint32_t l16 = opq(t16 & 0x1F0);
        uint32_t F[64];
        float ot[3][2][4];
        uint32_t an[4];
        #define LDB(i) ldsm4t(b[i][0], b[i][1], b[i][2], b[i][3], MEM + l16 + (i) * 512)
        #define ST_X() do { char* xs = at(u_xs + (pb >> 16), rbhi) + wg * 4096; \
            st_g32(xs, tagm(pack2((a[0][0] + a[1][0]) + (a[2][0] + a[3][0]), (a[0][2] + a[1][2]) + (a[2][2] + a[3][2])), mG, tau * 0x10001u)); \
            st_g32(xs + 32, tagm(pack2((a[0][1] + a[1][1]) + (a[2][1] + a[3][1]), (a[0][3] + a[1][3]) + (a[2][3] + a[3][3])), mG, tau * 0x10001u)); } while (0)
        #define ST_V() st_g64(at(u_xs + (t16 >> 1), rbhi) + (8192 + wg * 3072), \
            tagm(pack2((v[0][0] + v[1][0]) + (v[2][0] + v[3][0]), (v[0][1] + v[1][1]) + (v[2][1] + v[3][1])), mT, tau), \
            pack2((v[0][2] + v[1][2]) + (v[2][2] + v[3][2]), (v[0][3] + v[1][3]) + (v[2][3] + v[3][3])))
        #define V_MMA(i, o) do { mmaq(v[2 * ((i) & 1)], &T[8 * (i)], b[(o) + (i)][0], b[(o) + (i)][1]); mmaq(v[2 * ((i) & 1) + 1], &T[8 * (i) + 4], b[(o) + (i)][2], b[(o) + (i)][3]); } while (0)
        #define ST_R(i) do { \
                const uint32_t r0 = pack2((r[i][0][0] + r[i][1][0]) * i0, (r[i][0][1] + r[i][1][1]) * i1); \
                const uint32_t r1 = pack2((r[i][0][2] + r[i][1][2]) * i0, (r[i][0][3] + r[i][1][3]) * i1); \
                st_g64(at(ra ^ (i * 0x3000), rbhi), tagm(r0, mT, tau), r1); } while (0)
        #define LD_OB(i) ldsm4t(ob[4 * (i)], ob[4 * (i) + 1], ob[4 * (i) + 2], ob[4 * (i) + 3], OB + l16 + (i) * 512)
        #define WO_MMA(have, more, mid, tail) uint32_t ob[16], ra; float r[2][2][4] = {}; \
            LD_OB(0); __syncwarp(); LD_OB(1); __syncwarp(); if (OBA > 2) { LD_OB(2); __syncwarp(); } \
            _Pragma("unroll") for (int i = have; i < have + more; i++) { lds128u(&F[4 * i], WO + t16 + i * 4096); __syncwarp(); } \
            _Pragma("unroll") for (int i = 0; i < 16; i++) { \
                if (!(i & 1) || (i > 4 && i < 8)) CUT(pb); \
                if (i == 4) LD_OB(OBA); \
                if (i == 5 && OBA == 2) LD_OB(3); \
                { const int n = have + more + i - 8 + OBA; if (i >= 8 - OBA && n < 16) lds128u(&F[4 * n], WO + t16 + n * 4096); } \
                if (wg == 0 && i == 4) { const float2 su = lds64f(SUM + (l16 >> 1)); i0 = su.x; i1 = su.y; } \
                mmaq(r[(i >> 1) & 1][i & 1], &F[4 * i], ob[(i >> 2) * 4 + 2 * (i & 1)], ob[(i >> 2) * 4 + 2 * (i & 1) + 1]); \
                if (wg && i == 2) { i0 = opqf(rcpf(i0)); i1 = opqf(rcpf(i1)); } \
                if (i == PP) { mid; } \
                if (wg && i == POL) POLL(); \
                if (!wg && i == KVP) bulk_copy(TK + 16384 + w8 * 4096, kv_src(c, s + 1) + (16384 + w8 * 4096), 4096, MB_KV); \
                if (i == 11) { ra = (l16 >> 1) * 33 & 0x1078; CUT(ra); } \
                if (i == 13) ra = opq(ra ^ u_rs); } \
            CUT(pb); tail; \
            if (!wg) { i0 = rcpf(i0); i1 = rcpf(i1); } \
            ST_R(0); ST_R(1)
        #define LD_X(r, o) do { ld_g64(r, xa + (o)); ld_g64(r + 2, xa + ((o) + 2048)); ld_g64(r + 4, xa + ((o) + 1024)); ld_g64(r + 6, xa + ((o) + 3072)); } while (0)
        #define REPORT(w, add) asm volatile("{ .reg .pred p; .reg .u32 t; setp.lt.u32 p, %1, 32; mov.u32 t, %1; @p mov.u32 t, %%globaltimer_lo; add.u32 t, t, %3; lop3.b32 t, t, 31, %2, 0xB8; @p st.relaxed.gpu.global.u32 [%0], t; }" \
            :: "l"(at(u_rp + (l16 << 8), rbhi)), "r"(t16 - (w) * 512), "r"(s), "r"(add) : "memory")
        #define POLL() asm volatile("{ .reg .pred p; setp.ge.u32 p, %5, 3584; mov.u32 %0, 0; mov.u32 %1, 0; mov.u32 %2, 0; mov.u32 %3, 0; @p ld.relaxed.gpu.global.v4.u32 {%0,%1,%2,%3}, [%4]; }" \
            : "=&r"(an[0]), "=&r"(an[1]), "=&r"(an[2]), "=&r"(an[3]) : "l"(at(u_ta + l16, rbhi)), "r"(t16) : "memory")
        #define GET_B(sl) do { const uint32_t a_ = u_bl ^ (sl); bulk_copy(MEM, at(a_, rbhi), 4096, MB_B); bulk_copy(MEM + 4096, at(a_ ^ 0x3000, rbhi), 4096, MB_B); } while (0)
        if constexpr (wg == 0) {
            float a[4][4], v[4][4] = {};
            uint32_t b[16][4];
            if (__builtin_expect(redo, 0)) {
                RETRY(6, 1);
                bsync<B_RD, 256>();
                if (w8 == 3) { bulk_expect(MB_B, 8192); GET_B(1 << 20); }
                __syncwarp();
            }
            const uint32_t ck = opq(t16 * 2 + ((l16 >> 4) & 0x1C)), tp = opq(phase(s - 1)), cm = opq((2 * bc + (s > 0 && bc < SPIN_LIMIT)) | (t16 >> 19));
            CUT(pa);
            mbar_wait(MB_B, ~bc & 1);
            #define ORD(n) (n)
            LDB(ORD(0)); __syncwarp(); LDB(ORD(1)); __syncwarp();
            const uint32_t c0 = lds32(MEM + ck), c1 = lds32(MEM + 4096 + ck);
            __syncwarp();
            #pragma unroll
            for (int n = 2; n < PRE0; n++) { LDB(ORD(n)); __syncwarp(); }
            PROF(0);
            uint32_t vw[2];
            #pragma unroll
            for (int n = 0; n < 16; n++) {
                const int i = ORD(n);
                CUT(pa);
                #pragma unroll
                for (int m = AHEAD(n); m < AHEAD(n + 1); m++) { LDB(ORD(m)); __syncwarp(); }
                if (n == HC) redo = opq(lop3<0x7E>(c0, tp, c1) & cm);
                if (n == HC + 1) asm volatile("{ .reg .pred p; setp.ne.u32 p, %2, 0; @p st.shared.u32 [%0], %1; }" :: "r"(SUM + 256), "r"(cm), "r"(redo & 1) : "memory");
                if (n == H0) barrive<B_H0, 256>();
                if (n == HR + 1) { redo = lds32(SUM + 256 + opq(t16 >> 20)); __syncwarp(); }
                if (n == HR) bsync<B_START, 128>();
                if (n == 12) redo = !late(redo ^ (2 * bc + 1), 0, ~0u);
                const int e = n < 8 ? 0 : 2 * (~n & 1);
                if (!(n & 7)) a[e][0] = a[e][1] = a[e][2] = a[e][3] = a[e + 1][0] = a[e + 1][1] = a[e + 1][2] = a[e + 1][3] = 0.f;
                mmaq(a[e], &W[8 * i], b[i][0], b[i][1]);
                if (n < 8) { mmaq(v[0], &T[8 * i], b[i][0], b[i][1]); CUT(pa); }
                mmaq(a[e + 1], &W[8 * i + 4], b[i][2], b[i][3]);
                if (n < 8) mmaq(v[1], &T[8 * i + 4], b[i][2], b[i][3]);
                if (n == 10) { vw[0] = opq(pack2(v[0][0] + v[1][0], v[0][1] + v[1][1])); vw[1] = opq(pack2(v[0][2] + v[1][2], v[0][3] + v[1][3])); }
            }
            CUT(pa);
            if (__builtin_expect(redo, 0)) { __syncwarp(); continue; }
            CUT(pa); CUT(pb);
            const uint32_t mG = (l16 & 0x1C0) ? 0 : 0x10001u, mT = (l16 & 0x30) ? 0 : 1;
            ST_X();
            CUT(pa);
            PROF(1);
            const char* const xa = at(u_x + (t16 >> 1), rbhi);
            float sc[4][4];
            uint32_t k[8], A[16], q[16], kf[16];
            #define LD_Q(xb) do { LD_X(q, 0); { const char* const xa = xb; LD_X(q + 8, 0); } } while (0)
            #define XB() at((u_x + (opq(t16) >> 1)) ^ 256, rbhi)
            #define LD_A(i) ldsm4t(A[4 * i], A[4 * i + 1], A[4 * i + 2], A[4 * i + 3], TQ + (i & 1) * 1024 + ((i & 2) ? qb : qa))
            uint32_t k1[16];
            #define LD_K(i) do { ldsm4t(kf[4 * i], kf[4 * i + 1], kf[4 * i + 2], kf[4 * i + 3], TK + ka[i]); ldsm4t(k1[4 * i], k1[4 * i + 1], k1[4 * i + 2], k1[4 * i + 3], TK + 8192 + ka[i]); __syncwarp(); } while (0)
            const char* const xb = XB();
            const uint32_t ka[4] = {opq(pa & 0xFFFF), opq((pa & 0xFFFF) ^ 0x400), opq((pa & 0xFFFF) ^ 0x10), opq((pa & 0xFFFF) ^ 0x410)}, qa = opq(pa >> 16), qb = opq(qa ^ 0x100);
            st_g64(at(u_xs + (t16 >> 1), rbhi) + 8192, tagm(vw[0], mT, tau), vw[1]);
            CUT(pb);
            bsync<B_H2, 256>();
            if (QF) { LD_Q(xb); __syncwarp(); }
            #pragma unroll
            for (int i = 0; i < NA; i++) LD_K(i);
            CUT(pb);
            #pragma unroll
            for (int i = 0; i < 4 * NA; i++) kf[i] = opq(hadd2(kf[i], k1[i]));
            CUT(pb);
            if (!QF) { DELAY(QD); LD_Q(xb); CUT(pb); }
            bsync<B_H3, 256>();
            #pragma unroll
            for (int i = NA; i < 4; i++) LD_K(i);
            LD_A(0); LD_A(1); LD_A(2); LD_A(3);
            CUT(pb);
            if (KM == 1) {
                #pragma unroll
                for (int i = 4 * NA; i < 16; i++) kf[i] = opq(hadd2(kf[i], k1[i]));
                CUT(pb);
            }
            DELAY(KD);
            LD_X(k, 4096);
            barrive<B_VX, 256>();
            CUT(pb);
            PROF(3);
            if (KM == 2) {
                #pragma unroll
                for (int i = 4 * NA; i < 16; i++) kf[i] = opq(hadd2(kf[i], k1[i]));
            }
            #pragma unroll
            for (int i = 0; i < 8; i++) A[2 * i + 1] = opq(hadd2(A[2 * i], A[2 * i + 1]));
            CUT(pb);
            AGAIN(1, LD_Q(XB()); LD_X(k, 4096); sts32(SUM + 268, s + 1), late(stale<4, 2>(q, tau), stale<4, 2>(q + 8, tau), mT))
            #pragma unroll
            for (int i = 0; i < 4; i++) {
                A[4 * i] = hadd2(q[4 * i], q[4 * i + 2]); A[4 * i + 2] = hadd2(q[4 * i + 1], q[4 * i + 3]);
                if (i < 2) { sc[i][0] = sc[i][1] = sc[i][2] = sc[i][3] = sc[2 + i][0] = sc[2 + i][1] = sc[2 + i][2] = sc[2 + i][3] = 0.f; }
                mmaq(sc[i & 1], A + 4 * i, kf[2 * i], kf[2 * i + 1]); mmaq(sc[2 + (i & 1)], A + 4 * i, kf[8 + 2 * i], kf[9 + 2 * i]);
            }
            sts128f(SC + t16, sc[0][0] + sc[1][0], sc[0][1] + sc[1][1], sc[2][0] + sc[3][0], sc[2][1] + sc[3][1]);
            barrive<B_S1, 256>();
            sts128f(SC + 3072 + t16, sc[0][2] + sc[1][2], sc[0][3] + sc[1][3], sc[2][2] + sc[3][2], sc[2][3] + sc[3][3]);
            load_frag<0, WB1>(WO + t16, F);
            const uint32_t sa = opq(l16 + u_sa);
            CUT(pb);
            PROF(4);
            float d[16];
            #pragma unroll 1
            for (int n_ = 0;; n_++) {
                #pragma unroll
                for (int i = 0; i < 4; i++) { d[4 * i] = d[4 * i + 1] = d[4 * i + 2] = d[4 * i + 3] = 0.f; mmaq(d + 4 * i, A + 4 * (i >> 1), k[2 * i], k[2 * i + 1]); }
                if (__builtin_expect(!late(stale<2, 2>(k, tau), stale<2, 2>(k + 4, tau), mT), 1) || n_ >= SPIN_LIMIT) break;
                RETRY(2, 1);
                LD_X(k, 4096);
            }
            sts64f(SC + 2048 + sa, (d[0] + d[4]) + (d[8] + d[12]), (d[1] + d[5]) + (d[9] + d[13]));
            barrive<B_SC, 256>();
            CUT(pb);
            sts64f(SC + 5120 + sa, (d[2] + d[6]) + (d[10] + d[14]), (d[3] + d[7]) + (d[11] + d[15]));
            PROF(5);
            if (w8 == 0) {
                float x[10];
                bsync<B_S0, 128>();
                tok_scores(x, SC + 3072 + l16); mem_scores(x, SC + 3072 + l16);
                __syncwarp();
                load_frag<WB1, WB2>(WO + t16, F);
                const int g = l16 >> 6, lim = 8 * (g >> 1) + 2 * (c & 3) + (g & 1) - ((l16 >> 1) & 0x18);
                #pragma unroll
                for (int i = 0; i < 8; i++) if (i > lim) x[i] = -INFINITY;
                const float ms = opqf(-SCL * max4lanes(fmaxf(max8(x), fmaxf(x[8], x[9]))));
                CUT(pb);
                #pragma unroll
                for (int i = 0; i < 10; i++) x[i] = ex2(fmaf(x[i], SCL, ms));
                load_frag<WB2, WB3>(WO + t16, F);
                sts128(PT + l16, make_uint4(pack2(x[0], x[1]), pack2(x[2], x[3]), pack2(x[4], x[5]), pack2(x[6], x[7])));
                sts32(PT + 512 + (l16 >> 2), pack2(x[8], x[9]));
                if (!ONE) barrive<B_PT, 160>();
            } else {
                if (ANN == 2) { bsync<B_S0, 128>(); const uint32_t f = lds32(SUM + 268 + opq(t16 >> 16)); REPORT(3, f == s + 1 ? P(2) : 0); } else barrive<B_S0, 128>();
                if (w8 == 1) {
                    mbar_wait(MB_X, ~seg & 1); bulk_expect(MB_X, 32768);
                    if (XPF) prefetch_l2(prm.x + (((seg + XPF) & 63) * 65536 + c * 512), 512);
                    __syncwarp();
                    if (XDL == 300) load_x(tmX, c, seg + 1, (s & 1) ? XT : XT2);
                }
                else if (w8 == 2) {
                    bulk_expect(MB_KV, 36864);
                    bulk_copy(TK, kv_src(c, s + 1), 16384, MB_KV); bulk_copy(TQ, kv_src(c, s + 1) + (32768 + (c & 3) * 4096), 4096, MB_KV);
                    bulk_expect(MB_B, 8192); bulk_expect(MB_R, 4096);
                    __syncwarp();
                }
                bsync<B_SC2, 224>();
                load_frag<WB1, WB3>(WO + t16, F);
                __syncwarp();
                CUT(pb);
            }
            bsync<B_O2, 256>();
            PROF(6);
            float i0, i1;
            WO_MMA(WB3, 0, , );
        } else {
            float a[4][4], v[4][4] = {};
            uint32_t b[16][4];
            barrive_if<B_RD, 256>(redo);
            CUT(pa);
            bsync<B_H0, 256>();
            #pragma unroll
            for (int n = 0; n < PRE1; n++) { LDB(n); __syncwarp(); }
            redo = lds32(SUM + 256 + opq(t16 >> 20));
            PROF(0);
            #pragma unroll
            for (int i = 0; i < 16; i++) {
                if (!(i & 1)) {
                    CUT(pa);
                    if (PRE1 < 8 && i + PRE1 < 16) { LDB(i + PRE1); __syncwarp(); LDB(i + PRE1 + 1); __syncwarp(); }
                    if (PRE1 == 8 && i >= 2 && i < 10) { LDB(i + 6); __syncwarp(); LDB(i + 7); __syncwarp(); }
                    if (i == 6) redo = !late(redo ^ (2 * bc + 1), 0, ~0u);
                    if (i == H2) { barrive_if<B_H2, 256>(!redo); CUT(pa); }
                }
                else if (CO) CUT(pa);
                if (i < 2) { a[2 * i][0] = a[2 * i][1] = a[2 * i][2] = a[2 * i][3] = a[2 * i + 1][0] = a[2 * i + 1][1] = a[2 * i + 1][2] = a[2 * i + 1][3] = 0.f; }
                mmaq(a[2 * (i & 1)], &W[8 * i], b[i][0], b[i][1]); mmaq(a[2 * (i & 1) + 1], &W[8 * i + 4], b[i][2], b[i][3]);
            }
            if (__builtin_expect(redo, 0)) { __syncwarp(); continue; }
            CUT(pa); CUT(pb);
            const uint32_t mG = (l16 & 0x1C0) ? 0 : 0x10001u, mT = (l16 & 0x30) ? 0 : 1;
            ST_X();
            barrive<B_H3, 256>();
            CUT(pa);
            PROF(1);
            #pragma unroll
            for (int i = 7; i >= 0; i--) V_MMA(i, 8);
            ST_V();
            CUT(pb);
            bsync<B_VX, 256>();
            PROF(2);
            uint32_t vf[16], vm[16];
            const uint32_t va = opq(pa), vb = opq(va ^ 0x20);
            #define LD_V() do { _Pragma("unroll") for (int i = 0; i < 4; i++) { const uint32_t a_ = TK + 16384 + ((i & 1) ? vb : va) + (i >> 1) * 4096; \
                ldsm4(vf[4 * i], vf[4 * i + 1], vf[4 * i + 2], vf[4 * i + 3], a_); ldsm4(vm[4 * i], vm[4 * i + 1], vm[4 * i + 2], vm[4 * i + 3], a_ + 8192); } } while (0)
            LD_V();
            __syncwarp();
            load_frag<0, WA0>(WO + t16, F);
            #pragma unroll
            for (int i = 0; i < 16; i++) vf[i] = opq(hadd2(vf[i], vm[i]));
            const char* const xa = at(u_x + (t16 >> 1), rbhi) + (8192 - 1024);
            if (VP) CUT(pb);
            DELAY(VD);
            LD_X(vm, 0); LD_X(vm + 8, 4096);
            __syncwarp();
            load_frag<WA0, WA1>(WO + t16, F);
            CUT(pb);
            float x[10];
            bsync<B_S1, 256>();
            tok_scores(x, SC + l16);
            const float mt = opqf(max8(x));
            if (ANN == 3) REPORT(7, 0);
            CUT(pb);
            PROF(3);
            bsync<B_SC, 256>();
            mem_scores(x, SC + l16);
            const float m1 = fmaxf(mt, fmaxf(x[8], x[9]));
            const float m2 = __shfl_xor_sync(~0u, m1, 1), m3 = __shfl_xor_sync(~0u, m1, 2), m4 = __shfl_xor_sync(~0u, m1, 3);
            CUT(pb);
            load_frag<WA1, WA2>(WO + t16, F);
            barrive<B_SC2, 224>();
            uint32_t p[5], vs[4];
            #define SUM_V() do { _Pragma("unroll") for (int i = 0; i < 4; i++) { const int e = (i >> 1) * 4 + (i & 1); vs[i] = hadd2(hadd2(vm[e], vm[e + 8]), hadd2(vm[e + 2], vm[e + 10])); } } while (0)
            CUT(pb);
            const float ms = -SCL * fmaxf(fmaxf(m1, m2), fmaxf(m3, m4));
            PROF(5);
            #pragma unroll
            for (int i = 0; i < 10; i++) x[i] = fmaf(x[i], SCL, ms);
            x[8] = opqf(ex2(x[8])); x[9] = opqf(ex2(x[9]));
            CUT(pb);
            uint32_t badv = late(stale<4, 2>(vm, tau), stale<4, 2>(vm + 8, tau), mT);
            SUM_V();
            #pragma unroll
            for (int i = 0; i < 4; i++) { x[i] = opqf(ex2(x[i])); vs[i] = opq(vs[i]); }
            const uint32_t z0 = t16 >> 16;
            uint32_t one[4] = {opq(ONES | z0), opq(ONES ^ z0), opq(ONES + z0), opq(ONES - z0)};
            CUT(pb);
            #pragma unroll
            for (int i = 4; i < 8; i++) x[i] = ex2(x[i]);
            #pragma unroll
            for (int i = 0; i < 5; i++) p[i] = pack2(x[2 * i], x[2 * i + 1]);
            float sm[4] = {};
            #define PV(also) do { float o[8] = {}; \
                mma8(o, vs[0], vs[1], p[4]); mma8(o + 4, vs[2], vs[3], p[4]); if (also) mma8(sm, one[0], one[1], p[4]); \
                mmaq(o, vf, p[0], p[1]); mmaq(o + 4, vf + 8, p[0], p[1]); if (also) mmaq(sm, one, p[0], p[1]); \
                mmaq(o, vf + 4, p[2], p[3]); mmaq(o + 4, vf + 12, p[2], p[3]); if (also) mmaq(sm, one, p[2], p[3]); \
                stsm4(OB - 2048 + opq(t16), pack2(o[0], o[1]), pack2(o[2], o[3]), pack2(o[4], o[5]), pack2(o[6], o[7])); } while (0)
            PV(true);
            if (w8 == 4) sts64f(SUM + (l16 >> 1), sm[0], sm[1]);
            if (__builtin_expect(badv, 0)) {
                int n_ = 0;
                uint32_t vm[16];
                const char* const xa = at(u_x + (8192 - 1024) + (opq(t16) >> 1), rbhi);
                do { RETRY(3, 1); LD_X(vm, 0); LD_X(vm + 8, 4096); } while (late(stale<4, 2>(vm, tau), stale<4, 2>(vm + 8, tau), mT) && ++n_ < SPIN_LIMIT);
                SUM_V();
                PV(false);
            }
            if (ONE) bsync<B_O2, 256>(); else { barrive<B_O2, 256>(); bsync<B_O, 128>(); }
            PROF(6);
            float i0 = sm[0], i1 = sm[1];
            #define GET_P() if (!ONE) bsync<B_PT, 160>(); lds128u(p, PT + l16); p[4] = lds32(PT + 512 + (l16 >> 2))
            #define TOK_PV() { const uint32_t z = t16 >> 17; one[0] = ONES | z; one[1] = ONES ^ z; one[2] = ONES + z; one[3] = ONES - z; } \
                _Pragma("unroll") for (int i = 0; i < 12; i++) ot[i >> 2][0][i & 3] = ot[i >> 2][1][i & 3] = 0.f; \
                mma8(ot[0][0], vs[0], vs[1], p[4]); mma8(ot[1][0], vs[2], vs[3], p[4]); mma8(ot[2][0], one[0], one[1], p[4]); \
                mmaq(ot[0][1], vf + 4, p[2], p[3]); mmaq(ot[1][1], vf + 12, p[2], p[3]); mmaq(ot[2][1], one, p[2], p[3]); CUT(pa)
            WO_MMA(WA2, WA3, GET_P(), TOK_PV());
            CUT(pa);
            mmaq(ot[0][0], vf, p[0], p[1]); mmaq(ot[1][0], vf + 8, p[0], p[1]); mmaq(ot[2][0], one, p[0], p[1]);
            CUT(pb);
            barrive<B_GO, 256>();
        }
        CUT(pb);
        PROF(7);
        #define PK_O() const float j0 = rcpf(ot[2][0][0] + ot[2][1][0]), j1 = rcpf(ot[2][0][1] + ot[2][1][1]); uint32_t ow[4]; \
            _Pragma("unroll") for (int i = 0; i < 4; i++) \
                ow[i] = opq(pack2((ot[i >> 1][0][2 * (i & 1)] + ot[i >> 1][1][2 * (i & 1)]) * j0, (ot[i >> 1][0][2 * (i & 1) + 1] + ot[i >> 1][1][2 * (i & 1) + 1]) * j1))
        #define ST_O() do { uint32_t* og = (uint32_t*)((char*)g_O + (u_og + (l16 >> 2))); \
            _Pragma("unroll") for (int i = 0; i < 4; i++) og[(i >> 1) * 256 + (i & 1) * 32] = ow[i]; } while (0)
        #define BSO() ((u_bs) ^ ((l16 & 0x10) + ((l16 >> 3) & 0xC) + (l16 & 0x80) * 0x20 + (l16 & 0x100) * 0x80))
        const uint32_t taus = phase(seg);
        const uint64_t* const dq = c_xd + (s & 1) * 32; const uint64_t* const dv = dq + (wg * 16 | uz);
        float acc[16], acv[16];
        uint32_t u[8];
        if constexpr (wg == 0) {
            if (s == NSEG - 1) { bsync<B_GO, 256>(); st_g32(at(BSO(), rbhi), 0); mbar_wait(MB_KV, 1); if (XDL == 300) mbar_wait(MB_X, 1); break; }
            load_frag<16 - EV, 16, 2048>(VEB + t16, T);
            bsync<B_GO, 256>();
            PROF(8);
            wg_run<0, 16 - EV>(acv, T, dv);
            wg_run<16 - EV, 16>(acv, T, dv);
            wg_run<0, 5>(acc, W, dq); wg_wait<1>();
            qk_pack(acv, u);
            #pragma unroll
            for (int i = 0; i < 8; i++) u[i] = opq(u[i]);
            CUT(pa);
            wg_run<5, 8>(acc, W, dq);
            __syncwarp();
            sts128(SC + opq(t16), make_uint4(u[0], u[1], u[2], u[3])); sts128(SC + 2048 + opq(t16), make_uint4(u[4], u[5], u[6], u[7]));
            barrive<B_VX, 256>();
            __syncwarp();
            PROF(9);
            wg_run<8, 12>(acc, W, dq);
            CUT(pa);
            char* const bs = at(opq(BSO()), opq(rbhi));
            CUT(pa);
            wg_run<12, 15>(acc, W, dq);
            CUT(pa);
            const uint32_t ro = opq(l16 * 8 + ((l16 & 0x70) ^ ((w8 & 3) << 5))), ro2 = opq(ro ^ 0x10);
            const uint32_t mG = opq((l16 & 0x1C0) ? 0 : 0x10001u), mB = opq((((l16 >> 2) & 4) + ((l16 >> 5) & 3)) == ((u_bs >> 7) & 7) ? 1 : 0), zz = t16 >> 18;
            CUT(pa);
            wg_run<15, 18>(acc, W, dq);
            CUT(pa);
            const uint32_t one[4] = {opq(ONES | zz), opq(ONES ^ zz), opq(ONES + zz), opq(ONES - zz)};
            const uint32_t par = s & 1, tt = tau * 0x10001u;
            CUT(pa);
            wg_run<18, RP>(acc, W, dq);
            CUT(pa);
            PROF(10);
            mbar_wait(MB_R, par);
            PROF(14);
            uint32_t x[8], bad;
            float d[4][4];
            #define SUM_R() do { ldsm4t(x[0], x[1], x[2], x[3], RS + ro); ldsm4t(x[4], x[5], x[6], x[7], RS + ro2); \
                _Pragma("unroll") for (int i = 0; i < 4; i++) { d[i][0] = d[i][1] = d[i][2] = d[i][3] = 0.f; mmaq(d[i], one, x[2 * i], x[2 * i + 1]); } } while (0)
            #define PUT_B() do { bad = late(stale<2, 1>(x, tt), stale<2, 1>(x + 2, tt), mG); \
                const uint32_t w0 = pack2(d[0][0] + d[1][0], d[0][1] + d[1][1]), w1 = pack2(d[2][0] + d[3][0], d[2][1] + d[3][1]); \
                asm volatile("{ .reg .pred p; setp.eq.b32 p, %2, 0; @p st.relaxed.gpu.global.u32 [%0], %1; }" :: "l"(bs), "r"(tagm((l16 & 0x40) ? w1 : w0, mB, tt)), "r"(bad) : "memory"); } while (0)
            SUM_R();
            CUT(pa);
            wg_run<RP, (RP + RQ < 32 ? RP + RQ : 32)>(acc, W, dq);
            if (RP + RQ >= RL) barrive<B_BT, 256>();
            CUT(pa);
            PUT_B();
            const uint32_t tb = lds32(SUM + 272 + 28 + zz);
            CUT(pa);
            PROF(11);
            if (RP + RQ < RL) { wg_run<RP + RQ, RL>(acc, W, dq); __syncwarp(); barrive<B_BT, 256>(); __syncwarp(); }
            wg_run<(RP + RQ < RL ? RL : RP + RQ), 32>(acc, W, dq);
            CUT(pa);
            AGAIN(5, ld_g128(x, at(u_rl + opq(ro), rbhi)); ld_g128(x + 4, at(u_rl + opq(ro2), rbhi)); sts128(RS + ro, make_uint4(x[0], x[1], x[2], x[3])); sts128(RS + ro2, make_uint4(x[4], x[5], x[6], x[7]));
                     CUT(pa); __syncwarp(); SUM_R(); PUT_B(), bad)
            #define REQ_B() if (w8 == 3) { TRC(13, gtime() - tb); wait_g(tb, t16); GET_B(0); PROFW(13, 3); }
            if (!BL) REQ_B();
            const uint32_t ps = opq(pb & 0xFFFF), ps2 = opq(ps ^ HI8);
            char* const qd0 = TOK_DST() + ps; char* const qd1 = TOK_DST() + ps2;
            TAGM();
            wg_wait<0>();
            pack_tag(acc, u, taus, tm);
            #pragma unroll
            for (int i = 0; i < 8; i++) u[i] = opq(u[i]);
            CUT(pa);
            if (BL) REQ_B();
            bsync<B_S0, 128>();
            st_if(seg < NSEG, qd0, u); st_if(seg < NSEG, qd1, u + 4);
            if (XDL >= 200 && XDL < 300 && w8 == 1) { CUT(pb); DELAY(XDL - 200); load_x(tmX, c, seg + 1, (s & 1) ? XT : XT2); }
            PROF(12);
        } else {
            #define LAST() __reduce_max_sync(~0u, max(max(an[0], an[1]), max(an[2], an[3])))
            PK_O();
            CUT(pa);
            if (s == NSEG - 1) { ST_O(); break; }
            PROF(8);
            if (w8 != 7) {
                load_frag<16 - EV, 16 - EV + TA0, 2048>(VEB + t16, T);
                mbar_wait(MB_KV, s & 1);
                AGAIN(0, refetch_kv(c, s + 1, w8 - 4, l16), kv_stale(w8 - 4, l16, phase(s + 1)))
            } else {
                uint32_t tr = LAST();
                AGAIN(8, ld_g128(an, at(u_ta + l16, rbhi)); tr = LAST(), late(stale<2, 1>(an, s), stale<2, 1>(an + 2, s), 31))
                tr = (tr & ~31u) + P(0);
                TRC(14, gtime() - tr);
                wait_g(tr, t16);
                if (R4) { for (int i = 0; i < 4; i++) bulk_copy(RS + i * 1024, at(u_rl + i * 1024, rbhi), 1024, MB_R); }
                else bulk_copy(RS, at(u_rl, rbhi), 4096, MB_R);
                PROFW(14, 3);
                sts32(SUM + 272 + 28, tr + P(1));
                load_frag<16 - EV, 16 - EV + TA0, 2048>(VEB + t16, T);
                if (XDL < 100) { CUT(pb); DELAY(XDL); load_x(tmX, c, seg + 1, (s & 1) ? XT : XT2); }
            }
            CUT(pa);
            bsync<B_VX, 256>();
            lds128u(u, SC - 2048 + opq(t16)); lds128u(u + 4, SC + opq(t16));
            CUT(pa);
            ST_O();
            CUT(pa);
            load_frag<16 - EV + TA0, 16 - EV + TA, 2048>(VEB + t16, T);
            acc_init(acv, u);
            #pragma unroll
            for (int i = 0; i < 16; i++) acv[i] = opqf(acv[i]);
            const uint32_t ps = opq(pb & 0xFFFF), ps2 = opq(ps ^ HI8);
            CUT(pa);
            PROF(9);
            if (XDL == 100 && w8 == 7) load_x(tmX, c, seg + 1, (s & 1) ? XT : XT2);
            bsync<B_BT, 256>();
            CUT(pa);
            wg_run<0, 3>(acc, W, dq);
            PROF(11);
            wg_run<3, NT, true>(acc, W, dq);
            __syncwarp();
            load_frag<16 - EV + TA, 16, 2048>(VEB + t16, T);
            __syncwarp();
            wg_run<NT, NB>(acc, W, dq);
            char* const qd0 = TOK_DST() + ps; char* const qd1 = TOK_DST() + ps2;
            TAGM();
            wg_run<NB, 32>(acc, W, dq);
            wg_run<0, 5, true>(acv, T, dv);
            wg_wait<1>();
            PROF(12);
            pack_tag(acc, u, taus, tm);
            #pragma unroll
            for (int i = 0; i < 8; i++) u[i] = opq(u[i]);
            CUT(pa);
            wg_run<5, 16 - EV>(acv, T, dv);
            __syncwarp();
            st_if(seg < NSEG, qd0, u); st_if(seg < NSEG, qd1, u + 4);
            __syncwarp();
            wg_run<16 - EV, 16>(acv, T, dv);
            CUT(pa);
            PROF(10);
            wg_wait<0>();
            PROF(13);
            pack_tag(acv, u, taus, tm);
            st_if(seg < NSEG, qd0 + 16384, u); st_if(seg < NSEG, qd1 + 16384, u + 4);
        }
        sb++;
        u_rs ^= 1 << 20; u_rl ^= 1 << 20; u_bs ^= 1 << 20; u_bl ^= 1 << 20; u_x ^= 1 << 20; u_xs ^= 1 << 20; u_ta ^= 1 << 20; u_rp ^= 1 << 20; u_og += 262144;
    }
}

namespace ck {
constexpr uint32_t UPL = 144 * 16 + 64, UCH = 2 * UPL;
constexpr uint32_t FCP = 4160, FCH = 2 * FCP;
template <int NW> struct At { static constexpr uint32_t K = NW == 2 ? mk::XT : mk::SB, V = K + 32768, F = NW == 2 ? V : V + 32768, U = F + 8 / NW * FCH; };
static_assert(At<2>::U + 4 * UCH <= mk::OB && At<1>::U + 8 * UCH <= mk::OB, "");
}
struct ConvIn { const bf16 *shift_k, *ssm_k, *ssm_D; };
template <int NW> struct ConvRaw { uint4 f[8 / NW], sk[4 / NW]; uint32_t fn, d; };
template <int NW> __device__ __forceinline__ void strip_request(const CUtensorMap* tmK, int grp) {
    mbar_expect(mk::MB_C, 65536);
    #pragma unroll 1
    for (int i = 0; i < 16; i++) tma3d(ck::At<NW>::K + i * 4096, tmK + (i >> 3), grp * 8, 0, i & 7, mk::MB_C);
}
template <int NW> __device__ __forceinline__ void conv_load(ConvRaw<NW>& r, const ConvIn& in, int ch0) {
    const int tid = threadIdx.x, w = tid >> 5, ch = ch0 + w / NW, e = w % NW;
    const bf16* fp = in.ssm_k + (size_t)ch * SEQ + e * 1024;
    #pragma unroll
    for (int i = 0; i < 8 / NW; i++) r.f[i] = __ldg((const uint4*)fp + (tid & 31) + 32 * i);
    r.fn = e == NW - 1 ? 0 : __ldg((const uint32_t*)(fp + 1024));
    r.d = __ldg((const unsigned short*)in.ssm_D + ch);
    #pragma unroll
    for (int i = 0; i < 4 / NW; i++) r.sk[i] = __ldg((const uint4*)(in.shift_k + ch0 * 4) + i);
}
template <int NW> __device__ __forceinline__ void kv_build(const ConvRaw<NW>& r, int ch0) {
    using namespace ck;
    const int tid = threadIdx.x;
    if (tid < 32 * 8 / NW) sts128(At<NW>::U + (tid >> 4) * UPL + (tid & 15) * 16, make_uint4(0, 0, 0, 0));
    #pragma unroll
    for (int hf = 0; hf < 2 / NW; hf++) {
        const uint32_t a = tid * 16 + (ch0 & 4) * 2 + hf * 8;
        float2 kr[11], vr[8];
        #pragma unroll
        for (int i = 0; i < 11; i++) { kr[i] = lds64f(At<NW>::K + ((i + 5) & 7) * 4096 - (i < 3) * 16 + a); if (i < 3 && !tid) kr[i] = make_float2(0.f, 0.f); }
        #pragma unroll
        for (int i = 0; i < 8; i++) vr[i] = lds64f(At<NW>::V + i * 4096 + a);
        #pragma unroll
        for (int ch = 0; ch < 4; ch++) {
            const uint32_t s01 = ((const uint32_t*)r.sk)[8 * hf + 2 * ch], s23 = ((const uint32_t*)r.sk)[8 * hf + 2 * ch + 1];
            const float sk[4] = {bflo(s01), bfhi(s01), bflo(s23), bfhi(s23)};
            float kf[11], kv[8];
            #pragma unroll
            for (int i = 0; i < 11; i++) { const uint32_t wd = __float_as_uint((ch & 2) ? kr[i].y : kr[i].x); kf[i] = (ch & 1) ? bfhi(wd) : bflo(wd); }
            #pragma unroll
            for (int i = 0; i < 8; i++) {
                const uint32_t wv = __float_as_uint((ch & 2) ? vr[i].y : vr[i].x);
                kv[i] = fmaf(kf[i + 3], sk[0], fmaf(kf[i + 2], sk[1], fmaf(kf[i + 1], sk[2], kf[i] * sk[3]))) * ((ch & 1) ? bfhi(wv) : bflo(wv));
            }
            sts128(At<NW>::U + (hf * 4 + ch) * UCH + (tid & 1) * UPL + (16 + (tid >> 1)) * 16,
                   make_uint4(pack2(kv[0], kv[1]), pack2(kv[2], kv[3]), pack2(kv[4], kv[5]), pack2(kv[6], kv[7])));
        }
    }
}
template <int NW> __device__ __forceinline__ void conv_filter(const ConvRaw<NW>& r, bool on) {
    using namespace ck;
    constexpr int N = 8 / NW;
    const int w = threadIdx.x >> 5, lane = threadIdx.x & 31, e = w % NW;
    const uint32_t fb = At<NW>::F + w / NW * FCH;
    if (on && !e && lane < 8) { sts32(fb + 4128 + lane * 4, 0); sts32(fb + FCP + 4128 + lane * 4, lane ? 0 : r.f[0].x & 0xFFFFu); }
    #pragma unroll
    for (int i = 0; i < N; i++) {
        const int vi = e * 128 + lane + 32 * i;
        const uint4 x = r.f[i];
        const uint32_t a = __shfl_down_sync(~0u, x.x, 1), b = i < N - 1 ? __shfl_sync(~0u, r.f[i < N - 1 ? i + 1 : i].x, 0) : r.fn;
        const uint32_t nxt = lane == 31 ? b : a;
        const uint32_t ea = fb + (2056 - 8 * vi) * 2;
        if (on) sts128(ea, make_uint4(__byte_perm(x.w, 0, 0x1032), __byte_perm(x.z, 0, 0x1032), __byte_perm(x.y, 0, 0x1032), __byte_perm(x.x, 0, 0x1032)));
        if (on) sts128(ea + FCP, make_uint4(__byte_perm(nxt, x.w, 0x7610), __byte_perm(x.w, x.z, 0x7610), __byte_perm(x.z, x.y, 0x7610), __byte_perm(x.y, x.x, 0x7610)));
    }
}
template <int NW> __device__ __forceinline__ void conv_mma(int ch0, uint32_t d, uint32_t zero, bool on) {
    using namespace ck;
    constexpr int N = 16 / NW;
    const int w = threadIdx.x >> 5, lane = threadIdx.x & 31, ch = w / NW, e = w % NW, g = lane >> 2, t = lane & 3;
    float acc[N][4] = {};
    uint32_t fa = At<NW>::F + ch * FCH + ((g & 1) ? (2063 - g + 2 * t) * 2 : FCP + (2064 - g + 2 * t) * 2);
    uint32_t ua = At<NW>::U + ch * UCH + ((lane >> 3) & 1) * UPL + (24 + (e - NW) * 8 + (lane >> 4) * 8 + (lane & 7)) * 16;
    uint32_t Fr[32], A[2][8], yo = (ch0 + ch) * 512 + e * 32 + t * 8 + g;
    const uint32_t t16 = lane | zero;
    #define LD_U(m0, m1) _Pragma("unroll") for (int m = m0; m < m1; m++) ldsm4(Fr[4 * m], Fr[4 * m + 1], Fr[4 * m + 2], Fr[4 * m + 3], ua + m * 256)
    #define LD_F(b, o, p) _Pragma("unroll") for (int i = 0; i < 2; i++) { const uint32_t x_ = fa - (o) * 32 - (i ? 15 - (p) : (p)) * 256; \
        A[b][4 * i] = lds32(x_); A[b][4 * i + 1] = lds32(x_ - 16); A[b][4 * i + 2] = lds32(x_ + 16); }
    #define ROW(a, q, j0, j1, after) _Pragma("unroll") for (int j = 0; j < N; j++) if (j >= (j0) && j < (j1)) { \
        mmaq(acc[j], a, Fr[2 * (NW * j + NW - 1 - (q))], Fr[2 * (NW * j + NW - 1 - (q)) + 1]); after; }
    LD_U(0, 8);
    LD_F(0, 0, 0);
    {
        const uint32_t da = (g >> 1) == t ? d << ((g & 1) * 16) : 0, D[4] = {da, zero, zero >> 1, da ^ zero};
        ROW(D, 0, 0, N, );
    }
    #pragma unroll 1
    for (int r = on ? 0 : 7; r < 8; r++) {
        ua -= 16;
        #pragma unroll
        for (int p = 0; p < 8; p++) {
            uint32_t* const a = A[p & 1];
            a[3] = a[0] ^ zero; a[7] = a[4] ^ zero;
            LD_F(~p & 1, p == 7, (p + 1) & 7);
            if (p >= 2 && !(p & 1)) { LD_U(8 - p / 2, 9 - p / 2); }
            const int j0 = p / NW, j1 = (15 - p) / NW, jm = j0 + (j1 - j0) / 2;
            ROW(a, p, j0, jm, );
            if (CC) CUT(yo);
            ROW(a + 4, 15 - p, j1, N, if (CC) CUT(yo));
            ROW(a, p, jm, j1, );
            if (CC) CUT(yo);
            ROW(a, p, j1, N, if (CC) CUT(yo));
        }
        LD_U(0, 5);
        fa -= 32;
    }
    uint2* y = (uint2*)g_Y + yo;
    #pragma unroll
    for (int j = 0; j < N; j++) {
        const uint32_t p0 = pack2(acc[j][0], acc[j][2]), p1 = pack2(acc[j][1], acc[j][3]), x = __shfl_xor_sync(~0u, (g & 1) ? p0 : p1, 4);
        const uint32_t lo = (g & 1) ? x : p0, hi = (g & 1) ? p1 : x;
        if (on) y[j * 32 * NW] = make_uint2(__byte_perm(lo, hi, 0x5410), __byte_perm(lo, hi, 0x7632));
    }
}
__device__ __noinline__ void spare(const CUtensorMap* tmK, const ConvIn in, int i, uint32_t zero) {
    const int w = __shfl_sync(~0u, threadIdx.x >> 5, 0);
    ConvRaw<1> raw;
    #pragma unroll 1
    for (int grp = 56 + i, n = 0; grp < NSP; grp += 4, n++) {
        if (n) { mbar_wait(mk::MB_C, ~n & 1); kv_build<1>(raw, grp * 8); conv_filter<1>(raw, true); }
        const uint32_t d = raw.d;
        asm volatile("fence.proxy.async.shared::cta;" ::: "memory");
        __syncthreads();
        if (grp + 4 < NSP) {
            if (w == 0 && elect()) { mbar_expect(mk::MB_C, 65536); for (int j = 0; j < 2; j++) tma3d(ck::At<1>::K + j * 32768, tmK + 2 + j, grp * 8 + 32, 0, 0, mk::MB_C); }
            __syncwarp();
            conv_load<1>(raw, in, grp * 8 + 32);
        }
        if (n) conv_mma<1>(grp * 8, d, zero, true);
        __syncthreads();
    }
}

__device__ __forceinline__ uint32_t round_trip(char* a, int n) {
    uint32_t best = 0x7FFFu;
    #pragma unroll 1
    for (int i = 0; i < n; i++) {
        uint32_t v; const uint32_t t0 = clk();
        asm volatile("atom.relaxed.gpu.global.exch.b32 %0, [%1], %2;" : "=r"(v) : "l"(a), "r"(i) : "memory");
        if (v == 0x7FC1A5A5u) g_err = 2;
        best = min(best, clk() - t0);
    }
    return (__popc((uint32_t)(uintptr_t)a & HOME_BITS) & 1) ? best << 16 | 0x7FFFu : best | 0x7FFF0000u;
}
__device__ __forceinline__ int place(int by_sm) {
    uint32_t sm = blockIdx.x;
    if (by_sm) asm volatile("mov.u32 %0, %%smid;" : "=r"(sm));
    const uint32_t g = sm < 64 ? (sm & 15) >> 1 : 1 + (sm - 64) % 14 / 2, j = sm < 64 ? sm >> 4 : 4 + (sm - 64) / 14;
    return sm < 120 ? (g ? g * 16 - 8 : 0) + j * 2 + (sm & 1) : sm;
}
__device__ __forceinline__ void publish(char* rb, int p) {
    const int t = threadIdx.x, i = p * 2 + (t >> 6);
    char* line = rb + RB_P + (i & 31) * 128 + (i >> 5) * 8192 + (t & 32) * 128;
    if ((t & 31) < 2) st_g128(line + (t & 1) * 16, 0, 0, 0, 0);
    __syncwarp();
    if (!(t & 31)) sts32(mk::SUM + (t >> 3), round_trip(line, NPR));
    bsync<1, 128>();
    if (t == 32) {
        const uint4 x = lds128(mk::SUM);
        st_g32(g_cls + p, 0x80000000u | __vminu2(__vminu2(x.x, x.y), __vminu2(x.z, x.w)));
    }
    __syncwarp();
}
__device__ __forceinline__ uint32_t survey(uint32_t& x, int n) {
    const int lane = threadIdx.x & 31;
    uint32_t a[4] = {}, b[2] = {};
    while (__any_sync(~0u, !((a[0] & a[1] & a[2] & a[3] & b[0] & b[1]) >> 31)) && --n > 0) { ld_g128(a, g_cls + lane * 4); ld_g64(b, g_cls + 120 + lane % 6 * 2); }
    const uint32_t m = __vminu2(__vminu2(a[0], a[1]), __vminu2(a[2], a[3])), e = __vminu2(b[0], b[1]);
    const uint32_t M = __ballot_sync(~0u, (m >> 16 & 0x7FFF) < (m & 0xFFFF)) & 0x3FFFFFFF, E = __ballot_sync(~0u, (e >> 16 & 0x7FFF) < (e & 0xFFFF)) & 63;
    const int x0 = min(max(max(__popc(M) - 14, 2 - __popc(E) / 2), 0), min(2, (6 - __popc(E)) / 2));
    x = E | x0 << 8;
    return M | (x0 < 1) << 30 | (x0 < 2) << 31;
}
__device__ __forceinline__ int role(int p, uint32_t x) {
    const int i = (p - 120) >> 1, x0 = x >> 8, side = x >> i & 1, r = __popc((side ? x : ~x) & ((1 << i) - 1)), e0 = 6 - __popc(x & 63);
    const int pair = !side ? (r < 2 * x0 ? r : 4 + r - 2 * x0) : (r < 4 - 2 * x0 ? 2 * x0 + r : e0 + r);
    return 120 + 2 * pair + (p & 1);
}
__device__ __forceinline__ void tma_prefetch(const CUtensorMap* m, int c0, int c1) {
    asm volatile("cp.async.bulk.prefetch.tensor.2d.L2.global [%0, {%1, %2}];" :: "l"(m), "r"(c0), "r"(c1) : "memory");
}

struct Maps { CUtensorMap m[9]; };
__global__ void __launch_bounds__(256, 1)
main_kernel(const __grid_constant__ Maps tm, const bf16* __restrict__ mem0, const __grid_constant__ ConvIn in, const __grid_constant__ MainParams prm) {
    const CUtensorMap &tmWq = tm.m[0], &tmWk = tm.m[1], &tmWv = tm.m[2], &tmWo = tm.m[3], &tmX = tm.m[4], *tmK = tm.m + 5;
    using namespace mk;
    extern __shared__ __align__(1024) uint8_t smem_raw[];
    if (smem_u32(smem_raw) != SB) __trap();
    TL(0); TL(2); TS(0);
    const int tid0 = threadIdx.x, w8 = __shfl_sync(~0u, tid0 >> 5, 0), wg = w8 >> 2;
    const int p = __shfl_sync(~0u, place(prm.by_sm), 0);
    const uint32_t t16 = tid0 * 16, rbhi = (uint32_t)((uintptr_t)prm.rb >> 32);
    int c = p, budget = 1;
    uint32_t W[128], T[64], m0[8], pa, pb, u_rs, u_rl, u_bs, u_bl;
    ConvRaw<2> raw;
    asm volatile("griddepcontrol.launch_dependents;" ::: "memory");
    uint32_t on = opq(DRY ? wg ^ 1 : 1);
    #define PART(L) if (!on) goto START; L:
    #define SYNC() if (on) __syncthreads()
    #define WAIT(mb, ph) if (on) mbar_wait(mb, ph)
    if (!wg) {
        if (w8 == 0 && elect()) {
            for (int i = 0; i < 9; i++) mbar_init(BAR + i * 8, 1);
            asm volatile("fence.mbarrier_init.release.cluster;" ::: "memory");
            asm volatile("fence.proxy.async.shared::cta;" ::: "memory");
            sts32(SUM + 256, 0); sts32(SUM + 268, 0); mbar_arrive(MB_B);
        }
        if (tid0 >= 121) asm volatile("prefetch.tensormap [%0];" :: "l"(tm.m + (127 - tid0)) : "memory");
        __syncwarp();
        publish(prm.rb, p);
    } else {
        if (!c_xd[(tid0 >> 3 & 15) * 6]) g_err = 3;
        __syncwarp();
        if (DRY) switch (p & 7) { case 0: goto P0; case 1: goto P1; case 2: goto P2; case 3: goto P3; case 4: goto P4; case 5: goto P5; case 6: goto P6; default: goto P7; }
    }
START:
    on = opq(1);
    budget = SPIN_LIMIT;
    TS(1);
    if (p >= 120) {
        uint32_t x;
        survey(x, SPIN_LIMIT);
        c = role(p, x);
        TS(2);
        if (c >= 128) { spare(tmK, in, c - 128, prm.zero); TLX(18); return; }
    }
    conv_load<2>(raw, in, p * 4);
    #pragma unroll
    for (int i = 0; i < 8; i++) m0[i] = __ldg((const uint32_t*)(mem0 + i * DM + (c & 1) * 512) + tid0);
    if (tid0 < 16) g_gate[c * 16 + tid0] = -1.f;
    if (w8 == 0 && elect()) {
        if (p < 120) strip_request<2>(tmK, p >> 1);
        mbar_expect(MB_WQ, 65536); mbar_expect(MB_WK, 65536);
        for (int i = 0; i < 2; i++) { tma2d(WO + i * 32768, &tmWq, (c >> 1) * 64, (c & 1) * 512 + i * 256, MB_WQ); tma2d(WV + i * 32768, &tmWk, (c >> 1) * 64, (c & 1) * 512 + i * 256, MB_WK); }
    }
    __syncthreads();
    if (p < 120) mbar_wait(MB_C, 0);
    TS(3);
P0:
    kv_build<2>(raw, p * 4);
    SYNC();
    TS(4);
PART(P1)
    if (w8 == 0 && elect()) {
        mbar_expect(MB_X, 32768); tma3d(XT, &tmX, 0, 32, (c & 1) * 8, MB_X);
        for (int i = 0; i < 4; i++) tma_prefetch(&tmWo, (c & 3) * 256 + i * 64, (c >> 2) * DH);
        for (int i = 0; i < 2; i++) tma_prefetch(&tmWv, (c >> 1) * 64, (c & 1) * 512 + i * 256);
    }
    __syncwarp();
    conv_filter<2>(raw, on);
    SYNC();
    TS(5);
PART(P2)
    conv_mma<2>(p * 4, raw.d, prm.zero, on && p < 120);
    TS(6);
PART(P3)
    asm volatile("fence.proxy.async.shared::cta;" ::: "memory");
    SYNC();
    if (w8 == 0 && elect()) { mbar_expect(MB_KV, 32768); tma3d(TK, &tmX, 0, 0, (c & 1) * 8, MB_KV); }
    #pragma unroll
    for (int i = 0; i < 2; i++) {
        const uint32_t e = i ? 0x7632 : 0x5410;
        sts128(MEM + tid0 * 32 + i * 16, make_uint4(__byte_perm(m0[0], m0[1], e), __byte_perm(m0[2], m0[3], e), __byte_perm(m0[4], m0[5], e), __byte_perm(m0[6], m0[7], e)));
    }
    WAIT(wg ? MB_WK : MB_WQ, 0);
    TS(7);
    load_tile<0, 32>(tile_off(tid0 & 31, 2 * (w8 & 3)) + (wg ? WV : WO), W);
    SYNC();
    TS(8);
    if (w8 == 0 && elect()) {
        mbar_expect(MB_WO, 65536);
        for (int i = 0; i < 4; i++) tma2d(WO + i * 16384, &tmWo, (c & 3) * 256 + i * 64, (c >> 2) * DH, MB_WO);
        mbar_expect(MB_WV, 65536);
        for (int i = 0; i < 2; i++) tma2d(WV + i * 32768, &tmWv, (c >> 1) * 64, (c & 1) * 512 + i * 256, MB_WV);
    }
    __syncwarp();
PART(P4)
    {
        const int lane = tid0 & 31, w = w8 & 3, g = lane >> 2, t = lane & 3;
        auto vec = [](int hf, int gg, int ch) { return hf * 512 + (gg >> 1) * 128 + (gg & 1) * 64 + ((ch ^ (gg >> 1) ^ (hf << 1)) << 4); };
        const int kg = ((lane >> 3) & 1) * 4 + ((lane & 7) >> 1);
        pa = wg ? w * 1024 + vec((lane >> 3) & 1, lane & 7, lane >> 4)
                : ((lane >> 4) * 4096 + w * 1024 + vec(lane & 1, kg, 2 * (w & 1))) | ((lane & 8) * 256 + w * 256 + (lane & 1) * 128 + ((((lane >> 4) ^ (lane & 1)) * 4 + ((lane & 7) >> 1)) << 4)) << 16;
        pb = (wg ? w * 1024 + vec(0, g, t) : t * 4096 + w * 256 + g * 16) | (w * 256 + t * 64 + (g & 3) * 8 + (g >> 2) * 4) << 16;
    }
    #define ST_TOK(o) do { const uint32_t ps = pb & 0xFFFF; TAGM(); pack_tag(acc, u, 1, tm); \
        st_if(on, tok_dst(c, seg, wg) + ((o) + ps), u); st_if(on, tok_dst(c, seg, wg) + ((o) + (ps ^ HI8)), u + 4); } while (0)
    #pragma unroll 1
    for (int seg = on; seg >= 0; seg--) {
        float acc[16];
        uint32_t u[8];
        WAIT(seg ? MB_X : MB_KV, 0);
        wg_run<0, 32>(acc, W, c_xd + (seg ? 0 : 64));
        wg_wait<0>();
        ST_TOK(0);
    }
    TS(9);
PART(P5)
    {
        WAIT(MB_WO, 0);
        TS(10);
        const int lane = tid0 & 31;
        const uint32_t a = (tid0 >> 6) * 16384 + tile_off(lane, (w8 & 1) * 4) + WO;
        #pragma unroll
        for (int i = 0; i < 16; i++) ldsm4t(T[4 * i], T[4 * i + 1], T[4 * i + 2], T[4 * i + 3], ((i & 2) ? a ^ 32 : a) + ((i >> 2) + 4 * (i & 1)) * 2048);
        SYNC();
        const uint32_t d = WO + w8 * 512 + ((lane >> 3) * 4 + (lane & 3)) * 16 + ((lane >> 2) & 1) * 4;
        #pragma unroll
        for (int i = 0; i < 64; i++) sts32_if(on, d + (i >> 2) * 4096 + (i & 1) * 256 + (i & 2) * 4, T[i]);
    }
    TS(11);
    WAIT(MB_WV, 0);
    TS(12);
    load_tile<0, 16>(tile_off(tid0 & 31, 2 * (w8 & 3)) + wg * 32768 + WV, T);
PART(P6)
    #pragma unroll 1
    for (int seg = 0; seg <= on; seg++) {
        float acc[16];
        uint32_t u[8];
        wg_run<0, 16>(acc, T, c_xd + (seg ? 0 : 64) + wg * 16);
        wg_wait<0>();
        const uint32_t x = SC + seg * 4096 + (t16 & 2047);
        if (!wg) { qk_pack(acc, u); sts128(x, make_uint4(u[0], u[1], u[2], u[3])); sts128(x + 2048, make_uint4(u[4], u[5], u[6], u[7])); }
        SYNC();
        if (wg) { lds128u(u, x); lds128u(u + 4, x + 2048); acc_add(acc, u); ST_TOK(16384); }
    }
    TS(13);
PART(P7)
    if (w8 == 1) { bulk_expect(MB_X, 32768); load_x(&tmX, c, 2, XT); }
    {
        const int lane = tid0 & 31, h = c >> 2, j = c & 3;
        uint32_t cl;
        const uint32_t M = survey(cl, budget), below = (1u << h) - 1;
        const int pos = ((M >> h) & 1) ? 32 - __popc(M) + __popc(M & below) : __popc(~M & below), G = pos >> 4, rk = pos & 15;
        auto half = [&](uint32_t off) { return (uint32_t)(uintptr_t)prm.rb + off + ((__popc(off & HOME_BITS) ^ G) & 1) * 4096; };
        auto rpair = [&](int m) { return RB_R + (j << 16) + ((m & 1) << 13) + (((m >> 1) & 3) << 14) + ((m >> 3) << 18); };
        u_rs = (half(rpair(2 * w8)) ^ (G << 12)) + h * 128 + (h & 7) * 16;
        u_rl = half(rpair(rk));
        u_bs = (uint32_t)(uintptr_t)prm.rb + RB_B + ((j & 1) << 13) + ((j >> 1) << 16) + rk * 256 + G * 128 + (w8 & 3) * 32;
        u_bl = half(RB_B + ((c & 1) << 16));
        if (w8 == 0) {
            const char* v0 = kv_src(c, 0) + 16384 + lane * 128 + (lane & 3) * 4;
            do cl = ld_g32(v0) & ld_g32(v0 + 4096) & ld_g32(v0 + 8192) & ld_g32(v0 + 12288); while (__any_sync(~0u, !(cl & 1)) && --budget > 0);
            get_kv(c, 0);
        }
    }
    TS(14);
    WAIT(MB_KV, 1);
    TS(15);
    if (w8 > 4) while (kv_stale(w8 - 5, t16 & 0x1F0, 1) && --budget > 0) refetch_kv(c, 0, w8 - 5, t16 & 0x1F0);
    if (!on) goto START;
    asm volatile("fence.proxy.async.shared::cta;" ::: "memory");
    TS(16); TLX(7);
    __syncwarp();
    const Ctx cx = {u_rs, u_rl, u_bs, u_bl, (uint32_t)(uintptr_t)prm.rb, rbhi, w8, c};
    if (wg) steps<1>(W, T, t16, pa, pb, cx, &tmX, prm); else steps<0>(W, T, t16, pa, pb, cx, &tmX, prm);
    TLX(3);
}

namespace ok {
constexpr int STAGES = 4;
constexpr uint32_t STG = 49152, TOTAL = STAGES * STG + 32768 + 768, NOG = 0xBF800000u;
}
#define R8(o) F4(d, o), F4(d, o + 4)
__device__ __forceinline__ void wgmma_n256_ss_tt(float* d, uint64_t da, uint64_t db, int accum) {
    asm volatile("{.reg .pred p; setp.ne.b32 p, %130, 0;\n"
        "wgmma.mma_async.sync.aligned.m64n256k16.f32.bf16.bf16 {%0,%1,%2,%3,%4,%5,%6,%7,%8,%9,%10,%11,%12,%13,%14,%15,"
        "%16,%17,%18,%19,%20,%21,%22,%23,%24,%25,%26,%27,%28,%29,%30,%31,%32,%33,%34,%35,%36,%37,%38,%39,%40,%41,%42,%43,%44,%45,%46,%47,"
        "%48,%49,%50,%51,%52,%53,%54,%55,%56,%57,%58,%59,%60,%61,%62,%63,%64,%65,%66,%67,%68,%69,%70,%71,%72,%73,%74,%75,%76,%77,%78,%79,"
        "%80,%81,%82,%83,%84,%85,%86,%87,%88,%89,%90,%91,%92,%93,%94,%95,%96,%97,%98,%99,%100,%101,%102,%103,%104,%105,%106,%107,%108,%109,%110,%111,"
        "%112,%113,%114,%115,%116,%117,%118,%119,%120,%121,%122,%123,%124,%125,%126,%127}, %128, %129, p, 1, 1, 1, 1;}"
        : R8(0), R8(8), R8(16), R8(24), R8(32), R8(40), R8(48), R8(56), R8(64), R8(72), R8(80), R8(88), R8(96), R8(104), R8(112), R8(120)
        : "l"(da), "l"(db), "r"(accum));
}
#undef R8
__global__ void __cluster_dims__(2, 1, 1) __launch_bounds__(320, 1)
out_kernel(const __grid_constant__ CUtensorMap tmO, const __grid_constant__ CUtensorMap tmWo, const __grid_constant__ CUtensorMap tmA,
           const __grid_constant__ CUtensorMap tmOut, const __grid_constant__ CUtensorMap tmQ, const bf16* __restrict__ q, const bf16* __restrict__ gate_w) {
    using namespace ok;
    extern __shared__ __align__(1024) uint8_t smem_raw[];
    const uint32_t SB = smem_u32(smem_raw), AT = SB + STAGES * STG, BAR = AT + 32768;
    if (SB & 1023) __trap();
    const int tid = threadIdx.x, w = tid >> 5, lane = tid & 31;
    const int rank = blockIdx.x & 1, mt = blockIdx.x >> 3, nt = (blockIdx.x >> 1) & 3;
    const uint32_t full = BAR, empty = BAR + 64, afull = BAR + 128;
    if (tid == 0) {
        for (int i = 0; i < STAGES; i++) { mbar_init(full + i * 8, 1); mbar_init(empty + i * 8, 8); }
        mbar_init(afull, 2);
        asm volatile("fence.mbarrier_init.release.cluster;" ::: "memory");
    }
    __syncthreads();
    asm volatile("griddepcontrol.wait;" ::: "memory");
    if (blockIdx.x == 0 && tid < 160) g_cls[tid] = 0;
    TL(4);
    if (w >= 8) {
        if (w == 9) {
            uint4 gw[4];
            #pragma unroll
            for (int i = 0; i < 4; i++) gw[i] = __ldg((const uint4*)gate_w + lane + 32 * i);
            #pragma unroll 2
            for (int row = blockIdx.x * 16; row < blockIdx.x * 16 + 16; row++) {
                float a = 0.f;
                #pragma unroll
                for (int i = 0; i < 4; i++) {
                    const uint4 x = __ldg((const uint4*)(q + (size_t)row * DM) + lane + 32 * i);
                    #pragma unroll
                    for (int j = 0; j < 4; j++) { const uint32_t gg = ((const uint32_t*)&gw[i])[j], u = ((const uint32_t*)&x)[j]; a = fmaf(bflo(u), bflo(gg), fmaf(bfhi(u), bfhi(gg), a)); }
                }
                #pragma unroll
                for (int o = 16; o; o >>= 1) a += __shfl_xor_sync(~0u, a, o);
                if (lane == 0) st_g32(g_gate + row, __float_as_uint(1.f / (1.f + __expf(-a))));
            }
            uint32_t x[4];
            int n = 0;
            do ld_g128(x, g_gate + mt * 128 + lane * 4); while ((x[0] == NOG || x[1] == NOG || x[2] == NOG || x[3] == NOG) && ++n < SPIN_LIMIT);
            sts128(BAR + 256 + lane * 16, make_uint4(x[0], x[1], x[2], x[3]));
        } else if (lane == 0) {
            int st = 0, ph = 1;
            for (int kb = 0; kb < 32; kb++) {
                if (kb >= STAGES) mbar_wait(empty + st * 8, ph);
                mbar_expect(full + st * 8, STG);
                tma3d(SB + st * STG, &tmO, 0, (rank * 32 + kb) * 2, mt * 16, full + st * 8);
                tma3d(SB + st * STG + 16384, &tmWo, 0, (rank * 32 + kb) * 64, nt * 4, full + st * 8);
                if (kb == STAGES - 1) { mbar_expect(afull, 32768); tma3d(AT, &tmA, 0, (nt * 2 + rank) * 128, mt * 2, afull); }
                if (kb >> 1 == 4) asm volatile("cp.async.bulk.prefetch.tensor.5d.L2.global [%0, {%1, %2, %2, %2, %3}];" :: "l"(&tmQ), "r"(nt * 256 + rank * 128 + (kb & 1) * 64), "r"(0), "r"(mt * 4) : "memory");
                if (++st == STAGES) { st = 0; ph ^= 1; }
            }
            mbar_wait(empty, ph);
            mbar_expect(afull, 32768);
            for (int hf = 0; hf < 2; hf++)
                asm volatile("cp.async.bulk.tensor.5d.shared::cluster.global.mbarrier::complete_tx::bytes [%0], [%1, {%3, %4, %4, %4, %5}], [%2];"
                    :: "r"(SB + hf * 16384), "l"(&tmQ), "r"(afull), "r"(nt * 256 + rank * 128 + hf * 64), "r"(0), "r"(mt * 4) : "memory");
        }
        __syncwarp();
        asm volatile("barrier.cluster.arrive.aligned; barrier.cluster.wait.aligned;" ::: "memory");
        asm volatile("barrier.cluster.arrive.aligned; barrier.cluster.wait.aligned;" ::: "memory");
    } else {
        const int wg = w >> 2, g = lane >> 2;
        float acc[128];
        int st = 0, ph = 0, pst = 0;
        #pragma unroll 1
        for (int kb = 0; kb < 32; kb++) {
            mbar_wait(full + st * 8, ph);
            const uint64_t da = mkdesc(SB + st * STG + wg * 8192, 128, 1024, 0), db = mkdesc(SB + st * STG + 16384, 8192, 1024, 1);
            wg_fence();
            #pragma unroll
            for (int ks = 0; ks < 4; ks++) wgmma_n256_ss_tt(acc, da + ks * 16, db + ks * 128, (kb | ks) != 0);
            wg_commit();
            wg_wait<1>();
            if (kb > 0 && lane == 0) mbar_arrive(empty + pst * 8);
            pst = st;
            if (++st == STAGES) { st = 0; ph ^= 1; }
        }
        wg_wait<0>();
        TLX(12);
        asm volatile("barrier.cluster.arrive.aligned; barrier.cluster.wait.aligned;" ::: "memory");
        uint32_t peer;
        asm volatile("mapa.shared::cluster.u32 %0, %1, %2;" : "=r"(peer) : "r"(SB + 65536 + tid * 16), "r"(rank ^ 1));
        #define SND(e) pack2(rank ? acc[8 * i + (e)] : acc[64 + 8 * i + (e)], rank ? acc[8 * i + (e) + 1] : acc[65 + 8 * i + (e)])
        #pragma unroll
        for (int i = 0; i < 8; i++)
            asm volatile("st.shared::cluster.v4.b32 [%0], {%1,%2,%3,%4};" :: "r"(peer + i * 4096), "r"(SND(0)), "r"(SND(2)), "r"(SND(4)), "r"(SND(6)) : "memory");
        #undef SND
        asm volatile("barrier.cluster.arrive.aligned; barrier.cluster.wait.aligned;" ::: "memory");
        mbar_wait(afull, 0);
        const uint32_t ga = BAR + 256 + (32 * (w >> 1) + 8 * (g >> 1) + 4 * (w & 1) + (g & 1)) * 4;
        const float g0 = __uint_as_float(lds32(ga)), g1 = __uint_as_float(lds32(ga + 8)), h0 = 1.f - g0, h1 = 1.f - g1;
        const uint32_t la = AT + wg * 16384 + ((lane >> 4) * 8 + (lane & 7)) * 128 + ((((w & 3) * 2 + ((lane >> 3) & 1)) ^ (lane & 7)) << 4);
        const uint32_t ra = SB + (w * 16 + (lane & 15)) * 128;
        #pragma unroll
        for (int i = 0; i < 8; i++) {
            const uint32_t a = ra + (i >> 2) * 16384 + ((((i & 3) * 2 + (lane >> 4)) ^ (lane & 7)) << 4);
            uint32_t r0, r1, r2, r3, x0, x1, x2, x3;
            ldsm4t(r0, r1, r2, r3, la + i * 2048);
            ldsm4(x0, x1, x2, x3, a);
            const uint4 u = lds128(SB + 65536 + tid * 16 + i * 4096);
            float p[8];
            #pragma unroll
            for (int e = 0; e < 8; e++) { const uint32_t x = ((const uint32_t*)&u)[e >> 1]; p[e] = (rank ? acc[64 + 8 * i + e] : acc[8 * i + e]) + ((e & 1) ? bfhi(x) : bflo(x)); }
            #define MIX(g, h, r, x, e) pack2(fmaf(g * bflo(x), bflo(r), h * p[e]), fmaf(g * bfhi(x), bfhi(r), h * p[e + 1]))
            stsm4(a, MIX(g0, h0, r0, x0, 0), MIX(g1, h1, r1, x1, 2), MIX(g0, h0, r2, x2, 4), MIX(g1, h1, r3, x3, 6));
        }
        asm volatile("fence.proxy.async.shared::cta;" ::: "memory");
        bsync<1, 256>();
        if (tid == 0) {
            for (int hf = 0; hf < 2; hf++)
                asm volatile("cp.async.bulk.tensor.5d.global.shared::cta.bulk_group [%0, {%2, %3, %3, %3, %4}], [%1];"
                    :: "l"(&tmOut), "r"(SB + hf * 16384), "r"(nt * 256 + rank * 128 + hf * 64), "r"(0), "r"(mt * 4) : "memory");
            asm volatile("cp.async.bulk.commit_group;" ::: "memory");
            asm volatile("cp.async.bulk.wait_group 0;" ::: "memory");
        }
        TL(5);
    }
}

typedef CUresult (*EncodeFn)(CUtensorMap*, CUtensorMapDataType, cuuint32_t, void*, const cuuint64_t*, const cuuint64_t*, const cuuint32_t*,
                             const cuuint32_t*, CUtensorMapInterleave, CUtensorMapSwizzle, CUtensorMapL2promotion, CUtensorMapFloatOOBfill);
static void enc(EncodeFn fn, CUtensorMap* m, void* base, int rank, const cuuint64_t* dims, const cuuint64_t* strides, const cuuint32_t* box, CUtensorMapSwizzle sw) {
    cuuint32_t es[5] = {1, 1, 1, 1, 1};
    fn(m, CU_TENSOR_MAP_DATA_TYPE_BFLOAT16, rank, base, dims, strides, box, es, CU_TENSOR_MAP_INTERLEAVE_NONE, sw,
       CU_TENSOR_MAP_L2_PROMOTION_L2_128B, CU_TENSOR_MAP_FLOAT_OOB_FILL_NONE);
}
static MainParams h_prm = {{768, 576, 512, 0, 0, 0, 0, 0, 0, 0, 0, 0}, 0, 1, nullptr, nullptr};

extern "C" void kernel_launch(void* const* d_in, const int* in_sizes, int n_in, void* d_out, int out_size) {
    const bf16* q = (const bf16*)d_in[0];
    const bf16* shift_k = (const bf16*)d_in[3];
    const bf16* ssm_k = (const bf16*)d_in[4];
    const bf16* ssm_D = (const bf16*)d_in[5];
    const bf16* mem0 = (const bf16*)d_in[7];
    const bf16* gate_w = (const bf16*)d_in[13];

    static EncodeFn fn = nullptr;
    static void* pO = nullptr;
    static void* pA = nullptr;
    if (!fn) {
        cudaDriverEntryPointQueryResult qr;
        cudaGetDriverEntryPoint("cuTensorMapEncodeTiled", (void**)&fn, cudaEnableDefault, &qr);
        cudaGetSymbolAddress(&pO, g_O);
        cudaGetSymbolAddress(&pA, g_Y);
        void* pRB; cudaGetSymbolAddress(&pRB, g_RB);
        h_prm.rb = (char*)(((uintptr_t)pRB + (4u << 20) - 1) & ~(uintptr_t)((4u << 20) - 1));
        int dev, sms; cudaGetDevice(&dev); cudaDeviceGetAttribute(&sms, cudaDevAttrMultiProcessorCount, dev);
        h_prm.by_sm = sms == NCTA;
        cudaFuncSetAttribute(main_kernel, cudaFuncAttributeMaxDynamicSharedMemorySize, mk::TOTAL);
        cudaFuncSetAttribute(out_kernel, cudaFuncAttributeMaxDynamicSharedMemorySize, ok::TOTAL);
    }
    Maps mm;
    CUtensorMap &mWq = mm.m[0], &mWk = mm.m[1], &mWv = mm.m[2], &mWo = mm.m[3], &mX = mm.m[4], mO, mWo2, mA, mOut, mQ;
    {
        cuuint64_t d[2] = {4096, 1024}, s[1] = {8192}; cuuint32_t b[2] = {64, 256};
        enc(fn, &mWq, d_in[8], 2, d, s, b, CU_TENSOR_MAP_SWIZZLE_128B);
        enc(fn, &mWk, d_in[9], 2, d, s, b, CU_TENSOR_MAP_SWIZZLE_128B);
        enc(fn, &mWv, d_in[10], 2, d, s, b, CU_TENSOR_MAP_SWIZZLE_128B);
    }
    {
        cuuint64_t d[2] = {1024, 4096}, s[1] = {2048}; cuuint32_t b[2] = {64, 128};
        enc(fn, &mWo, d_in[11], 2, d, s, b, CU_TENSOR_MAP_SWIZZLE_128B);
        cuuint64_t d2[3] = {64, 4096, 16}, s2[2] = {2048, 128}; cuuint32_t b2[3] = {64, 64, 4};
        enc(fn, &mWo2, d_in[11], 3, d2, s2, b2, CU_TENSOR_MAP_SWIZZLE_128B);
    }
    {
        cuuint64_t d[3] = {64, 2048, 16}, s[2] = {2048, 128}; cuuint32_t b[3] = {64, 32, 8};
        enc(fn, &mX, d_in[0], 3, d, s, b, CU_TENSOR_MAP_SWIZZLE_128B);
    }
    {
        cuuint64_t d[3] = {256, 128, 256}, s[2] = {512, 65536}; cuuint32_t b[3] = {256, 2, 16};
        enc(fn, &mO, pO, 3, d, s, b, CU_TENSOR_MAP_SWIZZLE_NONE);
    }
    {
        cuuint64_t d[5] = {1024, 2, 4, 4, 64}, s[4] = {2048, 16384, 4096, 65536}; cuuint32_t b[5] = {64, 2, 4, 4, 4};
        cuuint64_t da[3] = {64, 1024, 32}, sa[2] = {4096, 128}; cuuint32_t ba[3] = {64, 128, 2};
        enc(fn, &mA, pA, 3, da, sa, ba, CU_TENSOR_MAP_SWIZZLE_128B);
        enc(fn, &mQ, d_in[0], 5, d, s, b, CU_TENSOR_MAP_SWIZZLE_128B);
        enc(fn, &mOut, d_out, 5, d, s, b, CU_TENSOR_MAP_SWIZZLE_128B);
    }
    {
        cuuint64_t d[3] = {1024, 256, 8}, s[2] = {16384, 2048}; cuuint32_t b[3] = {8, 256, 1};
        for (int i = 0; i < 4; i++) { b[2] = i < 2 ? 1 : 8; enc(fn, &mm.m[5 + i], d_in[1 + (i & 1)], 3, d, s, b, CU_TENSOR_MAP_SWIZZLE_NONE); }
    }
    cudaStream_t st = cudaStreamPerThread;
    cudaLaunchAttribute at[1];
    at[0].id = cudaLaunchAttributeProgrammaticStreamSerialization;
    at[0].val.programmaticStreamSerializationAllowed = 1;
    cudaLaunchConfig_t cfg = {};
    cfg.stream = st; cfg.attrs = at;
    cfg.gridDim = dim3(NCTA); cfg.blockDim = dim3(256); cfg.dynamicSmemBytes = mk::TOTAL;
    h_prm.x = (const char*)q;
    const ConvIn cin = {shift_k, ssm_k, ssm_D};
    cudaLaunchKernelEx(&cfg, main_kernel, mm, mem0, cin, h_prm);
    cfg.numAttrs = PDL;
    cfg.gridDim = dim3(128); cfg.blockDim = dim3(320); cfg.dynamicSmemBytes = ok::TOTAL;
    cudaLaunchKernelEx(&cfg, out_kernel, mO, mWo2, mA, mOut, mQ, q, gate_w);
}
```
